```python
import torch

def _softmax(x, axis=-1):
    return torch.softmax(x, dim=axis)
def _gelu(x):
    return torch.nn.functional.gelu(x, approximate="tanh")
def _silu(x):
    return torch.nn.functional.silu(x)
def _sigmoid(x):
    return torch.sigmoid(x)
def _layernorm(x, axis=-1, eps=1e-5):
    m = x.mean(dim=axis, keepdim=True)
    v = x.var(dim=axis, keepdim=True, unbiased=False)
    return (x - m) / torch.sqrt(v + eps)
def _scatter_add(tgt, idx, src, axis=0):
    return tgt.clone().index_add_(axis, idx, src)
def _segment_sum(src, seg, n):
    out = torch.zeros((n,) + src.shape[1:], dtype=src.dtype)
    return out.index_add_(0, seg, src)
def _pad(x, pw):
    flat = tuple(v for pair in reversed(pw) for v in pair)
    return torch.nn.functional.pad(x, flat)

kernel_name = 'recurrent_scan__mha_block_cached__moe_arch_mod__prompt'

def setup_inputs():

    _w = (lambda a: (lambda t: t.to(torch.bfloat16) if t.is_floating_point() else t)(torch.as_tensor(a)))
    def _A_setup():
        B, Sq, D = 1, 2048, 640
        H, Sk, Dh = 32, 2048, 128
        return {
            "x": _w((lambda *s: torch.randn(*s, dtype=torch.bfloat16) * 0.05)(B, Sq, D)),
            "k_cache": _w((lambda *s: torch.randn(*s, dtype=torch.bfloat16) * 1.6)(B, H, Sk, Dh)),
            "v_cache": _w((lambda *s: torch.randn(*s, dtype=torch.bfloat16) * 0.2)(B, H, Sk, Dh)),
            "wq": _w((lambda *s: torch.randn(*s, dtype=torch.bfloat16) * 1.6)(D, H * Dh) * (D ** -0.5)),
            "wo": _w((lambda *s: torch.randn(*s, dtype=torch.bfloat16) * 0.2)(H * Dh, D) * ((H * Dh) ** -0.5)),
        }
    _A_in = _A_setup()

    def _B_setup():
        B, S, D, F, C = 1, 2048, 640, 1728, 8
        return {
            "x": _w((lambda *s: torch.randn(*s, dtype=torch.bfloat16) * 0.05)(B, S, D)),
            "w_r": _w((lambda *s: torch.randn(*s, dtype=torch.bfloat16) * 0.2)(D)),
            "w_gate": _w((lambda *s: torch.randn(*s, dtype=torch.bfloat16) * 0.1)(D, F)),
            "w_up": _w((lambda *s: torch.randn(*s, dtype=torch.bfloat16) * 0.1)(D, F)),
            "w_down": _w((lambda *s: torch.randn(*s, dtype=torch.bfloat16) * 0.1)(F, D)),
        }
    _B_in = _B_setup()

    return {
        "A_x": _A_in["x"],
        "A_k_cache": _A_in["k_cache"],
        "A_v_cache": _A_in["v_cache"],
        "A_wq": _A_in["wq"],
        "A_wo": _A_in["wo"],
        "B_x": _B_in["x"],
        "B_w_r": _B_in["w_r"],
        "B_w_gate": _B_in["w_gate"],
        "B_w_up": _B_in["w_up"],
        "B_w_down": _B_in["w_down"],
    }

def reference(A_x, A_k_cache, A_v_cache, A_wq, A_wo, B_x, B_w_r, B_w_gate, B_w_up, B_w_down):
    def _A_ref(x, k_cache, v_cache, wq, wo):
        B, Sq, D = x.shape
        H, Dh = 32, 128
        q = (lambda x, *d: x.permute(*d))((x @ wq).reshape(B, Sq, H, Dh), 0, 2, 1, 3)
        scores = torch.einsum("bhqd,bhkd->bhqk", q, k_cache) * (Dh ** -0.5)
        p = _softmax(scores, axis=-1)
        o = torch.einsum("bhqk,bhkd->bhqd", p, v_cache)
        return (lambda x, *d: x.permute(*d))(o, 0, 2, 1, 3).reshape(B, Sq, H * Dh) @ wo

    def _B_ref(x, w_r, w_gate, w_up, w_down):
        B, S, D = x.shape
        C = 8
        r = x @ w_r
        idx = torch.argsort(-r, axis=-1)[:, :C]
        idx_e = (lambda x, n, axis: torch.repeat_interleave(x, n, dim=axis))(idx.reshape(B, C, 1), D, axis=2)
        x_sel = (lambda x, i, axis: torch.take_along_dim(x, i, dim=axis))(x, idx_e, axis=1)
        g = _silu(x_sel @ w_gate)
        u = x_sel @ w_up
        y = (g * u) @ w_down
        r_sel = _sigmoid((lambda x, i, axis: torch.take_along_dim(x, i, dim=axis))(r, idx, axis=1))
        y = y * r_sel.reshape(B, C, 1)
        b_off = (torch.arange(B) * S).reshape(B, 1)
        flat_idx = (idx + b_off).reshape(B * C)
        zero = (x * 0.0).reshape(B * S, D)
        upd = _scatter_add(zero, flat_idx, y.reshape(B * C, D), axis=0)
        return x + upd.reshape(B, S, D)

    x = A_x
    xn = _layernorm(x, axis=-1)
    s = _A_ref(xn, A_k_cache, A_v_cache, A_wq, A_wo)
    g = _silu(_B_ref(xn, B_w_r, B_w_gate, B_w_up, B_w_down))
    return x + s * g
```

```cpp
#include <cuda_runtime.h>
#include <cuda_bf16.h>
#include <cuda.h>
#include <stdint.h>

#define C_EARLY 6
#define MAXPOLL (1 << 24)
#define SKEW0 16
#define SKEW1 16
#define DPOS 28
#define DPOSF 12
#define KVPF 4
#define ETEST 1
#define AUXW 0
#define WPF 0
namespace {

constexpr int S_LEN = 2048, DM = 640, NH = 32, DH = 128, FF = 1728, TOPC = 8;
constexpr float SCALE_LOG2E = 0.08838834764831845f * 1.4426950408889634f;

struct alignas(128) Cnt { unsigned v; unsigned pad[31]; };
struct Scratch {
  uint4 part[16 * 10 * 8 * 1024];
  __nv_bfloat16 gate[S_LEN * DM];
  uint32_t stat[S_LEN];
  uint32_t cs[NH * DH];
  uint32_t prog[16 * 32];
  float ypart[4 * TOPC * DM];
  uint2 top[32];
  Cnt cnt_mod, mod_done;
  unsigned long long ticket;
};
__device__ Scratch g_s;

__device__ __forceinline__ uint32_t smem_u32(const void* p) { return (uint32_t)__cvta_generic_to_shared(p); }
__device__ __forceinline__ void mbar_init(uint32_t bar, uint32_t cnt) { asm volatile("mbarrier.init.shared::cta.b64 [%0], %1;" :: "r"(bar), "r"(cnt) : "memory"); }
__device__ __forceinline__ void mbar_expect_tx(uint32_t bar, uint32_t bytes) { asm volatile("mbarrier.arrive.expect_tx.shared::cta.b64 _, [%0], %1;" :: "r"(bar), "r"(bytes) : "memory"); }
__device__ __forceinline__ void mbar_arrive(uint32_t bar) { asm volatile("mbarrier.arrive.shared::cta.b64 _, [%0];" :: "r"(bar) : "memory"); }
__device__ __forceinline__ uint32_t map_cta(uint32_t a, uint32_t cta) { uint32_t r; asm volatile("mapa.shared::cluster.u32 %0, %1, %2;" : "=r"(r) : "r"(a), "r"(cta)); return r; }
__device__ __forceinline__ void mbar_arrive_cluster(uint32_t bar) { asm volatile("mbarrier.arrive.shared::cluster.b64 _, [%0];" :: "r"(bar) : "memory"); }
__device__ __forceinline__ void mbar_wait(uint32_t bar, uint32_t parity) {
  asm volatile("{\n.reg .pred p;\n.reg .u32 c;\nmbarrier.try_wait.parity.shared::cta.b64 p, [%0], %1;\n@p bra LAB_DONE;\nmov.u32 c, 0;\n"
               "LAB_WAIT:\nmbarrier.try_wait.parity.shared::cta.b64 p, [%0], %1;\n@p bra LAB_DONE;\nadd.u32 c, c, 1;\nsetp.lt.u32 p, c, 16777216;\n@p bra LAB_WAIT;\ntrap;\nLAB_DONE:\n}\n" :: "r"(bar), "r"(parity) : "memory"); }
__device__ __forceinline__ bool mbar_test2(uint32_t bar0, uint32_t par0, uint32_t bar1, uint32_t par1) { uint32_t r;
  asm volatile("{\n.reg .pred p, q;\nmbarrier.test_wait.parity.shared::cta.b64 p, [%1], %2;\nmbarrier.test_wait.parity.shared::cta.b64 q, [%3], %4;\nand.pred p, p, q;\nselp.u32 %0, 1, 0, p;\n}\n"
               : "=r"(r) : "r"(bar0), "r"(par0), "r"(bar1), "r"(par1) : "memory"); return r; }
__device__ __forceinline__ void mbar_pace(uint32_t bar, uint32_t parity) {
  asm volatile("{\n.reg .pred p;\n.reg .u32 c;\nmov.u32 c, 0;\nLAB_WAIT:\nmbarrier.try_wait.parity.shared::cta.b64 p, [%0], %1;\n@p bra LAB_DONE;\n"
               "add.u32 c, c, 1;\nsetp.lt.u32 p, c, 4096;\n@p bra LAB_WAIT;\nLAB_DONE:\n}\n" :: "r"(bar), "r"(parity) : "memory"); }
__device__ __forceinline__ void flag_wait(const unsigned* p, unsigned target) {
  asm volatile("{\n.reg .pred p;\n.reg .u32 c, v;\nmov.u32 c, 0;\nLAB_WAIT:\nld.acquire.gpu.global.u32 v, [%0];\nsub.u32 v, v, %1;\nsetp.ge.s32 p, v, 0;\n@p bra LAB_DONE;\n"
               "nanosleep.u32 1000;\nadd.u32 c, c, 1;\nsetp.lt.u32 p, c, 8388608;\n@p bra LAB_WAIT;\ntrap;\nLAB_DONE:\n}\n" :: "l"(p), "r"(target) : "memory"); }
__device__ __forceinline__ void flag_add_release(unsigned* p) { asm volatile("fence.acq_rel.gpu;\nred.relaxed.gpu.global.add.u32 [%0], 1;" :: "l"(p) : "memory"); }
__device__ __forceinline__ void tma_load_2d(uint32_t dst, const CUtensorMap* tm, uint32_t bar, int c0, int c1) {
  asm volatile("cp.async.bulk.tensor.2d.shared::cluster.global.mbarrier::complete_tx::bytes [%0], [%1, {%3, %4}], [%2];"
    :: "r"(dst), "l"(tm), "r"(bar), "r"(c0), "r"(c1) : "memory"); }
__device__ __forceinline__ void tma_load_2d_mc(uint32_t dst, const CUtensorMap* tm, uint32_t bar, int c0, int c1) {
  asm volatile("cp.async.bulk.tensor.2d.shared::cluster.global.mbarrier::complete_tx::bytes.multicast::cluster [%0], [%1, {%3, %4}], [%2], %5;"
    :: "r"(dst), "l"(tm), "r"(bar), "r"(c0), "r"(c1), "h"((uint16_t)3) : "memory"); }
__device__ __forceinline__ void tma_load_3d_mc(uint32_t dst, const CUtensorMap* tm, uint32_t bar, int c0, int c1, int c2) {
  asm volatile("cp.async.bulk.tensor.3d.shared::cluster.global.mbarrier::complete_tx::bytes.multicast::cluster [%0], [%1, {%3, %4, %5}], [%2], %6;"
    :: "r"(dst), "l"(tm), "r"(bar), "r"(c0), "r"(c1), "r"(c2), "h"((uint16_t)3) : "memory"); }
__device__ __forceinline__ void l2_prefetch(const void* p, uint32_t bytes) { asm volatile("cp.async.bulk.prefetch.L2.global [%0], %1;" :: "l"(p), "r"(bytes) : "memory"); }
__device__ __forceinline__ void l2_prefetch_line(const void* p) { asm volatile("prefetch.global.L2 [%0];" :: "l"(p) : "memory"); }
__device__ __forceinline__ void wg_fence() { asm volatile("wgmma.fence.sync.aligned;" ::: "memory"); }
__device__ __forceinline__ void wg_commit() { asm volatile("wgmma.commit_group.sync.aligned;" ::: "memory"); }
template <int N> __device__ __forceinline__ void wg_wait() { asm volatile("wgmma.wait_group.sync.aligned %0;" :: "n"(N) : "memory"); }
__device__ __forceinline__ void bar_sync(int id, int n) { asm volatile("bar.sync %0, %1;" :: "r"(id), "r"(n) : "memory"); }
__device__ __forceinline__ void bar_arrive(int id, int n) { asm volatile("bar.arrive %0, %1;" :: "r"(id), "r"(n) : "memory"); }
__device__ __forceinline__ bool bar_any(int id, int n, uint32_t v) { uint32_t r;
  asm volatile("{\n.reg .pred p;\nsetp.ne.u32 p, %3, 0;\nbar.red.or.pred p, %1, %2, p;\nselp.u32 %0, 1, 0, p;\n}\n" : "=r"(r) : "r"(id), "r"(n), "r"(v) : "memory"); return r; }
__device__ __forceinline__ bool elect_one() { uint32_t r; asm volatile("{\n.reg .pred p;\nelect.sync _|p, 0xffffffff;\nselp.u32 %0, 1, 0, p;\n}\n" : "=r"(r)); return r; }
__device__ __forceinline__ void cluster_arrive() { asm volatile("barrier.cluster.arrive.relaxed.aligned;" ::: "memory"); }
__device__ __forceinline__ void cluster_wait() { asm volatile("barrier.cluster.wait.aligned;" ::: "memory"); }
__device__ __forceinline__ void proxy_fence() { asm volatile("fence.proxy.async.shared::cta;" ::: "memory"); }
__device__ __forceinline__ uint32_t pack_bf16(float lo, float hi) { uint32_t r; asm("cvt.rn.bf16x2.f32 %0, %1, %2;" : "=r"(r) : "f"(hi), "f"(lo)); return r; }
__device__ __forceinline__ float bf_lo(uint32_t v) { return __uint_as_float(v << 16); }
__device__ __forceinline__ float bf_hi(uint32_t v) { return __uint_as_float(v & 0xffff0000u); }
__device__ __forceinline__ float rbf(float x) { return __bfloat162float(__float2bfloat16_rn(x)); }
__device__ __forceinline__ float ex2(float x) { float y; asm("ex2.approx.ftz.f32 %0, %1;" : "=f"(y) : "f"(x)); return y; }
__device__ __forceinline__ uint32_t lds32(uint32_t a) { uint32_t v; asm volatile("ld.shared.u32 %0, [%1];" : "=r"(v) : "r"(a) : "memory"); return v; }
__device__ __forceinline__ void sts32(uint32_t a, uint32_t v) { asm volatile("st.shared.u32 [%0], %1;" :: "r"(a), "r"(v) : "memory"); }
__device__ __forceinline__ uint4 lds128(uint32_t a) { uint4 v; asm volatile("ld.shared.v4.u32 {%0,%1,%2,%3}, [%4];" : "=r"(v.x), "=r"(v.y), "=r"(v.z), "=r"(v.w) : "r"(a) : "memory"); return v; }
__device__ __forceinline__ void sts128(uint32_t a, uint32_t x, uint32_t y, uint32_t z, uint32_t w) { asm volatile("st.shared.v4.u32 [%0], {%1,%2,%3,%4};" :: "r"(a), "r"(x), "r"(y), "r"(z), "r"(w) : "memory"); }
__device__ __forceinline__ void st_tagged(uint4* p, uint32_t x, uint32_t y, uint32_t z, uint32_t w) {
  asm volatile("st.relaxed.gpu.global.v4.u32 [%0], {%1,%2,%3,%4};" :: "l"(p), "r"(x), "r"(y), "r"(z), "r"(w) : "memory"); }
__device__ __forceinline__ uint4 ld_tagged(const uint4* p) { uint4 v;
  asm volatile("{\n.reg .b128 v;\nld.relaxed.gpu.global.b128 v, [%4];\nmov.b128 {%0,%1,%2,%3}, v;\n}\n" : "=r"(v.x), "=r"(v.y), "=r"(v.z), "=r"(v.w) : "l"(p) : "memory"); return v; }
__device__ __forceinline__ uint4 ld_relaxed4(const void* p) { uint4 v;
  asm volatile("ld.relaxed.gpu.global.v4.u32 {%0,%1,%2,%3}, [%4];" : "=r"(v.x), "=r"(v.y), "=r"(v.z), "=r"(v.w) : "l"(p) : "memory"); return v; }
__device__ __forceinline__ uint4 ldg_nc(const void* p) { uint4 v;
  asm volatile("ld.global.nc.L1::no_allocate.v4.u32 {%0,%1,%2,%3}, [%4];" : "=r"(v.x), "=r"(v.y), "=r"(v.z), "=r"(v.w) : "l"(p) : "memory"); return v; }
__device__ __forceinline__ uint32_t ldg32(const void* p) { uint32_t v; asm volatile("ld.relaxed.gpu.global.u32 %0, [%1];" : "=r"(v) : "l"(p) : "memory"); return v; }
__device__ __forceinline__ void st_relaxed(uint32_t* p, uint32_t v) { asm volatile("st.relaxed.gpu.global.u32 [%0], %1;" :: "l"(p), "r"(v) : "memory"); }
__device__ __forceinline__ uint32_t mul_bf2(uint32_t a, uint32_t b) { uint32_t r; asm("mul.rn.bf16x2 %0, %1, %2;" : "=r"(r) : "r"(a), "r"(b)); return r; }
__device__ __forceinline__ uint32_t add_bf2(uint32_t a, uint32_t b) { uint32_t r; asm("add.rn.bf16x2 %0, %1, %2;" : "=r"(r) : "r"(a), "r"(b)); return r; }
__device__ __forceinline__ uint32_t sub_bf2(uint32_t a, uint32_t b) { uint32_t r; asm("sub.rn.bf16x2 %0, %1, %2;" : "=r"(r) : "r"(a), "r"(b)); return r; }
__device__ __forceinline__ void stsm4(uint32_t a, uint32_t r0, uint32_t r1, uint32_t r2, uint32_t r3) {
  asm volatile("stmatrix.sync.aligned.m8n8.x4.shared.b16 [%0], {%1,%2,%3,%4};" :: "r"(a), "r"(r0), "r"(r1), "r"(r2), "r"(r3) : "memory"); }
__device__ __forceinline__ void stsm4t(uint32_t a, uint32_t r0, uint32_t r1, uint32_t r2, uint32_t r3) {
  asm volatile("stmatrix.sync.aligned.m8n8.x4.trans.shared.b16 [%0], {%1,%2,%3,%4};" :: "r"(a), "r"(r0), "r"(r1), "r"(r2), "r"(r3) : "memory"); }
__device__ __forceinline__ uint32_t movm_t(uint32_t a) { uint32_t d; asm volatile("movmatrix.sync.aligned.m8n8.trans.b16 %0, %1;" : "=r"(d) : "r"(a)); return d; }
__device__ __forceinline__ uint32_t tag_miss(uint32_t a, uint32_t b, uint32_t tm) { uint32_t d; asm("lop3.b32 %0, %1, %2, %3, 0x7E;" : "=r"(d) : "r"(a), "r"(b), "r"(tm)); return d; }
template <int R> __device__ __forceinline__ void fence_regs(float (&d)[R]) {
  #pragma unroll
  for (int i = 0; i < R; i++) asm volatile("" : "+f"(d[i]) :: "memory"); }
template <int R> __device__ __forceinline__ void fence_regs(uint32_t (&d)[R]) {
  #pragma unroll
  for (int i = 0; i < R; i++) asm volatile("" : "+r"(d[i]) :: "memory"); }
__device__ __forceinline__ uint32_t desc_lo(uint32_t addr, uint32_t lbo_bytes) { return ((addr & 0x3FFFF) >> 4) | ((lbo_bytes >> 4) << 16); }
__device__ __forceinline__ uint64_t desc(uint32_t sb, uint32_t var = 0) {
  uint64_t d; asm("mov.b64 %0, {%1, %2};" : "=l"(d) : "r"(desc_lo(sb, 0) + var), "r"(0x40000040u)); return d; }
__host__ __device__ constexpr int doff(uint32_t off, uint32_t lbo_bytes) { return (off >> 4) | ((lbo_bytes >> 4) << 16); }
__device__ __forceinline__ float rcp_approx(float x) { float y; asm("rcp.approx.f32 %0, %1;" : "=f"(y) : "f"(x)); return y; }
__device__ __forceinline__ float rcp_fast(float x) { float y; asm("rcp.approx.ftz.f32 %0, %1;" : "=f"(y) : "f"(x)); return y; }
__device__ __forceinline__ float sqrt_approx(float x) { float y; asm("sqrt.approx.f32 %0, %1;" : "=f"(y) : "f"(x)); return y; }
__device__ __forceinline__ float sigmoid_f(float z) { return rcp_fast(1.f + ex2(z * -1.4426950408889634f)); }
__device__ __forceinline__ uint32_t norm2(uint32_t x, uint32_t mean2, float rsd) { const uint32_t d = sub_bf2(x, mean2); return pack_bf16(bf_lo(d) * rsd, bf_hi(d) * rsd); }
#define TRACE(w, i)
#define TRACE1(w, i)
#define TRACEF(m, w, i)

template <int OA, int OB> __device__ __forceinline__ void wgmma_ss_n256_tb(float (&d)[128], uint64_t da, uint64_t db, int sd) {
  asm volatile("{\n.reg .pred p;\n.reg .b64 a, b;\nadd.s64 a, %128, %131;\nadd.s64 b, %129, %132;\nsetp.ne.b32 p, %130, 0;\n"
    "wgmma.mma_async.sync.aligned.m64n256k16.f32.bf16.bf16 {%0, %1, %2, %3, %4, %5, %6, %7, %8, %9, %10, %11, %12, %13, %14, %15, %16, %17, %18, %19, %20, %21, %22, %23, %24, %25, %26, %27, %28, %29, %30, %31, %32, %33, %34, %35, %36, %37, %38, %39, %40, %41, %42, %43, %44, %45, %46, %47, %48, %49, %50, %51, %52, %53, %54, %55, %56, %57, %58, %59, %60, %61, %62, %63, %64, %65, %66, %67, %68, %69, %70, %71, %72, %73, %74, %75, %76, %77, %78, %79, %80, %81, %82, %83, %84, %85, %86, %87, %88, %89, %90, %91, %92, %93, %94, %95, %96, %97, %98, %99, %100, %101, %102, %103, %104, %105, %106, %107, %108, %109, %110, %111, %112, %113, %114, %115, %116, %117, %118, %119, %120, %121, %122, %123, %124, %125, %126, %127}, a, b, p, 1, 1, 0, 1;\n}\n"
    : "+f"(d[0]), "+f"(d[1]), "+f"(d[2]), "+f"(d[3]), "+f"(d[4]), "+f"(d[5]), "+f"(d[6]), "+f"(d[7]), "+f"(d[8]), "+f"(d[9]), "+f"(d[10]), "+f"(d[11]), "+f"(d[12]), "+f"(d[13]), "+f"(d[14]), "+f"(d[15]), "+f"(d[16]), "+f"(d[17]), "+f"(d[18]), "+f"(d[19]), "+f"(d[20]), "+f"(d[21]), "+f"(d[22]), "+f"(d[23]), "+f"(d[24]), "+f"(d[25]), "+f"(d[26]), "+f"(d[27]), "+f"(d[28]), "+f"(d[29]), "+f"(d[30]), "+f"(d[31]), "+f"(d[32]), "+f"(d[33]), "+f"(d[34]), "+f"(d[35]), "+f"(d[36]), "+f"(d[37]), "+f"(d[38]), "+f"(d[39]), "+f"(d[40]), "+f"(d[41]), "+f"(d[42]), "+f"(d[43]), "+f"(d[44]), "+f"(d[45]), "+f"(d[46]), "+f"(d[47]), "+f"(d[48]), "+f"(d[49]), "+f"(d[50]), "+f"(d[51]), "+f"(d[52]), "+f"(d[53]), "+f"(d[54]), "+f"(d[55]), "+f"(d[56]), "+f"(d[57]), "+f"(d[58]), "+f"(d[59]), "+f"(d[60]), "+f"(d[61]), "+f"(d[62]), "+f"(d[63]), "+f"(d[64]), "+f"(d[65]), "+f"(d[66]), "+f"(d[67]), "+f"(d[68]), "+f"(d[69]), "+f"(d[70]), "+f"(d[71]), "+f"(d[72]), "+f"(d[73]), "+f"(d[74]), "+f"(d[75]), "+f"(d[76]), "+f"(d[77]), "+f"(d[78]), "+f"(d[79]), "+f"(d[80]), "+f"(d[81]), "+f"(d[82]), "+f"(d[83]), "+f"(d[84]), "+f"(d[85]), "+f"(d[86]), "+f"(d[87]), "+f"(d[88]), "+f"(d[89]), "+f"(d[90]), "+f"(d[91]), "+f"(d[92]), "+f"(d[93]), "+f"(d[94]), "+f"(d[95]), "+f"(d[96]), "+f"(d[97]), "+f"(d[98]), "+f"(d[99]), "+f"(d[100]), "+f"(d[101]), "+f"(d[102]), "+f"(d[103]), "+f"(d[104]), "+f"(d[105]), "+f"(d[106]), "+f"(d[107]), "+f"(d[108]), "+f"(d[109]), "+f"(d[110]), "+f"(d[111]), "+f"(d[112]), "+f"(d[113]), "+f"(d[114]), "+f"(d[115]), "+f"(d[116]), "+f"(d[117]), "+f"(d[118]), "+f"(d[119]), "+f"(d[120]), "+f"(d[121]), "+f"(d[122]), "+f"(d[123]), "+f"(d[124]), "+f"(d[125]), "+f"(d[126]), "+f"(d[127])
    : "l"(da), "l"(db), "r"(sd), "n"(OA), "n"(OB));
}
__device__ __forceinline__ void wgmma_rs_n256_tb(float (&d)[128], uint32_t a0, uint32_t a1, uint32_t a2, uint32_t a3, uint64_t db, int sd) {
  asm volatile("{\n.reg .pred p;\nsetp.ne.b32 p, %133, 0;\n"
    "wgmma.mma_async.sync.aligned.m64n256k16.f32.bf16.bf16 {%0, %1, %2, %3, %4, %5, %6, %7, %8, %9, %10, %11, %12, %13, %14, %15, %16, %17, %18, %19, %20, %21, %22, %23, %24, %25, %26, %27, %28, %29, %30, %31, %32, %33, %34, %35, %36, %37, %38, %39, %40, %41, %42, %43, %44, %45, %46, %47, %48, %49, %50, %51, %52, %53, %54, %55, %56, %57, %58, %59, %60, %61, %62, %63, %64, %65, %66, %67, %68, %69, %70, %71, %72, %73, %74, %75, %76, %77, %78, %79, %80, %81, %82, %83, %84, %85, %86, %87, %88, %89, %90, %91, %92, %93, %94, %95, %96, %97, %98, %99, %100, %101, %102, %103, %104, %105, %106, %107, %108, %109, %110, %111, %112, %113, %114, %115, %116, %117, %118, %119, %120, %121, %122, %123, %124, %125, %126, %127}, {%128, %129, %130, %131}, %132, p, 1, 1, 1;\n}\n"
    : "+f"(d[0]), "+f"(d[1]), "+f"(d[2]), "+f"(d[3]), "+f"(d[4]), "+f"(d[5]), "+f"(d[6]), "+f"(d[7]), "+f"(d[8]), "+f"(d[9]), "+f"(d[10]), "+f"(d[11]), "+f"(d[12]), "+f"(d[13]), "+f"(d[14]), "+f"(d[15]), "+f"(d[16]), "+f"(d[17]), "+f"(d[18]), "+f"(d[19]), "+f"(d[20]), "+f"(d[21]), "+f"(d[22]), "+f"(d[23]), "+f"(d[24]), "+f"(d[25]), "+f"(d[26]), "+f"(d[27]), "+f"(d[28]), "+f"(d[29]), "+f"(d[30]), "+f"(d[31]), "+f"(d[32]), "+f"(d[33]), "+f"(d[34]), "+f"(d[35]), "+f"(d[36]), "+f"(d[37]), "+f"(d[38]), "+f"(d[39]), "+f"(d[40]), "+f"(d[41]), "+f"(d[42]), "+f"(d[43]), "+f"(d[44]), "+f"(d[45]), "+f"(d[46]), "+f"(d[47]), "+f"(d[48]), "+f"(d[49]), "+f"(d[50]), "+f"(d[51]), "+f"(d[52]), "+f"(d[53]), "+f"(d[54]), "+f"(d[55]), "+f"(d[56]), "+f"(d[57]), "+f"(d[58]), "+f"(d[59]), "+f"(d[60]), "+f"(d[61]), "+f"(d[62]), "+f"(d[63]), "+f"(d[64]), "+f"(d[65]), "+f"(d[66]), "+f"(d[67]), "+f"(d[68]), "+f"(d[69]), "+f"(d[70]), "+f"(d[71]), "+f"(d[72]), "+f"(d[73]), "+f"(d[74]), "+f"(d[75]), "+f"(d[76]), "+f"(d[77]), "+f"(d[78]), "+f"(d[79]), "+f"(d[80]), "+f"(d[81]), "+f"(d[82]), "+f"(d[83]), "+f"(d[84]), "+f"(d[85]), "+f"(d[86]), "+f"(d[87]), "+f"(d[88]), "+f"(d[89]), "+f"(d[90]), "+f"(d[91]), "+f"(d[92]), "+f"(d[93]), "+f"(d[94]), "+f"(d[95]), "+f"(d[96]), "+f"(d[97]), "+f"(d[98]), "+f"(d[99]), "+f"(d[100]), "+f"(d[101]), "+f"(d[102]), "+f"(d[103]), "+f"(d[104]), "+f"(d[105]), "+f"(d[106]), "+f"(d[107]), "+f"(d[108]), "+f"(d[109]), "+f"(d[110]), "+f"(d[111]), "+f"(d[112]), "+f"(d[113]), "+f"(d[114]), "+f"(d[115]), "+f"(d[116]), "+f"(d[117]), "+f"(d[118]), "+f"(d[119]), "+f"(d[120]), "+f"(d[121]), "+f"(d[122]), "+f"(d[123]), "+f"(d[124]), "+f"(d[125]), "+f"(d[126]), "+f"(d[127])
    : "r"(a0), "r"(a1), "r"(a2), "r"(a3), "l"(db), "r"(sd));
}
template <int OA, int OB> __device__ __forceinline__ void wgmma_ss_n128_ta(float (&d)[64], uint64_t da, uint64_t db, int sd) {
  asm volatile("{\n.reg .pred p;\n.reg .b64 a, b;\nadd.s64 a, %64, %67;\nadd.s64 b, %65, %68;\nsetp.ne.b32 p, %66, 0;\n"
    "wgmma.mma_async.sync.aligned.m64n128k16.f32.bf16.bf16 {%0, %1, %2, %3, %4, %5, %6, %7, %8, %9, %10, %11, %12, %13, %14, %15, %16, %17, %18, %19, %20, %21, %22, %23, %24, %25, %26, %27, %28, %29, %30, %31, %32, %33, %34, %35, %36, %37, %38, %39, %40, %41, %42, %43, %44, %45, %46, %47, %48, %49, %50, %51, %52, %53, %54, %55, %56, %57, %58, %59, %60, %61, %62, %63}, a, b, p, 1, 1, 1, 0;\n}\n"
    : "+f"(d[0]), "+f"(d[1]), "+f"(d[2]), "+f"(d[3]), "+f"(d[4]), "+f"(d[5]), "+f"(d[6]), "+f"(d[7]), "+f"(d[8]), "+f"(d[9]), "+f"(d[10]), "+f"(d[11]), "+f"(d[12]), "+f"(d[13]), "+f"(d[14]), "+f"(d[15]), "+f"(d[16]), "+f"(d[17]), "+f"(d[18]), "+f"(d[19]), "+f"(d[20]), "+f"(d[21]), "+f"(d[22]), "+f"(d[23]), "+f"(d[24]), "+f"(d[25]), "+f"(d[26]), "+f"(d[27]), "+f"(d[28]), "+f"(d[29]), "+f"(d[30]), "+f"(d[31]), "+f"(d[32]), "+f"(d[33]), "+f"(d[34]), "+f"(d[35]), "+f"(d[36]), "+f"(d[37]), "+f"(d[38]), "+f"(d[39]), "+f"(d[40]), "+f"(d[41]), "+f"(d[42]), "+f"(d[43]), "+f"(d[44]), "+f"(d[45]), "+f"(d[46]), "+f"(d[47]), "+f"(d[48]), "+f"(d[49]), "+f"(d[50]), "+f"(d[51]), "+f"(d[52]), "+f"(d[53]), "+f"(d[54]), "+f"(d[55]), "+f"(d[56]), "+f"(d[57]), "+f"(d[58]), "+f"(d[59]), "+f"(d[60]), "+f"(d[61]), "+f"(d[62]), "+f"(d[63])
    : "l"(da), "l"(db), "r"(sd), "n"(OA), "n"(OB));
}
template <int OB> __device__ __forceinline__ void wgmma_rs_n128(float (&d)[64], uint32_t a0, uint32_t a1, uint32_t a2, uint32_t a3, uint64_t db, int sd) {
  asm volatile("{\n.reg .pred p;\n.reg .b64 b;\nadd.s64 b, %68, %70;\nsetp.ne.b32 p, %69, 0;\n"
    "wgmma.mma_async.sync.aligned.m64n128k16.f32.bf16.bf16 {%0, %1, %2, %3, %4, %5, %6, %7, %8, %9, %10, %11, %12, %13, %14, %15, %16, %17, %18, %19, %20, %21, %22, %23, %24, %25, %26, %27, %28, %29, %30, %31, %32, %33, %34, %35, %36, %37, %38, %39, %40, %41, %42, %43, %44, %45, %46, %47, %48, %49, %50, %51, %52, %53, %54, %55, %56, %57, %58, %59, %60, %61, %62, %63}, {%64, %65, %66, %67}, b, p, 1, 1, 0;\n}\n"
    : "+f"(d[0]), "+f"(d[1]), "+f"(d[2]), "+f"(d[3]), "+f"(d[4]), "+f"(d[5]), "+f"(d[6]), "+f"(d[7]), "+f"(d[8]), "+f"(d[9]), "+f"(d[10]), "+f"(d[11]), "+f"(d[12]), "+f"(d[13]), "+f"(d[14]), "+f"(d[15]), "+f"(d[16]), "+f"(d[17]), "+f"(d[18]), "+f"(d[19]), "+f"(d[20]), "+f"(d[21]), "+f"(d[22]), "+f"(d[23]), "+f"(d[24]), "+f"(d[25]), "+f"(d[26]), "+f"(d[27]), "+f"(d[28]), "+f"(d[29]), "+f"(d[30]), "+f"(d[31]), "+f"(d[32]), "+f"(d[33]), "+f"(d[34]), "+f"(d[35]), "+f"(d[36]), "+f"(d[37]), "+f"(d[38]), "+f"(d[39]), "+f"(d[40]), "+f"(d[41]), "+f"(d[42]), "+f"(d[43]), "+f"(d[44]), "+f"(d[45]), "+f"(d[46]), "+f"(d[47]), "+f"(d[48]), "+f"(d[49]), "+f"(d[50]), "+f"(d[51]), "+f"(d[52]), "+f"(d[53]), "+f"(d[54]), "+f"(d[55]), "+f"(d[56]), "+f"(d[57]), "+f"(d[58]), "+f"(d[59]), "+f"(d[60]), "+f"(d[61]), "+f"(d[62]), "+f"(d[63])
    : "r"(a0), "r"(a1), "r"(a2), "r"(a3), "l"(db), "r"(sd), "n"(OB));
}
template <int OB> __device__ __forceinline__ void wgmma_rs_n128_tb(float (&d)[64], uint32_t a0, uint32_t a1, uint32_t a2, uint32_t a3, uint64_t db, int sd) {
  asm volatile("{\n.reg .pred p;\n.reg .b64 b;\nadd.s64 b, %68, %70;\nsetp.ne.b32 p, %69, 0;\n"
    "wgmma.mma_async.sync.aligned.m64n128k16.f32.bf16.bf16 {%0, %1, %2, %3, %4, %5, %6, %7, %8, %9, %10, %11, %12, %13, %14, %15, %16, %17, %18, %19, %20, %21, %22, %23, %24, %25, %26, %27, %28, %29, %30, %31, %32, %33, %34, %35, %36, %37, %38, %39, %40, %41, %42, %43, %44, %45, %46, %47, %48, %49, %50, %51, %52, %53, %54, %55, %56, %57, %58, %59, %60, %61, %62, %63}, {%64, %65, %66, %67}, b, p, 1, 1, 1;\n}\n"
    : "+f"(d[0]), "+f"(d[1]), "+f"(d[2]), "+f"(d[3]), "+f"(d[4]), "+f"(d[5]), "+f"(d[6]), "+f"(d[7]), "+f"(d[8]), "+f"(d[9]), "+f"(d[10]), "+f"(d[11]), "+f"(d[12]), "+f"(d[13]), "+f"(d[14]), "+f"(d[15]), "+f"(d[16]), "+f"(d[17]), "+f"(d[18]), "+f"(d[19]), "+f"(d[20]), "+f"(d[21]), "+f"(d[22]), "+f"(d[23]), "+f"(d[24]), "+f"(d[25]), "+f"(d[26]), "+f"(d[27]), "+f"(d[28]), "+f"(d[29]), "+f"(d[30]), "+f"(d[31]), "+f"(d[32]), "+f"(d[33]), "+f"(d[34]), "+f"(d[35]), "+f"(d[36]), "+f"(d[37]), "+f"(d[38]), "+f"(d[39]), "+f"(d[40]), "+f"(d[41]), "+f"(d[42]), "+f"(d[43]), "+f"(d[44]), "+f"(d[45]), "+f"(d[46]), "+f"(d[47]), "+f"(d[48]), "+f"(d[49]), "+f"(d[50]), "+f"(d[51]), "+f"(d[52]), "+f"(d[53]), "+f"(d[54]), "+f"(d[55]), "+f"(d[56]), "+f"(d[57]), "+f"(d[58]), "+f"(d[59]), "+f"(d[60]), "+f"(d[61]), "+f"(d[62]), "+f"(d[63])
    : "r"(a0), "r"(a1), "r"(a2), "r"(a3), "l"(db), "r"(sd), "n"(OB));
}
__device__ __forceinline__ void wgmma_ss_n8_ta(float (&d)[4], uint64_t da, uint64_t db, int sd) {
  asm volatile("{\n.reg .pred p;\nsetp.ne.b32 p, %6, 0;\n"
    "wgmma.mma_async.sync.aligned.m64n8k16.f32.bf16.bf16 {%0, %1, %2, %3}, %4, %5, p, 1, 1, 1, 0;\n}\n"
    : "+f"(d[0]), "+f"(d[1]), "+f"(d[2]), "+f"(d[3]) : "l"(da), "l"(db), "r"(sd));
}

constexpr uint32_t U = 16384;
constexpr uint32_t SM_QO = 2 * U, SM_W = 8 * U, SM_V = 8 * U, SM_K1 = 12 * U, SM_BAR = 14 * U;
constexpr uint32_t B_WF = SM_BAR, B_KF = SM_BAR + 48, B_CF = SM_BAR + 80, B_GATE = SM_BAR + 128, B_OF = SM_BAR + 136, B_EP = SM_BAR + 144, B_EXT = SM_BAR + 152,
                   B_CST = SM_BAR + 168, B_WE = SM_BAR + 192, B_KE = SM_BAR + 240, B_CE = SM_BAR + 288, B_OS = SM_BAR + 336, B_SUM = SM_BAR + 352, B_S8 = SM_BAR + 360;
constexpr uint32_t SM_ONE = SM_BAR + 388;
constexpr uint32_t SM_BADF = SM_BAR + 392, SM_EP = SM_BAR + 396;
constexpr uint32_t SM_STAT = SM_BAR + 400, SM_EXT = SM_STAT + 512;
constexpr int SMEM_BYTES = SM_EXT + 2048 + 96;
__device__ __forceinline__ uint32_t c_slot(int s) { return (0xBADC10u >> (4 * s)) & 15; }

struct Params {
  const __nv_bfloat16 *x, *k, *v, *wq, *wo, *wr;
  __nv_bfloat16* out;
  Scratch* g;
};

__device__ __forceinline__ void release2(uint32_t rbar, int lane) { if (lane < 2) mbar_arrive_cluster(rbar); }
__device__ __forceinline__ void release2_after(uint32_t rbar, int lane, float e0, float e1) {
  asm volatile("{\n.reg .pred p, q;\nsetp.lt.s32 q, %1, 2;\nsetp.geu.and.f32 p, %2, %3, q;\n@p mbarrier.arrive.shared::cluster.b64 _, [%0];\n}\n" :: "r"(rbar), "r"(lane), "f"(e0), "f"(-e1) : "memory"); }
__device__ __forceinline__ uint32_t new_launch(Scratch* g) { return (uint32_t)(atomicAdd(&g->ticket, 1ull) / 132) + 1; }

__device__ __forceinline__ void attn_slow(uint32_t (&q)[32], const __nv_bfloat16* __restrict__ X, const __nv_bfloat16* __restrict__ WQ, uint32_t st0, uint32_t st1,
                                          const __nv_bfloat16* __restrict__ K, const __nv_bfloat16* __restrict__ V, int lane) {
  float o[64];
  #pragma unroll
  for (int i = 0; i < 64; i++) o[i] = 0.f;
  const int g = lane >> 2, qd = lane & 3;
  #pragma unroll 1
  for (int k0 = 0; k0 < DM; k0 += 16) {
    uint32_t a[4];
    #pragma unroll
    for (int e = 0; e < 4; e++) {
      const uint32_t xv = *(const uint32_t*)(X + (size_t)(g + (e & 1) * 8) * DM + k0 + (e >> 1) * 8 + 2 * qd);
      const float mb = bf_lo((e & 1) ? st1 : st0);
      a[e] = pack_bf16(bf_lo(xv) - mb, bf_hi(xv) - mb);
    }
    const unsigned short* wr = (const unsigned short*)(WQ + (size_t)(k0 + 2 * qd) * (NH * DH) + g);
    #pragma unroll
    for (int nb = 0; nb < 16; nb++) {
      uint32_t b0 = (uint32_t)wr[nb * 8] | ((uint32_t)wr[nb * 8 + NH * DH] << 16);
      uint32_t b1 = (uint32_t)wr[nb * 8 + 8 * NH * DH] | ((uint32_t)wr[nb * 8 + 9 * NH * DH] << 16);
      asm volatile("mma.sync.aligned.m16n8k16.row.col.f32.bf16.bf16.f32 {%0,%1,%2,%3}, {%4,%5,%6,%7}, {%8,%9}, {%0,%1,%2,%3};"
        : "+f"(o[nb*4]), "+f"(o[nb*4+1]), "+f"(o[nb*4+2]), "+f"(o[nb*4+3]) : "r"(a[0]), "r"(a[1]), "r"(a[2]), "r"(a[3]), "r"(b0), "r"(b1));
    }
  }
  {
    const float r0 = rcp_approx(bf_hi(st0)) * SCALE_LOG2E, r1 = rcp_approx(bf_hi(st1)) * SCALE_LOG2E;
    #pragma unroll
    for (int i = 0; i < 16; i++) { q[2*i] = pack_bf16(o[4*i] * r0, o[4*i+1] * r0); q[2*i+1] = pack_bf16(o[4*i+2] * r1, o[4*i+3] * r1); }
    #pragma unroll
    for (int i = 0; i < 64; i++) o[i] = 0.f;
  }
  float m0 = -INFINITY, m1 = -INFINITY, l0 = 0.f, l1 = 0.f;
  #pragma unroll 1
  for (int n0 = 0; n0 < S_LEN; n0 += 16) {
    float s[8];
    #pragma unroll
    for (int i = 0; i < 8; i++) s[i] = 0.f;
    #pragma unroll
    for (int nb = 0; nb < 2; nb++) {
      const uint32_t* kr = (const uint32_t*)(K + (size_t)(n0 + nb * 8 + g) * DH) + qd;
      #pragma unroll
      for (int kk = 0; kk < 8; kk++) {
        uint32_t b0 = kr[kk * 8], b1 = kr[kk * 8 + 4];
        asm volatile("mma.sync.aligned.m16n8k16.row.col.f32.bf16.bf16.f32 {%0,%1,%2,%3}, {%4,%5,%6,%7}, {%8,%9}, {%0,%1,%2,%3};"
          : "+f"(s[nb*4]), "+f"(s[nb*4+1]), "+f"(s[nb*4+2]), "+f"(s[nb*4+3]) : "r"(q[kk*4]), "r"(q[kk*4+1]), "r"(q[kk*4+2]), "r"(q[kk*4+3]), "r"(b0), "r"(b1));
      }
    }
    float x0 = fmaxf(fmaxf(s[0], s[1]), fmaxf(s[4], s[5])), x1 = fmaxf(fmaxf(s[2], s[3]), fmaxf(s[6], s[7]));
    x0 = fmaxf(x0, __shfl_xor_sync(0xffffffff, x0, 1)); x1 = fmaxf(x1, __shfl_xor_sync(0xffffffff, x1, 1));
    x0 = fmaxf(x0, __shfl_xor_sync(0xffffffff, x0, 2)); x1 = fmaxf(x1, __shfl_xor_sync(0xffffffff, x1, 2));
    const float n0m = fmaxf(m0, x0), n1m = fmaxf(m1, x1);
    const float sh0 = (n0m == -INFINITY) ? 0.f : n0m, sh1 = (n1m == -INFINITY) ? 0.f : n1m;
    const float c0 = ex2(m0 - sh0), c1 = ex2(m1 - sh1);
    m0 = n0m; m1 = n1m;
    s[0] = ex2(s[0] - sh0); s[1] = ex2(s[1] - sh0); s[4] = ex2(s[4] - sh0); s[5] = ex2(s[5] - sh0);
    s[2] = ex2(s[2] - sh1); s[3] = ex2(s[3] - sh1); s[6] = ex2(s[6] - sh1); s[7] = ex2(s[7] - sh1);
    l0 = l0 * c0 + (s[0] + s[1]) + (s[4] + s[5]); l1 = l1 * c1 + (s[2] + s[3]) + (s[6] + s[7]);
    const uint32_t a0 = pack_bf16(s[0], s[1]), a1 = pack_bf16(s[2], s[3]), a2 = pack_bf16(s[4], s[5]), a3 = pack_bf16(s[6], s[7]);
    const unsigned short* vr = (const unsigned short*)(V + (size_t)(n0 + 2 * qd) * DH + g);
    #pragma unroll
    for (int nb = 0; nb < 16; nb++) {
      uint32_t b0 = (uint32_t)vr[nb * 8] | ((uint32_t)vr[nb * 8 + DH] << 16);
      uint32_t b1 = (uint32_t)vr[nb * 8 + 8 * DH] | ((uint32_t)vr[nb * 8 + 9 * DH] << 16);
      o[nb*4] *= c0; o[nb*4+1] *= c0; o[nb*4+2] *= c1; o[nb*4+3] *= c1;
      asm volatile("mma.sync.aligned.m16n8k16.row.col.f32.bf16.bf16.f32 {%0,%1,%2,%3}, {%4,%5,%6,%7}, {%8,%9}, {%0,%1,%2,%3};"
        : "+f"(o[nb*4]), "+f"(o[nb*4+1]), "+f"(o[nb*4+2]), "+f"(o[nb*4+3]) : "r"(a0), "r"(a1), "r"(a2), "r"(a3), "r"(b0), "r"(b1));
    }
  }
  l0 += __shfl_xor_sync(0xffffffff, l0, 1); l1 += __shfl_xor_sync(0xffffffff, l1, 1);
  l0 += __shfl_xor_sync(0xffffffff, l0, 2); l1 += __shfl_xor_sync(0xffffffff, l1, 2);
  const float i0 = rcp_approx(l0), i1 = rcp_approx(l1);
  #pragma unroll
  for (int i = 0; i < 16; i++) { q[2*i] = pack_bf16(o[4*i] * i0, o[4*i+1] * i0); q[2*i+1] = pack_bf16(o[4*i+2] * i1, o[4*i+3] * i1); }
}

__device__ __forceinline__ bool finish_head(float (&o)[64], float l0, float l1, uint32_t (&of)[32], int one) {
  l0 += __shfl_xor_sync(0xffffffff, l0, one); l1 += __shfl_xor_sync(0xffffffff, l1, one);
  l0 += __shfl_xor_sync(0xffffffff, l0, 2); l1 += __shfl_xor_sync(0xffffffff, l1, 2);
  const float i0 = rcp_fast(l0), i1 = rcp_fast(l1);
  #pragma unroll
  for (int i = 0; i < 16; i++) { of[2*i] = pack_bf16(o[4*i] * i0, o[4*i+1] * i0); of[2*i+1] = pack_bf16(o[4*i+2] * i1, o[4*i+3] * i1); }
  uint32_t z0 = 0, z1 = 0;
  #pragma unroll
  for (int i = 0; i < 8; i++) {
    asm("fma.rn.bf16x2 %0, %1, %2, %0;" : "+r"(z0) : "r"(of[4*i]), "r"(of[4*i+1]));
    asm("fma.rn.bf16x2 %0, %1, %2, %0;" : "+r"(z1) : "r"(of[4*i+2]), "r"(of[4*i+3]));
  }
  asm("fma.rn.bf16x2 %0, %1, %2, %3;" : "=r"(z0) : "r"(z0), "r"(0u), "r"(0u));
  asm("fma.rn.bf16x2 %0, %1, %2, %0;" : "+r"(z0) : "r"(z1), "r"(0u));
  const bool ok = (l0 >= 0.00390625f) && (l0 <= 1.8446744e19f) && (l1 >= 0.00390625f) && (l1 <= 1.8446744e19f) && ((z0 & 0x7fff7fffu) == 0);
  return __all_sync(0xffffffff, ok);
}
__device__ __forceinline__ uint32_t warp_rows(uint32_t sb) { uint32_t t; asm volatile("mov.u32 %0, %%tid.x;" : "=r"(t)); return sb + ((t >> 5) - 4) * 2048; }
__device__ __forceinline__ uint32_t qo_slot(int h) { return SM_QO + ((0x3102 >> (4 * h)) & 3) * 2 * U; }
__device__ __forceinline__ void store_o(uint32_t sb, int lane, uint32_t slot, const uint32_t (&of)[32]) {
  const uint32_t a = warp_rows(sb) + (lane & 15) * 128 + (((lane >> 4) ^ (lane & 7)) << 4) + slot;
  #pragma unroll
  for (int i = 0; i < 8; i++) stsm4((a ^ ((i & 3) << 5)) + (i >> 2) * U, of[4*i], of[4*i+1], of[4*i+2], of[4*i+3]);
}

__device__ __noinline__ void redo_heads(const Params& P, uint32_t sb, uint32_t bad, int row0, int head0) {
  const int lane = threadIdx.x & 31;
  const uint32_t st0 = lds32(sb + SM_STAT + ((row0 & 127) + (lane >> 2)) * 4), st1 = lds32(sb + SM_STAT + ((row0 & 127) + 8 + (lane >> 2)) * 4);
  #pragma unroll 1
  for (int h = 0; h < 4; h++) {
    if (!((bad >> h) & 1)) continue;
    uint32_t q[32];
    attn_slow(q, P.x + (size_t)row0 * DM, P.wq + (head0 + h) * DH, st0, st1, P.k + (size_t)(head0 + h) * S_LEN * DH, P.v + (size_t)(head0 + h) * S_LEN * DH, lane);
    store_o(sb, lane, qo_slot(h), q);
  }
}

template <int K> struct IC { static constexpr int v = K; };
template <int K, int N, class F> __device__ __forceinline__ void static_for(F&& f) { if constexpr (K < N) { f(IC<K>{}); static_for<K + 1, N>(f); } }
template <uint32_t OFF, int SITE> __device__ __forceinline__ void mma_qk(float (&s)[64], const uint32_t (&q)[32], uint64_t d0) {
  wg_fence();
  static_for<0, 8>([&](auto kc) { constexpr int k = decltype(kc)::v; wgmma_rs_n128<doff(OFF, 16) - SITE + (k / 4) * 1024 + (k % 4) * 2>(s, q[k*4], q[k*4+1], q[k*4+2], q[k*4+3], d0, k > 0); });
  wg_commit();
}
template <uint32_t OFF, int SITE> __device__ __forceinline__ void mma_pv(float (&o)[64], const uint32_t (&p)[32], uint64_t d0, bool keep) {
  wg_fence();
  static_for<0, 8>([&](auto kc) { constexpr int k = decltype(kc)::v; wgmma_rs_n128_tb<doff(OFF, U) - SITE + k * 128>(o, p[k*4], p[k*4+1], p[k*4+2], p[k*4+3], d0, (k > 0) || keep); });
  wg_commit();
}
template <int I0, int I1>
__device__ __forceinline__ void exp_rows(float (&s)[64], float (&l)[2]) {
  #pragma unroll
  for (int i = I0; i < I1; i++) { s[i] = ex2(s[i]); l[(i >> 1) & 1] += s[i]; }
}

template <int KS, bool FIRST>
__device__ __forceinline__ void attn_step(uint32_t sb, uint32_t rb, int wg, int lane, int j, int ph, float (&s)[64], float (&o)[64], uint32_t (&p)[32], uint32_t (&q)[32],
                                          float (&l)[2], uint32_t& bad, bool& ready, Scratch* g, unsigned (&tz)[3]) {
  if (FIRST) {
    const uint32_t a = warp_rows(sb) + lane * 16 + qo_slot((j >> 4) - 1);
    #pragma unroll
    for (int i = 0; i < 8; i++) { const uint4 v = lds128(a + (i >> 2) * U + (i & 3) * 512); q[4*i] = v.x; q[4*i+1] = v.y; q[4*i+2] = v.z; q[4*i+3] = v.w; }
  }
  if (!ETEST || !ready) {
    mbar_wait(sb + B_KF + 24 - KS * 8, KS ? ph : ph ^ 1);
    mbar_wait(sb + B_KF + KS * 8, ph);
  }
  bar_sync(1 + wg, 256);
  TRACEF(2, wg, 32 + j);
  mma_qk<KS * SM_K1, FIRST>(s, q, desc(sb, FIRST));
  mma_pv<SM_V + (1 - KS) * 2 * U, FIRST>(o, p, desc(sb, FIRST), !KS || ((j & 15) != 1));
  bar_arrive(1 + (wg ^ 1), 256);
  const int one = FIRST ? lds32(sb + SM_ONE) : 1;
  wg_wait<1>();
  fence_regs(s);
  if (DPOS < 0) release2(rb + B_KE + KS * 8, lane);
  const float lp0 = l[0], lp1 = l[1];
  if (FIRST) l[0] = l[1] = 0.f;
  constexpr int DP = DPOS < 0 ? 0 : (FIRST ? DPOSF : DPOS);
  exp_rows<0, DP>(s, l);
  if (DPOS >= 0) release2_after(rb + B_KE + KS * 8, lane, l[0], l[1]);
  exp_rows<DP, 64>(s, l);
  wg_wait<0>();
  fence_regs(o); fence_regs(p);
  release2(rb + B_KE + 24 - KS * 8, lane);
  if (ETEST) ready = mbar_test2(sb + B_KF + 16 + KS * 8, ph, sb + B_KF + 8 - KS * 8, KS ? ph ^ 1 : ph);
  if (FIRST) {
    const int h = (j >> 4) - 1;
    bad |= (finish_head(o, lp0, lp1, p, one) ? 0u : 1u) << h;
    store_o(sb, lane, qo_slot(h), p);
    if (lane == 0) {
      if (bad) sts32(sb + SM_BADF, 1u);
      mbar_arrive(sb + B_OS);
    }
  }
  #pragma unroll
  for (int i = 0; i < 32; i++) p[i] = pack_bf16(s[2*i], s[2*i+1]);
}

template <int SITE> __device__ __forceinline__ void mma_c(float (&acc)[64], uint32_t sb, int slot, int h, int arrive_bar) {
  const uint64_t a = desc(sb, c_slot(slot) * 1024 + SITE), b = desc(sb, h * 2048 + SITE);
  wg_fence();
  static_for<0, 8>([&](auto kc) { constexpr int k = decltype(kc)::v;
    if (k == C_EARLY && arrive_bar) bar_arrive(arrive_bar, 256);
    wgmma_ss_n128_ta<doff(0, 16) - SITE + k * 128, doff(SM_QO, 16) - SITE + (k >> 2) * 1024 + (k & 3) * 2>(acc, a, b, k > 0 || h > 0);
  });
  wg_commit();
}

__device__ __forceinline__ void mod_branch(const Params& P, const CUtensorMap* tmG, const CUtensorMap* tmU, const CUtensorMap* tmD, uint32_t sb, int m) {
  const int tid = threadIdx.x, warp = __shfl_sync(0xffffffff, tid >> 5, 0), lane = tid & 31;
  const uint32_t XS = sb + 8 * U, HS = XS + 10240, KEY = HS + 8192, SEL = KEY + 2048, BF = SEL + 64, BE = BF + 64;
  Scratch* const g = P.g;
  const int nj = m < 3 ? 14 : 12, nd = m < 3 ? 4 : 3, f0 = m * 448;
  if (warp < 8 && elect_one()) { mbar_init(BF + warp * 8, 1); mbar_init(BE + warp * 8, 4); }
  if (tid == 32) sts32(SEL + 32, new_launch(g));
  if (tid >= 64 && tid < 128) sts128(HS + 6144 + tid * 16, 0, 0, 0, 0);
  __syncthreads();
  const uint32_t launch = lds32(SEL + 32);
  {
    const int hl = lane & 15;
    uint4 w[5];
    #pragma unroll
    for (int i = 0; i < 5; i++) w[i] = ldg_nc((const uint4*)P.wr + i * 16 + hl);
    uint4 vn[5];
    uint32_t stn;
    auto fetch = [&](int row) {
      stn = ldg32(g->stat + row);
      #pragma unroll
      for (int i = 0; i < 5; i++) vn[i] = ldg_nc((const uint4*)(P.x + (size_t)row * DM) + i * 16 + hl);
    };
    fetch(m * 512 + warp * 2 + (lane >> 4));
    #pragma unroll 1
    for (int r = warp * 2 + (lane >> 4); r < 512; r += 24) {
      const int row = m * 512 + r;
      uint32_t st = stn;
      uint4 v[5];
      #pragma unroll
      for (int i = 0; i < 5; i++) v[i] = vn[i];
      #pragma unroll 1
      for (int it = 0; __any_sync(0xffffffff, ((st >> 31) ^ launch) & 1) && it < MAXPOLL; it++) st = ldg32(g->stat + row);
      fetch(min(row + 24, S_LEN - 1));
      const uint32_t m2 = __byte_perm(st, 0, 0x1010);
      const float rsd = rcp_approx(bf_hi(st & 0x7fffffffu));
      float a = 0.f;
      #pragma unroll 1
      for (int i = 0; i < 5; i++) {
        uint32_t z[4] = {v[0].x, v[0].y, v[0].z, v[0].w};
        const uint4 w0 = w[0];
        const uint32_t ww[4] = {w0.x, w0.y, w0.z, w0.w};
        #pragma unroll
        for (int e = 0; e < 4; e++) {
          v[e] = v[e + 1]; w[e] = w[e + 1];
          const uint32_t n = norm2(z[e], m2, rsd);
          const float lo = bf_lo(n), hi = bf_hi(n);
          a = fmaf(lo, bf_lo(ww[e]), fmaf(hi, bf_hi(ww[e]), a));
          z[e] = pack_bf16(lo * sigmoid_f(lo), hi * sigmoid_f(hi));
        }
        w[4] = w0;
        ((uint4*)(g->gate + (size_t)row * DM))[i * 16 + hl] = make_uint4(z[0], z[1], z[2], z[3]);
      }
      #pragma unroll
      for (int o = 8; o; o >>= 1) a += __shfl_xor_sync(0xffffffff, a, o);
      uint32_t u = pack_bf16(a, 0.f);
      if (u == 0x8000u) u = 0;
      u = (u & 0x8000u) ? (~u & 0xffffu) : (u | 0x8000u);
      if (hl == 0) sts32(KEY + r * 4, (u << 16) | (uint32_t)(0xffff - row));
    }
  }
  __syncthreads();
  TRACE(0, 1);
  if (warp == 0) {
    uint4 k4[4];
    #pragma unroll
    for (int i = 0; i < 4; i++) k4[i] = lds128(KEY + i * 512 + lane * 16);
    uint32_t bound = 0;
    #pragma unroll 1
    for (int c = 0; c < TOPC; c++) {
      uint32_t b = 0;
      #pragma unroll
      for (int i = 0; i < 4; i++) b = max(max(max(b, k4[i].x - bound), k4[i].y - bound), max(k4[i].z - bound, k4[i].w - bound));
      bound += __reduce_max_sync(0xffffffff, b);
      if (lane == 0) asm volatile("st.relaxed.gpu.global.b64 [%0], %1;" :: "l"(g->top + m * TOPC + c), "l"(((uint64_t)launch << 32) | bound) : "memory");
    }
    uint64_t v;
    int it = 0, n = 0;
    do asm volatile("ld.relaxed.gpu.global.b64 %0, [%1];" : "=l"(v) : "l"(g->top + lane) : "memory");
    while (__any_sync(0xffffffff, (uint32_t)(v >> 32) != launch) && ++it < MAXPOLL);
    #pragma unroll 1
    for (int j = 0; j < 32; j++) n += __shfl_sync(0xffffffff, (uint32_t)v, j) > (uint32_t)v;
    if (n < TOPC) sts32(SEL + n * 4, (uint32_t)v);
  }
  __syncthreads();
  #pragma unroll 1
  for (int i = tid; i < TOPC * 80; i += 384) {
    const int row = 0xffff - (lds32(SEL + (i & 7) * 4) & 0xffff);
    const uint32_t st = ldg32(g->stat + row), m2 = __byte_perm(st, 0, 0x1010);
    const float rsd = rcp_approx(bf_hi(st & 0x7fffffffu));
    const uint4 v = ldg_nc((const uint4*)(P.x + (size_t)row * DM) + (i >> 3));
    sts128(XS + i * 16, norm2(v.x, m2, rsd), norm2(v.y, m2, rsd), norm2(v.z, m2, rsd), norm2(v.w, m2, rsd));
  }
  proxy_fence();
  __syncthreads();
  TRACE(0, 2);
  if (warp == 0) { if (elect_one()) {
    int n = 0;
    #pragma unroll 1
    for (int job = 0; job < nj + 10; job++) {
      const bool up = job < nj;
      #pragma unroll 1
      for (int i = 0; i < (up ? 5 : nd); i++, n++) {
        const int s = n & 7;
        mbar_wait(BE + s * 8, ((n >> 3) & 1) ^ 1);
        mbar_expect_tx(BF + s * 8, U);
        tma_load_2d(sb + s * U, up ? ((job & 1) ? tmU : tmG) : tmD, BF + s * 8, up ? f0 + (job >> 1) * 64 : (job - nj) * 64, (up ? 0 : f0) + i * 128);
      }
    }
  } } else if ((warp >> 2) == 1) {
    int n = 0;
    float gs[4];
    #pragma unroll 1
    for (int job = 0; job < nj + 10; job++) {
      const bool up = job < nj;
      if (job == nj) { proxy_fence(); bar_sync(1, 128); }
      float ac[4][4], acc[4];
      #pragma unroll 1
      for (int i = 0; i < (up ? 5 : nd); i++, n++) {
        const int s = n & 7;
        mbar_wait(BF + s * 8, (n >> 3) & 1);
        const uint64_t a = desc(sb, s * 1024 + 0x10000), b = (uint64_t)(desc_lo(up ? XS : HS, 128) + i * 128) | (8ull << 32);
        wg_fence();
        #pragma unroll
        for (int k = 0; k < 8; k++) wgmma_ss_n8_ta(ac[k & 3], a + (uint64_t)(k * 128), b + (uint64_t)(k * 16), k > 3 || i > 0);
        wg_commit();
        wg_wait<0>();
        if (lane == 0) mbar_arrive(BE + s * 8);
      }
      #pragma unroll
      for (int e = 0; e < 4; e++) fence_regs(ac[e]);
      #pragma unroll
      for (int e = 0; e < 4; e++) acc[e] = (ac[0][e] + ac[1][e]) + (ac[2][e] + ac[3][e]);
      const int f = (warp & 3) * 16 + (lane >> 2), tk = (lane & 3) * 2;
      if (!up) {
        float* y = g->ypart + (m * DM + (job - nj) * 64 + f) * TOPC + tk;
        *(float2*)y = make_float2(acc[0], acc[1]); *(float2*)(y + 8 * TOPC) = make_float2(acc[2], acc[3]);
      } else {
        #pragma unroll
        for (int e = 0; e < 4; e++) {
          const float z = rbf(acc[e]);
          if (job & 1) asm volatile("st.shared.u16 [%0], %1;" :: "r"(HS + (job >> 1) * 1024 + ((f >> 3) + (e >> 1)) * 128 + (tk + (e & 1)) * 16 + (f & 7) * 2), "h"((uint16_t)pack_bf16(gs[e] * z, 0.f)) : "memory");
          gs[e] = rbf(z * sigmoid_f(z));
        }
      }
    }
  }
  __syncthreads();
  TRACE(0, 3);
  if (tid == 0) { flag_add_release(&g->cnt_mod.v); flag_wait(&g->cnt_mod.v, launch * 4); }
  __syncthreads();
  #pragma unroll 1
  for (int i = tid; i < 2 * DM; i += 384) {
    const int t = 2 * m + (i & 1), col = i >> 1;
    const uint32_t key = lds32(SEL + t * 4);
    const float* yp = g->ypart + col * TOPC + t;
    const float y = rbf((__ldcg(yp) + __ldcg(yp + TOPC * DM)) + (__ldcg(yp + 2 * TOPC * DM) + __ldcg(yp + 3 * TOPC * DM)));
    const float rs = rbf(sigmoid_f(bf_hi((key >> 31) ? key & 0x7fffffffu : ~key)));
    const uint32_t xn = lds32(XS + (col >> 3) * 128 + t * 16 + (col & 6) * 2);
    const float z = rbf(((col & 1) ? bf_hi(xn) : bf_lo(xn)) + rbf(y * rs));
    g->gate[(size_t)(0xffff - (key & 0xffff)) * DM + col] = __float2bfloat16_rn(z * sigmoid_f(z));
  }
  __syncthreads();
  if (tid == 0) flag_add_release(&g->mod_done.v);
  TRACE(0, 4);
}

__global__ void __cluster_dims__(2, 1, 1) __launch_bounds__(384, 1) fused_kernel(const __grid_constant__ CUtensorMap tmX, const __grid_constant__ CUtensorMap tmWQ,
    const __grid_constant__ CUtensorMap tmK, const __grid_constant__ CUtensorMap tmV, const __grid_constant__ CUtensorMap tmWO,
    const __grid_constant__ CUtensorMap tmG, const __grid_constant__ CUtensorMap tmU, const __grid_constant__ CUtensorMap tmD, const __grid_constant__ Params P) {
  extern __shared__ __align__(1024) uint8_t smem_raw[];
  const uint32_t sb = smem_u32(smem_raw);
  const int tid = threadIdx.x, lane = tid & 31;
  const int rank = blockIdx.x & 1, cl = blockIdx.x >> 1;
  if (cl >= 64) {
    mod_branch(P, &tmG, &tmU, &tmD, sb, blockIdx.x & 3);
    return;
  }
  const int rr = ((cl - 36) * 37) >> 8, qp = cl < 4 ? 0 : (cl < 36 ? (cl - 4) & 7 : cl - 35 - rr * 7);
  const int hg = cl < 4 ? cl : (cl < 36 ? ((cl - 4) >> 3) + (qp == 0 ? 4 : 0) : 4 + rr), qt = qp * 2 + rank;
  const int warp = __shfl_sync(0xffffffff, tid >> 5, 0), wgi = warp >> 2;
  Scratch* const g = P.g;
  if (elect_one()) {
    #pragma unroll
    for (int i = 0; i < 4; i++) mbar_init(sb + SM_BAR + warp * 32 + i * 8, 1 << ((0x233444000000ull >> (4 * warp)) & 7));
    if (warp == 0) { mbar_expect_tx(sb + B_WF, 2 * U); tma_load_2d(sb + 2 * U, &tmX, sb + B_WF, 0, qt * 128); }
    asm volatile("fence.mbarrier_init.release.cluster;" ::: "memory");
  }
  __syncwarp();
  if (wgi == 0) {
    cluster_arrive();
    asm volatile("setmaxnreg.dec.sync.aligned.u32 56;");
    cluster_wait();
    if (warp > 0 && AUXW >= 0) mbar_wait(sb + B_WF + AUXW * 8, 0);
    if (warp == 3) {
      if (lane < 12) sts128(sb + SM_EXT + 1024 + (lane >= 6 ? 1024 - 96 : 0) + lane * 16, 0, 0, 0, 0);
      #pragma unroll 1
      for (int ps = 0; ps < 2; ps++) {
        const __nv_bfloat16* const wp = P.wq + hg * 512 + ps * 256;
        if (WPF) {
          #pragma unroll
          for (int i = 0; i < 5; i++) l2_prefetch_line(wp + (size_t)(qt + (i * 8 + (lane >> 2)) * 16) * (NH * DH) + (lane & 3) * 64);
        }
        const uint4* src = (const uint4*)(wp + (size_t)(lane >> 1) * (NH * DH) + qt * 16) + (lane & 1);
        float cs[8];
        #pragma unroll
        for (int e = 0; e < 8; e++) cs[e] = 0.f;
        #pragma unroll 1
        for (int b = 0; b < 4; b++, src += 10 * 16 * 512) {
          uint4 w[10];
          #pragma unroll
          for (int i = 0; i < 10; i++) w[i] = ldg_nc(src + i * 16 * 512);
          #pragma unroll
          for (int i = 0; i < 10; i++) {
            cs[0] += bf_lo(w[i].x); cs[1] += bf_hi(w[i].x); cs[2] += bf_lo(w[i].y); cs[3] += bf_hi(w[i].y);
            cs[4] += bf_lo(w[i].z); cs[5] += bf_hi(w[i].z); cs[6] += bf_lo(w[i].w); cs[7] += bf_hi(w[i].w);
          }
        }
        #pragma unroll
        for (int w2 = 4; w2; w2 >>= 1) {
          const bool up = (lane >> 2) & w2;
          #pragma unroll
          for (int e = 0; e < w2; e++) { const float keep = up ? cs[e + w2] : cs[e], send = up ? cs[e] : cs[e + w2]; cs[e] = keep + __shfl_xor_sync(0xffffffff, send, w2 * 4); }
        }
        cs[0] += __shfl_xor_sync(0xffffffff, cs[0], 2);
        mbar_wait(sb + B_EP, 0);
        const uint32_t tag = lds32(sb + SM_EP) & 1, t16 = tag << 16, t31 = tag << 31;
        const float hi = rbf(cs[0]);
        uint32_t* const gc = g->cs + hg * 512 + ps * 256;
        if (!(lane & 2)) st_relaxed(gc + qt * 16 + (lane & 1) * 8 + (lane >> 2), (pack_bf16(hi, cs[0] - hi) & ~0x10000u) | t16);
        TRACE1(2, 4 + ps);
        uint4 v[3];
        int it = 0;
        uint32_t miss;
        do {
          v[0] = ld_relaxed4(gc + lane * 4); v[1] = ld_relaxed4(gc + 128 + lane * 4); v[2] = ld_relaxed4(g->stat + qt * 128 + lane * 4);
          miss = (tag_miss(v[2].x, v[2].y, t31) | tag_miss(v[2].z, v[2].w, t31)) >> 15;
          #pragma unroll
          for (int i = 0; i < 2; i++) miss |= tag_miss(v[i].x, v[i].y, t16) | tag_miss(v[i].z, v[i].w, t16);
        } while (__any_sync(0xffffffff, miss & 0x10000u) && ++it < MAXPOLL);
        #pragma unroll
        for (int i = 0; i < 2; i++) {
          const uint32_t a = sb + SM_EXT + ps * 1024 + i * 512 + (lane >> 1) * 32 + (lane & 1) * 8;
          asm volatile("st.shared.v2.u32 [%0], {%1,%2};" :: "r"(a), "r"(__byte_perm(v[i].x, v[i].y, 0x5410)), "r"(__byte_perm(v[i].z, v[i].w, 0x5410)) : "memory");
          asm volatile("st.shared.v2.u32 [%0], {%1,%2};" :: "r"(a + 16), "r"(__byte_perm(v[i].x, v[i].y, 0x7632)), "r"(__byte_perm(v[i].z, v[i].w, 0x7632)) : "memory");
        }
        sts128(sb + SM_STAT + lane * 16, v[2].x & 0x7fffffffu, v[2].y & 0x7fffffffu, v[2].z & 0x7fffffffu, v[2].w & 0x7fffffffu);
        proxy_fence();
        __syncwarp();
        if (lane == 0) mbar_arrive(sb + B_EXT + ps * 8);
        TRACE1(2, 6 + ps);
      }
    } else if (warp > 0) {
      #pragma unroll 1
      for (int b = 0; b < 2; b++) {
        const int row = qt * 128 + hg * 16 + (warp - 1) * 8 + b * 4 + (lane >> 4);
        uint4 v[2][5];
        #pragma unroll
        for (int i = 0; i < 10; i++) v[i & 1][i >> 1] = ldg_nc((const uint4*)(P.x + (size_t)(row + (i & 1) * 2) * DM) + (i >> 1) * 16 + (lane & 15));
        float x0[2], mb[2], sd[2];
        #pragma unroll
        for (int r = 0; r < 2; r++) {
          x0[r] = bf_lo(__shfl_sync(0xffffffff, v[r][0].x, lane & 16));
          mb[r] = sd[r] = 0.f;
          #pragma unroll
          for (int i = 0; i < 5; i++) {
            const uint32_t vw[4] = {v[r][i].x, v[r][i].y, v[r][i].z, v[r][i].w};
            #pragma unroll
            for (int e = 0; e < 4; e++) { const float d0 = bf_lo(vw[e]) - x0[r], d1 = bf_hi(vw[e]) - x0[r]; mb[r] += d0 + d1; sd[r] = fmaf(d0, d0, fmaf(d1, d1, sd[r])); }
          }
        }
        const bool up = lane & 8;
        float m1 = (up ? mb[1] : mb[0]) + __shfl_xor_sync(0xffffffff, up ? mb[0] : mb[1], 8), s1 = (up ? sd[1] : sd[0]) + __shfl_xor_sync(0xffffffff, up ? sd[0] : sd[1], 8);
        #pragma unroll
        for (int o = 4; o; o >>= 1) { m1 += __shfl_xor_sync(0xffffffff, m1, o); s1 += __shfl_xor_sync(0xffffffff, s1, o); }
        const float md = m1 * (1.f / DM), var = fmaxf(fmaf(-md, md, s1 * (1.f / DM)), 0.f);
        const uint32_t w = pack_bf16((up ? x0[1] : x0[0]) + md, sqrt_approx(rbf(rbf(var) + 1e-5f)));
        mbar_wait(sb + B_EP, 0);
        if (!(lane & 7)) st_relaxed(g->stat + row + (up ? 2 : 0), (w & 0x7fffffffu) | (lds32(sb + SM_EP) << 31));
      }
      TRACE1(2, 8);
    }
    asm volatile("setmaxnreg.dec.sync.aligned.u32 24;");
    if (warp == 0) {
      const int row0 = hg * 4 * S_LEN;
      auto kv = [&](int isv, int j) {
        const uint32_t bar = sb + B_KF + isv * 16 + (j & 1) * 8;
        if (elect_one()) {
          mbar_expect_tx(bar, 2 * U);
          tma_load_2d_mc(sb + (isv ? SM_V + (j & 1) * 2 * U : (j & 1) * SM_K1) + rank * U, isv ? &tmV : &tmK, bar, rank * 64, row0 + j * 128);
        }
      };
      uint32_t s = 0, ph = 1;
      #pragma unroll 1
      for (int c = 0; c < 20; c++) {
        const int k = (c < 10 ? c : (c < 18 ? c - 8 : c - 18)) * 64, cb = hg * 8 + rank * 2 + (c < 10 ? 0 : 4);
        const bool wx = c < 10 || c >= 18;
        const uint32_t bar = sb + B_WF + s * 8, dst = sb + SM_W + rank * 8192 + s * U;
        mbar_wait(bar + (B_WE - B_WF), ph);
        if (elect_one()) {
          if (c) mbar_expect_tx(bar, wx ? 2 * U : U);
          tma_load_3d_mc(dst, &tmWQ, bar, 0, k, cb);
          if (wx && c) tma_load_2d(sb + ((c + 2) & 7) * U, &tmX, bar, k, qt * 128);
        }
        mbar_wait(bar + (B_WE - B_WF) + 8, ph);
        if (elect_one()) {
          mbar_expect_tx(bar + 8, U);
          tma_load_3d_mc(dst + U, &tmWQ, bar + 8, 0, k + 32, cb);
        }
        s += 2;
        if (s == 6) { s = 0; ph ^= 1; }
      }
      kv(0, 0);
      mbar_wait(sb + B_WE + 40, 1); kv(0, 1);
      mbar_wait(sb + B_WE + 8, 0); kv(1, 0);
      mbar_wait(sb + B_WE + 24, 0); kv(1, 1);
      mbar_wait(sb + B_KE, 0); kv(0, 2);
      #pragma unroll 1
      for (int j = 2; j < 64; j++) {
        if (j < 63) { mbar_wait(sb + B_KE + (~j & 1) * 8, ((j - 1) >> 1) & 1); kv(0, j + 1); }
        mbar_wait(sb + B_KE + 16 + (j & 1) * 8, (~j >> 1) & 1); kv(1, j);
      }
      s = 0; ph = 1;
      #pragma unroll 1
      for (int n = 0; n < 40; n++) {
        const int st = n < 5 ? (n == 1) : n >> 2, h = n < 5 ? max(n - 1, 0) : n & 3;
        const int u = st < 2 ? 8 + st : ((hg + st - 1) & 7);
        mbar_wait(sb + (n < 6 ? B_KE + (n < 4 ? n >> 1 : 3) * 8 : B_CE + s * 8), ph);
        if (elect_one()) {
          mbar_expect_tx(sb + B_CF + s * 8, U);
          tma_load_2d_mc(sb + c_slot(s) * U + rank * 8192, &tmWO, sb + B_CF + s * 8, u * 64, hg * 512 + ((0x3021 >> (4 * h)) & 3) * 128 + rank * 64);
        }
        if (++s == 6) { s = 0; ph ^= 1; }
      }
    } else if (!elect_one()) {
    } else if (warp == 1) {
      mbar_wait(sb + B_EXT, 0);
      l2_prefetch(P.k + (size_t)(hg * 4 * S_LEN + qt * (16 + 8 * KVPF)) * DH, 4096 + 2048 * KVPF);
      l2_prefetch(P.v + (size_t)(hg * 4 * S_LEN + qt * (16 + 8 * KVPF)) * DH, 4096 + 2048 * KVPF);
      flag_wait(&g->mod_done.v, lds32(sb + SM_EP) * 4);
      mbar_arrive(sb + B_GATE);
    } else if (warp == 3) {
      #pragma unroll 1
      for (int j = 2; j < 64 - KVPF; j++) {
        mbar_pace(sb + B_KE + (j & 1) * 8, (~j >> 1) & 1);
        const size_t o = (size_t)(hg * 4 * S_LEN + (j + KVPF) * 128 + qt * 8) * DH;
        if (KVPF) { l2_prefetch(P.k + o, 2048); l2_prefetch(P.v + o, 2048); }
        if (j >= 40 && j < 56) l2_prefetch(P.wo + (size_t)(hg * 512 + qt * 32 + (j - 40) * 2) * DM, 2 * DM * 2);
        if (j >= 56 && j < 60) l2_prefetch(((j & 1) ? P.x : g->gate) + (size_t)(qt * 128 + hg * 16 + (j & 2) * 4) * DM, 8 * DM * 2);
      }
    } else {
      #pragma unroll 1
      for (int h = 0; h < 4; h++) {
        mbar_wait(sb + B_OS, h & 1);
        proxy_fence();
        mbar_arrive(sb + B_OF);
      }
      mbar_arrive(sb + B_CST);
    }
    __syncwarp();
    mbar_wait(sb + B_CST, 0);
    asm volatile("setmaxnreg.inc.sync.aligned.u32 184;");
    if (warp != 0) {
      const int p0 = warp == 1 ? 0 : warp * 10 - 9;
      const uint32_t launch = lds32(sb + SM_EP), tm = 0u - (launch & 1);
      const uint4* const part = g->part + (size_t)(qt * 80 + hg * 8) * 1024 + p0 * 32 + lane;
      const uint32_t* const prog = g->prog + qt * 32 + lane;
      float a[88];
      #pragma unroll
      for (int i = 0; i < 88; i++) a[i] = 0.f;
      uint4 v[11];
      auto sent = [&](uint32_t seen, int sp) { return __all_sync(0xffffffff, (int)(seen - (launch * 16 + sp + 1)) >= 0 || (lane & 7) != ((hg + 1 - sp) & 7)); };
      bool early = false;
      uint32_t seen = 0;
      #pragma unroll 1
      for (int sp = 2; sp < 9; sp++) {
        const uint4* const from = part + ((hg + 1 - sp) & 7) * 1024, * const next = part + ((hg - sp) & 7) * 1024;
        if (!early) {
          int it = 0;
          do seen = ldg32(prog); while (!sent(seen, sp) && ++it < MAXPOLL);
          #pragma unroll
          for (int i = 0; i < 11; i++) v[i] = ld_tagged(from + i * 32);
          seen = ldg32(prog);
        }
        early = sp < 8 && sent(seen, sp + 1);
        #pragma unroll
        for (int i0 = 0; i0 < 11; i0 += 4) {
          #pragma unroll 1
          for (int it = 0; __any_sync(0xffffffff, (tag_miss(v[i0].x, v[i0+1].x, tm) | tag_miss(v[i0+2].x, v[i0 < 8 ? i0 + 3 : 10].x, tm)) & 1) && it < MAXPOLL; it++) {
            #pragma unroll
            for (int i = i0; i < i0 + 4; i++) if (i < 11) v[i] = ld_tagged(from + i * 32);
          }
          if (i0 == 0) TRACE1(2, 16 + sp);
          #pragma unroll
          for (int i = i0; i < i0 + 4; i++) if (i < 11) {
            a[8*i] += bf_lo(v[i].x); a[8*i+1] += bf_hi(v[i].x); a[8*i+2] += bf_lo(v[i].y); a[8*i+3] += bf_hi(v[i].y);
            a[8*i+4] += bf_lo(v[i].z); a[8*i+5] += bf_hi(v[i].z); a[8*i+6] += bf_lo(v[i].w); a[8*i+7] += bf_hi(v[i].w);
          }
          if (early) {
            #pragma unroll
            for (int i = i0; i < i0 + 4; i++) if (i < 11) v[i] = ld_tagged(next + i * 32);
            if (i0 == 0) seen = ldg32(prog);
          }
        }
      }
      mbar_wait(sb + B_S8, 0);
      const uint32_t d0 = sb + 10 * U + (p0 * 32 + lane) * 16;
      #pragma unroll
      for (int i = 0; i < 11; i++) {
        sts128(d0 + i * 512, __float_as_uint(a[8*i]), __float_as_uint(a[8*i+1]), __float_as_uint(a[8*i+2]), __float_as_uint(a[8*i+3]));
        sts128(d0 + i * 512 + U, __float_as_uint(a[8*i+4]), __float_as_uint(a[8*i+5]), __float_as_uint(a[8*i+6]), __float_as_uint(a[8*i+7]));
      }
      __syncwarp();
      if (lane <= (warp == 1)) mbar_arrive(sb + B_SUM);
      TRACE1(2, 9);
    }
    cluster_arrive();
    cluster_wait();
  } else {
    const int wg = wgi - 1, t = tid & 127, cw = warp - 4;
    cluster_arrive();
    asm volatile("setmaxnreg.inc.sync.aligned.u32 224;");
    cluster_wait();
    TRACE(wg, 7);
    if (tid == 128) { sts32(sb + SM_BADF, 0); sts32(sb + SM_ONE, 1); sts32(sb + SM_EP, new_launch(g)); mbar_arrive(sb + B_EP); }
    __syncwarp();
    TRACE(wg, 8);
    uint32_t q[32], p[32];
    float s[64], o[64], l[2] = {0.f, 0.f};
    const uint32_t rb = map_cta(sb, lane & 1);
    uint32_t bad = 0;
    {
      uint32_t st0 = 0, st1 = 0;
      uint32_t sl = 0, ph = 0, rprev = 0;
      if (wg == 1) bar_arrive(1, 256);
      #pragma unroll
      for (int pass = 0; pass < 2; pass++) {
        float acc[128];
        #pragma unroll 1
        for (int i = 0; i < 10; i++) {
          if (i == (pass ? SKEW1 : SKEW0) / 2) {
            if (pass == 1) {
              const uint32_t d = warp_rows(sb) + lane * 16 + qo_slot(0);
              #pragma unroll
              for (int e = 0; e < 8; e++) sts128(d + (e >> 2) * U + (e & 3) * 512, p[4*e], p[4*e+1], p[4*e+2], p[4*e+3]);
            }
            bar_sync(1 + wg, 256);
          }
          const uint64_t a = desc(sb, ((i + 2 + 2 * pass) & 7) * 1024 + wg * 512 + doff(0, 16)), b = desc(sb, sl * 128 + doff(SM_W, 4096));
          mbar_wait(sb + B_WF + sl, ph);
          if (i == 0) TRACE(wg, 1 + pass);
          TRACEF(1, wg, 40 + pass * 20 + 2 * i);
          wg_fence();
          wgmma_ss_n256_tb<0, 0>(acc, a, b, i > 0);
          wgmma_ss_n256_tb<2, 128>(acc, a, b, 1);
          wg_commit();
          mbar_wait(sb + B_WF + 8 + sl, ph);
          wg_wait<1>();
          if (i > 0) release2(rprev, lane);
          TRACEF(1, wg, 41 + pass * 20 + 2 * i);
          wg_fence();
          wgmma_ss_n256_tb<4, 1024>(acc, a, b, 1);
          wgmma_ss_n256_tb<6, 1152>(acc, a, b, 1);
          wg_commit();
          rprev = rb + B_WE + 8 + sl;
          sl += 16;
          if (sl == 48) { sl = 0; ph ^= 1; }
          wg_wait<1>();
          release2(rprev - 8, lane);
        }
        if (pass == 1) asm volatile("setmaxnreg.inc.sync.aligned.u32 240;");
        mbar_wait(sb + B_EXT + pass * 8, 0);
        if (pass == 0) { st0 = lds32(sb + SM_STAT + (cw * 16 + (lane >> 2)) * 4); st1 = lds32(sb + SM_STAT + (cw * 16 + 8 + (lane >> 2)) * 4); }
        {
          const uint32_t a0 = (lane & 3) ? 0u : (__byte_perm(st0, 0, 0x1010) ^ 0x80008000u), a1 = (lane & 3) ? 0u : (__byte_perm(st1, 0, 0x1010) ^ 0x80008000u);
          wg_fence();
          wgmma_rs_n256_tb(acc, a0, a1, 0u, 0u, (uint64_t)desc_lo(sb + SM_EXT + pass * 1024, 0) | ((uint64_t)2 << 32), 1);
          wg_commit();
        }
        float rs0 = rcp_approx(bf_hi(st0)) * SCALE_LOG2E, rs1 = rcp_approx(bf_hi(st1)) * SCALE_LOG2E;
        bar_arrive(1 + (wg ^ 1), 256);
        wg_wait<0>();
        fence_regs(acc);
        release2(rprev, lane);
        if (pass == 0) {
          #pragma unroll
          for (int i = 0; i < 32; i++) {
            const float r = (i & 1) ? rs1 : rs0;
            q[i] = pack_bf16(acc[2*i] * r, acc[2*i+1] * r); p[i] = pack_bf16(acc[64+2*i] * r, acc[64+2*i+1] * r);
          }
        } else {
          const uint32_t d = warp_rows(sb) + lane * 16 + SM_QO;
          #pragma unroll
          for (int e = 0; e < 16; e++) {
            if (e == 8) {
              mbar_wait(sb + B_KF, 0);
              bar_sync(1 + wg, 256);
              TRACE(wg, 3);
              mma_qk<0, 2>(s, q, desc(sb, 2));
              bar_arrive(1 + (wg ^ 1), 256);
              const uint32_t one = lds32(sb + SM_ONE);
              rs0 = __uint_as_float(__float_as_uint(rs0) * one); rs1 = __uint_as_float(__float_as_uint(rs1) * one);
            }
            sts128(d + (e >> 2) * U + (e & 3) * 512, pack_bf16(acc[8*e] * rs0, acc[8*e+1] * rs0), pack_bf16(acc[8*e+2] * rs1, acc[8*e+3] * rs1),
                   pack_bf16(acc[8*e+4] * rs0, acc[8*e+5] * rs0), pack_bf16(acc[8*e+6] * rs1, acc[8*e+7] * rs1));
          }
          wg_wait<0>();
          fence_regs(s);
          release2(rb + B_KE, lane);
          exp_rows<0, 64>(s, l);
          #pragma unroll
          for (int i = 0; i < 32; i++) p[i] = pack_bf16(s[2*i], s[2*i+1]);
        }
      }
    }
    unsigned tz[3] = {0, 0, 0};
    bool ready = false;
    #pragma unroll 1
    for (int j = 1, ph = 0; ; j += 2) {
      attn_step<1, false>(sb, rb, wg, lane, j, ph, s, o, p, q, l, bad, ready, g, tz);
      ph ^= 1;
      if ((j & 15) != 15) attn_step<0, false>(sb, rb, wg, lane, j + 1, ph, s, o, p, q, l, bad, ready, g, tz);
      else if (j == 63) break;
      else if (wg < 2) attn_step<0, true>(sb, rb, wg, lane, j + 1, 0, s, o, p, q, l, bad, ready, g, tz);
    }
    mbar_wait(sb + B_OF, 0);
    mbar_wait(sb + B_CF + wg * 8, 0);
    mbar_wait(sb + B_KF + 24, 1);
    bar_sync(1 + wg, 256);
    TRACE(wg, 4);
    mma_pv<SM_V + 2 * U, 2>(o, p, desc(sb, 2), true);
    mma_c<3>(s, sb, wg, 0, 0);
    bar_arrive(1 + (wg ^ 1), 256);
    mbar_wait(sb + B_KE + 16, 1);
    const uint32_t redo = lds32(sb + SM_BADF);
    wg_wait<1>();
    fence_regs(o); fence_regs(p);
    release2(rb + B_KE + 24, lane);
    if (!finish_head(o, l[0], l[1], p, lds32(sb + SM_ONE))) bad |= 8u;
    store_o(sb, lane, SM_V, p);
    if (__builtin_expect(bar_any(4 + wg, 128, bad | redo), 0)) {
      wg_wait<0>();
      fence_regs(s);
      redo_heads(P, sb, bad, qt * 128 + cw * 16, hg * 4);
      #pragma unroll
      for (int i = 0; i < 64; i++) s[i] = 0.f;
      __syncwarp();
      if (lane == 0) mbar_arrive(sb + B_OS);
      mbar_wait(sb + B_OF, 1);
      mma_c<4>(s, sb, wg, 0, 0);
    } else if (lane == 0) mbar_arrive(sb + B_OS);
    asm volatile("setmaxnreg.dec.sync.aligned.u32 160;");
    {
      const uint32_t launch = lds32(sb + SM_EP), tag = launch & 1;
      uint4* const part = g->part + (size_t)qt * 80 * 1024 + t;
      const uint32_t e0 = (qt * 128 + wg * 64 + (t >> 3)) * DM + hg * 64 + (t & 7) * 8;
      const uint32_t e8 = (qt * 128 + hg * 16 + (lane >> 2)) * DM + (8 + wg) * 64 + (cw & 3) * 16 + (lane & 3) * 2;
      uint4 v[8];
      auto fetch8 = [&]() {
        #pragma unroll
        for (int i = 0; i < 8; i++) v[i] = ld_tagged(part + (8 + wg) * 8192 + hg * 128 + i * 1024);
      };
      uint32_t xr[4], gr[4];
      int sp = wg, sl = 2 + 3 * wg, ph = 0;
      bar_sync(1 + wg, 256);
      #pragma unroll 1
      for (int st = wg; ; st += 2) {
        TRACEF(4, wg, 100 + (st >> 1));
        #pragma unroll 1
        for (int h = 1; h < 4; h++) {
          mbar_wait(sb + B_CF + sl * 8, ph);
          if (h == 3) mbar_wait(sb + B_OF, 1);
          mma_c<5>(s, sb, sl, h, (h == 3 && st < 9) ? 1 + (wg ^ 1) : 0);
          wg_wait<1>();
          release2(rb + B_CE + sp * 8, lane);
          sp = sl;
          if (++sl == 6) { sl = 0; ph ^= 1; }
        }
        wg_wait<0>();
        fence_regs(s);
        TRACEF(4, wg, 106 + (st >> 1));
        if (st == 9) break;
        if (st == 8 && lane == 0) mbar_arrive(sb + B_S8);
        release2(rb + B_CE + sp * 8, lane);
        uint4* dst = part + ((st < 2 ? 8 + st : ((hg + st - 1) & 7)) * 8 + hg) * 1024;
        #pragma unroll
        for (int i = 0; i < 8; i++)
          st_tagged(dst + i * 128, (pack_bf16(s[8*i], s[8*i+1]) & ~1u) | tag, pack_bf16(s[8*i+2], s[8*i+3]), pack_bf16(s[8*i+4], s[8*i+5]), pack_bf16(s[8*i+6], s[8*i+7]));
        if (lane == 0) asm volatile("red.relaxed.gpu.global.max.u32 [%0], %1;" :: "l"(g->prog + qt * 32 + (cw & 3) * 8 + hg), "r"(launch * 16 + st + 1) : "memory");
        if (st == 8) break;
        if ((st >> 1) == 1) {
          mbar_wait(sb + B_GATE, 0);
          fetch8();
          #pragma unroll
          for (int e = 0; e < 4; e++) { xr[e] = ldg32(P.x + e8 + (e >> 1) * 8 * DM + (e & 1) * 8); gr[e] = ldg32(g->gate + e8 + (e >> 1) * 8 * DM + (e & 1) * 8); }
        } else if ((st >> 1) == 2) {
          const uint32_t tm = 0u - tag;
          #pragma unroll 1
          for (int it = 0; __any_sync(0xffffffff, (tag_miss(v[0].x, v[1].x, tm) | tag_miss(v[2].x, v[3].x, tm) | tag_miss(v[4].x, v[5].x, tm) | tag_miss(v[6].x, v[7].x, tm)) & 1) && it < MAXPOLL; it++)
            fetch8();
          float a[8];
          #pragma unroll
          for (int i = 0; i < 8; i++) a[i] = 0.f;
          #pragma unroll
          for (int i = 0; i < 8; i++) {
            a[0] += bf_lo(v[i].x); a[1] += bf_hi(v[i].x); a[2] += bf_lo(v[i].y); a[3] += bf_hi(v[i].y);
            a[4] += bf_lo(v[i].z); a[5] += bf_hi(v[i].z); a[6] += bf_lo(v[i].w); a[7] += bf_hi(v[i].w);
          }
          #pragma unroll
          for (int e = 0; e < 4; e++) *(uint32_t*)(P.out + e8 + (e >> 1) * 8 * DM + (e & 1) * 8) = add_bf2(xr[e], mul_bf2(movm_t(pack_bf16(a[2*e], a[2*e+1])), gr[e]));
          #pragma unroll
          for (int i = 0; i < 4; i++) { v[i] = ldg_nc(P.x + e0 + i * 16 * DM); v[4 + i] = ld_relaxed4(g->gate + e0 + i * 16 * DM); }
        }
        sl += st ? 4 : 3;
        if (sl >= 6) { sl -= 6; ph ^= 1; }
        mbar_wait(sb + B_CF + sl * 8, ph);
        bar_sync(1 + wg, 256);
        mma_c<6>(s, sb, sl, 0, 0);
        sp = sl;
        if (++sl == 6) { sl = 0; ph ^= 1; }
      }
      if (wg == 1) {
        mbar_wait(sb + B_SUM, 0);
        TRACE(wg, 5);
        #pragma unroll
        for (int i = 0; i < 8; i++) {
          const uint4 h0 = lds128(sb + 10 * U + t * 16 + i * 2048), h1 = lds128(sb + 11 * U + t * 16 + i * 2048);
          stsm4t(sb + (i * 16 + (lane >> 4) * 8 + (lane & 7)) * 128 + ((((cw & 3) * 2 + ((lane >> 3) & 1)) ^ (lane & 7)) << 4),
                 pack_bf16(s[8*i] + __uint_as_float(h0.x), s[8*i+1] + __uint_as_float(h0.y)), pack_bf16(s[8*i+2] + __uint_as_float(h0.z), s[8*i+3] + __uint_as_float(h0.w)),
                 pack_bf16(s[8*i+4] + __uint_as_float(h1.x), s[8*i+5] + __uint_as_float(h1.y)), pack_bf16(s[8*i+6] + __uint_as_float(h1.z), s[8*i+7] + __uint_as_float(h1.w)));
        }
      }
      cluster_arrive();
      bar_sync(3, 256);
      #pragma unroll
      for (int i = 0; i < 4; i++) {
        const uint4 sv = lds128(sb + (wg * 64 + i * 16 + (t >> 3)) * 128 + (((t & 7) ^ ((t >> 3) & 7)) << 4));
        *(uint4*)(P.out + e0 + i * 16 * DM) = make_uint4(add_bf2(v[i].x, mul_bf2(sv.x, v[4+i].x)), add_bf2(v[i].y, mul_bf2(sv.y, v[4+i].y)),
                                                            add_bf2(v[i].z, mul_bf2(sv.z, v[4+i].z)), add_bf2(v[i].w, mul_bf2(sv.w, v[4+i].w)));
      }
    }
    TRACE(wg, 6);
    cluster_wait();
  }
}

typedef CUresult (*EncodeFn)(CUtensorMap*, CUtensorMapDataType, cuuint32_t, void*, const cuuint64_t*, const cuuint64_t*, const cuuint32_t*, const cuuint32_t*,
                             CUtensorMapInterleave, CUtensorMapSwizzle, CUtensorMapL2promotion, CUtensorMapFloatOOBfill);
void make_map(EncodeFn enc, CUtensorMap* tm, const void* ptr, uint64_t inner, uint64_t outer, uint32_t box_outer, uint32_t blocks = 0) {
  cuuint64_t dims[3] = {blocks ? 64 : inner, outer, inner / 64}; cuuint64_t strides[2] = {inner * 2, 128};
  cuuint32_t box[3] = {64, box_outer, blocks}; cuuint32_t es[3] = {1, 1, 1};
  enc(tm, CU_TENSOR_MAP_DATA_TYPE_BFLOAT16, blocks ? 3 : 2, const_cast<void*>(ptr), dims, strides, box, es, CU_TENSOR_MAP_INTERLEAVE_NONE,
      CU_TENSOR_MAP_SWIZZLE_128B, CU_TENSOR_MAP_L2_PROMOTION_L2_256B, CU_TENSOR_MAP_FLOAT_OOB_FILL_NONE);
}

}

extern "C" void kernel_launch(void* const* d_in, const int* in_sizes, int n_in, void* d_out, int out_size) {
  (void)in_sizes; (void)n_in; (void)out_size;
  Params P;
  P.x = (const __nv_bfloat16*)d_in[0]; P.k = (const __nv_bfloat16*)d_in[1]; P.v = (const __nv_bfloat16*)d_in[2];
  P.wq = (const __nv_bfloat16*)d_in[3]; P.wo = (const __nv_bfloat16*)d_in[4]; P.wr = (const __nv_bfloat16*)d_in[6];
  P.out = (__nv_bfloat16*)d_out;
  cudaGetSymbolAddress((void**)&P.g, g_s);
  void* fn = nullptr; cudaDriverEntryPointQueryResult st;
  cudaGetDriverEntryPoint("cuTensorMapEncodeTiled", &fn, cudaEnableDefault, &st);
  EncodeFn enc = (EncodeFn)fn;
  CUtensorMap tmX, tmWQ, tmK, tmV, tmWO, tmG, tmU, tmD;
  make_map(enc, &tmX, P.x, DM, S_LEN, 128);
  make_map(enc, &tmWQ, P.wq, NH * DH, DM, 32, 2);
  make_map(enc, &tmK, P.k, DH, (uint64_t)NH * S_LEN, 128);
  make_map(enc, &tmV, P.v, DH, (uint64_t)NH * S_LEN, 128);
  make_map(enc, &tmWO, P.wo, DM, NH * DH, 64);
  make_map(enc, &tmG, d_in[7], FF, DM, 128);
  make_map(enc, &tmU, d_in[8], FF, DM, 128);
  make_map(enc, &tmD, d_in[9], DM, FF, 128);
  cudaFuncSetAttribute(fused_kernel, cudaFuncAttributeMaxDynamicSharedMemorySize, SMEM_BYTES);
  fused_kernel<<<132, 384, SMEM_BYTES, cudaStreamPerThread>>>(tmX, tmWQ, tmK, tmV, tmWO, tmG, tmU, tmD, P);
}
```

```cpp
#include <cuda_runtime.h>
#include <cuda_bf16.h>
#include <cuda.h>
#include <stdint.h>

#define C_EARLY 6
#define MAXPOLL (1 << 24)
#define SKEW0 18
#define SKEW1 18
#define DPOS 44
#define DPOSF 24
#define KVPF 4
#define ETEST 1
#define SMV 1
#define X_SKIP(qp) false
#define QSP 6
namespace {

constexpr int S_LEN = 2048, DM = 640, NH = 32, DH = 128, FF = 1728, TOPC = 8;
constexpr float SCALE_LOG2E = 0.08838834764831845f * 1.4426950408889634f;

struct alignas(128) Cnt { unsigned v; unsigned pad[31]; };
struct Scratch {
  uint4 part[16 * 10 * 8 * 1024];
  __nv_bfloat16 gate[S_LEN * DM];
  uint32_t stat[S_LEN];
  uint4 cs[NH * DH];
  float ypart[4 * TOPC * DM];
  uint2 top[32];
  Cnt cnt_mod, mod_done;
  unsigned long long ticket;
};
__device__ Scratch g_s;

__device__ __forceinline__ uint32_t smem_u32(const void* p) { return (uint32_t)__cvta_generic_to_shared(p); }
__device__ __forceinline__ void mbar_init(uint32_t bar, uint32_t cnt) { asm volatile("mbarrier.init.shared::cta.b64 [%0], %1;" :: "r"(bar), "r"(cnt) : "memory"); }
__device__ __forceinline__ void mbar_expect_tx(uint32_t bar, uint32_t bytes) { asm volatile("mbarrier.arrive.expect_tx.shared::cta.b64 _, [%0], %1;" :: "r"(bar), "r"(bytes) : "memory"); }
__device__ __forceinline__ void mbar_arrive(uint32_t bar) { asm volatile("mbarrier.arrive.shared::cta.b64 _, [%0];" :: "r"(bar) : "memory"); }
__device__ __forceinline__ uint32_t map_cta(uint32_t a, uint32_t cta) { uint32_t r; asm volatile("mapa.shared::cluster.u32 %0, %1, %2;" : "=r"(r) : "r"(a), "r"(cta)); return r; }
__device__ __forceinline__ void mbar_arrive_cluster(uint32_t bar) { asm volatile("mbarrier.arrive.shared::cluster.b64 _, [%0];" :: "r"(bar) : "memory"); }
__device__ __forceinline__ void mbar_wait(uint32_t bar, uint32_t parity) {
  asm volatile("{\n.reg .pred p;\n.reg .u32 c;\nmbarrier.try_wait.parity.shared::cta.b64 p, [%0], %1;\n@p bra LAB_DONE;\nmov.u32 c, 0;\n"
               "LAB_WAIT:\nmbarrier.try_wait.parity.shared::cta.b64 p, [%0], %1;\n@p bra LAB_DONE;\nadd.u32 c, c, 1;\nsetp.lt.u32 p, c, 16777216;\n@p bra LAB_WAIT;\ntrap;\nLAB_DONE:\n}\n" :: "r"(bar), "r"(parity) : "memory"); }
__device__ __forceinline__ bool mbar_test2(uint32_t bar0, uint32_t par0, uint32_t bar1, uint32_t par1) { uint32_t r;
  asm volatile("{\n.reg .pred p, q;\nmbarrier.test_wait.parity.shared::cta.b64 p, [%1], %2;\nmbarrier.test_wait.parity.shared::cta.b64 q, [%3], %4;\nand.pred p, p, q;\nselp.u32 %0, 1, 0, p;\n}\n"
               : "=r"(r) : "r"(bar0), "r"(par0), "r"(bar1), "r"(par1) : "memory"); return r; }
__device__ __forceinline__ void mbar_pace(uint32_t bar, uint32_t parity) {
  asm volatile("{\n.reg .pred p;\n.reg .u32 c;\nmov.u32 c, 0;\nLAB_WAIT:\nmbarrier.try_wait.parity.shared::cta.b64 p, [%0], %1;\n@p bra LAB_DONE;\n"
               "add.u32 c, c, 1;\nsetp.lt.u32 p, c, 4096;\n@p bra LAB_WAIT;\nLAB_DONE:\n}\n" :: "r"(bar), "r"(parity) : "memory"); }
__device__ __forceinline__ void flag_wait(const unsigned* p, unsigned target) {
  asm volatile("{\n.reg .pred p;\n.reg .u32 c, v;\nmov.u32 c, 0;\nLAB_WAIT:\nld.acquire.gpu.global.u32 v, [%0];\nsub.u32 v, v, %1;\nsetp.ge.s32 p, v, 0;\n@p bra LAB_DONE;\n"
               "nanosleep.u32 1000;\nadd.u32 c, c, 1;\nsetp.lt.u32 p, c, 8388608;\n@p bra LAB_WAIT;\ntrap;\nLAB_DONE:\n}\n" :: "l"(p), "r"(target) : "memory"); }
__device__ __forceinline__ void flag_add_release(unsigned* p) { asm volatile("fence.acq_rel.gpu;\nred.relaxed.gpu.global.add.u32 [%0], 1;" :: "l"(p) : "memory"); }
__device__ __forceinline__ void tma_load_2d(uint32_t dst, const CUtensorMap* tm, uint32_t bar, int c0, int c1) {
  asm volatile("cp.async.bulk.tensor.2d.shared::cluster.global.mbarrier::complete_tx::bytes [%0], [%1, {%3, %4}], [%2];"
    :: "r"(dst), "l"(tm), "r"(bar), "r"(c0), "r"(c1) : "memory"); }
__device__ __forceinline__ void tma_load_2d_mc(uint32_t dst, const CUtensorMap* tm, uint32_t bar, int c0, int c1) {
  asm volatile("cp.async.bulk.tensor.2d.shared::cluster.global.mbarrier::complete_tx::bytes.multicast::cluster [%0], [%1, {%3, %4}], [%2], %5;"
    :: "r"(dst), "l"(tm), "r"(bar), "r"(c0), "r"(c1), "h"((uint16_t)3) : "memory"); }
__device__ __forceinline__ void tma_load_3d_mc(uint32_t dst, const CUtensorMap* tm, uint32_t bar, int c0, int c1, int c2) {
  asm volatile("cp.async.bulk.tensor.3d.shared::cluster.global.mbarrier::complete_tx::bytes.multicast::cluster [%0], [%1, {%3, %4, %5}], [%2], %6;"
    :: "r"(dst), "l"(tm), "r"(bar), "r"(c0), "r"(c1), "r"(c2), "h"((uint16_t)3) : "memory"); }
__device__ __forceinline__ void l2_prefetch(const void* p, uint32_t bytes) { asm volatile("cp.async.bulk.prefetch.L2.global [%0], %1;" :: "l"(p), "r"(bytes) : "memory"); }
__device__ __forceinline__ void wg_fence() { asm volatile("wgmma.fence.sync.aligned;" ::: "memory"); }
__device__ __forceinline__ void wg_commit() { asm volatile("wgmma.commit_group.sync.aligned;" ::: "memory"); }
template <int N> __device__ __forceinline__ void wg_wait() { asm volatile("wgmma.wait_group.sync.aligned %0;" :: "n"(N) : "memory"); }
__device__ __forceinline__ void bar_sync(int id, int n) { asm volatile("bar.sync %0, %1;" :: "r"(id), "r"(n) : "memory"); }
__device__ __forceinline__ void bar_arrive(int id, int n) { asm volatile("bar.arrive %0, %1;" :: "r"(id), "r"(n) : "memory"); }
__device__ __forceinline__ bool bar_any(int id, int n, uint32_t v) { uint32_t r;
  asm volatile("{\n.reg .pred p;\nsetp.ne.u32 p, %3, 0;\nbar.red.or.pred p, %1, %2, p;\nselp.u32 %0, 1, 0, p;\n}\n" : "=r"(r) : "r"(id), "r"(n), "r"(v) : "memory"); return r; }
__device__ __forceinline__ int sel_lt(int a, int b, int x, int y) { int r; asm("{\n.reg .pred p;\nsetp.lt.s32 p, %1, %2;\nselp.s32 %0, %3, %4, p;\n}\n" : "=r"(r) : "r"(a), "r"(b), "r"(x), "r"(y)); return r; }
__device__ __forceinline__ bool elect_one() { uint32_t r; asm volatile("{\n.reg .pred p;\nelect.sync _|p, 0xffffffff;\nselp.u32 %0, 1, 0, p;\n}\n" : "=r"(r)); return r; }
__device__ __forceinline__ void cluster_arrive() { asm volatile("barrier.cluster.arrive.relaxed.aligned;" ::: "memory"); }
__device__ __forceinline__ void cluster_wait() { asm volatile("barrier.cluster.wait.aligned;" ::: "memory"); }
__device__ __forceinline__ void proxy_fence() { asm volatile("fence.proxy.async.shared::cta;" ::: "memory"); }
__device__ __forceinline__ uint32_t pack_bf16(float lo, float hi) { uint32_t r; asm("cvt.rn.bf16x2.f32 %0, %1, %2;" : "=r"(r) : "f"(hi), "f"(lo)); return r; }
__device__ __forceinline__ float bf_lo(uint32_t v) { return __uint_as_float(v << 16); }
__device__ __forceinline__ float bf_hi(uint32_t v) { return __uint_as_float(v & 0xffff0000u); }
__device__ __forceinline__ void add8(float* a, const uint4& w) {
  a[0] += bf_lo(w.x); a[1] += bf_hi(w.x); a[2] += bf_lo(w.y); a[3] += bf_hi(w.y); a[4] += bf_lo(w.z); a[5] += bf_hi(w.z); a[6] += bf_lo(w.w); a[7] += bf_hi(w.w); }
__device__ __forceinline__ float rbf(float x) { return __bfloat162float(__float2bfloat16_rn(x)); }
__device__ __forceinline__ float ex2(float x) { float y; asm("ex2.approx.ftz.f32 %0, %1;" : "=f"(y) : "f"(x)); return y; }
__device__ __forceinline__ uint32_t lds32(uint32_t a) { uint32_t v; asm volatile("ld.shared.u32 %0, [%1];" : "=r"(v) : "r"(a) : "memory"); return v; }
__device__ __forceinline__ void sts32(uint32_t a, uint32_t v) { asm volatile("st.shared.u32 [%0], %1;" :: "r"(a), "r"(v) : "memory"); }
__device__ __forceinline__ uint4 lds128(uint32_t a) { uint4 v; asm volatile("ld.shared.v4.u32 {%0,%1,%2,%3}, [%4];" : "=r"(v.x), "=r"(v.y), "=r"(v.z), "=r"(v.w) : "r"(a) : "memory"); return v; }
__device__ __forceinline__ void sts128(uint32_t a, uint32_t x, uint32_t y, uint32_t z, uint32_t w) { asm volatile("st.shared.v4.u32 [%0], {%1,%2,%3,%4};" :: "r"(a), "r"(x), "r"(y), "r"(z), "r"(w) : "memory"); }
__device__ __forceinline__ void st_tagged(uint4* p, uint32_t x, uint32_t y, uint32_t z, uint32_t w) {
  asm volatile("st.relaxed.gpu.global.v4.u32 [%0], {%1,%2,%3,%4};" :: "l"(p), "r"(x), "r"(y), "r"(z), "r"(w) : "memory"); }
__device__ __forceinline__ uint4 ld_tagged(const uint4* p) { uint4 v;
  asm volatile("{\n.reg .b128 v;\nld.relaxed.gpu.global.b128 v, [%4];\nmov.b128 {%0,%1,%2,%3}, v;\n}\n" : "=r"(v.x), "=r"(v.y), "=r"(v.z), "=r"(v.w) : "l"(p) : "memory"); return v; }
__device__ __forceinline__ uint4 ld_relaxed4(const void* p) { uint4 v;
  asm volatile("ld.relaxed.gpu.global.v4.u32 {%0,%1,%2,%3}, [%4];" : "=r"(v.x), "=r"(v.y), "=r"(v.z), "=r"(v.w) : "l"(p) : "memory"); return v; }
__device__ __forceinline__ uint4 ldg_nc(const void* p) { uint4 v;
  asm volatile("ld.global.nc.L1::no_allocate.v4.u32 {%0,%1,%2,%3}, [%4];" : "=r"(v.x), "=r"(v.y), "=r"(v.z), "=r"(v.w) : "l"(p) : "memory"); return v; }
__device__ __forceinline__ uint32_t ldg32(const void* p) { uint32_t v; asm volatile("ld.relaxed.gpu.global.u32 %0, [%1];" : "=r"(v) : "l"(p) : "memory"); return v; }
__device__ __forceinline__ void st_relaxed(uint32_t* p, uint32_t v) { asm volatile("st.relaxed.gpu.global.u32 [%0], %1;" :: "l"(p), "r"(v) : "memory"); }
__device__ __forceinline__ uint32_t mul_bf2(uint32_t a, uint32_t b) { uint32_t r; asm("mul.rn.bf16x2 %0, %1, %2;" : "=r"(r) : "r"(a), "r"(b)); return r; }
__device__ __forceinline__ uint32_t add_bf2(uint32_t a, uint32_t b) { uint32_t r; asm("add.rn.bf16x2 %0, %1, %2;" : "=r"(r) : "r"(a), "r"(b)); return r; }
__device__ __forceinline__ uint32_t sub_bf2(uint32_t a, uint32_t b) { uint32_t r; asm("sub.rn.bf16x2 %0, %1, %2;" : "=r"(r) : "r"(a), "r"(b)); return r; }
__device__ __forceinline__ void stsm4(uint32_t a, uint32_t r0, uint32_t r1, uint32_t r2, uint32_t r3) {
  asm volatile("stmatrix.sync.aligned.m8n8.x4.shared.b16 [%0], {%1,%2,%3,%4};" :: "r"(a), "r"(r0), "r"(r1), "r"(r2), "r"(r3) : "memory"); }
__device__ __forceinline__ void stsm4t(uint32_t a, uint32_t r0, uint32_t r1, uint32_t r2, uint32_t r3) {
  asm volatile("stmatrix.sync.aligned.m8n8.x4.trans.shared.b16 [%0], {%1,%2,%3,%4};" :: "r"(a), "r"(r0), "r"(r1), "r"(r2), "r"(r3) : "memory"); }
__device__ __forceinline__ uint4 gated(const uint4& x, const uint4& s, const uint4& g) {
  return make_uint4(add_bf2(x.x, mul_bf2(s.x, g.x)), add_bf2(x.y, mul_bf2(s.y, g.y)), add_bf2(x.z, mul_bf2(s.z, g.z)), add_bf2(x.w, mul_bf2(s.w, g.w))); }
__device__ __forceinline__ uint32_t or_bit0(uint32_t a, uint32_t b) { uint32_t d; asm("lop3.b32 %0, %1, %2, 1, 0xA8;" : "=r"(d) : "r"(a), "r"(b)); return d; }
__device__ __forceinline__ uint32_t tag_miss(uint32_t a, uint32_t b, uint32_t tm) { uint32_t d; asm("lop3.b32 %0, %1, %2, %3, 0x7E;" : "=r"(d) : "r"(a), "r"(b), "r"(tm)); return d; }
template <int R> __device__ __forceinline__ void fence_regs(float (&d)[R]) {
  #pragma unroll
  for (int i = 0; i < R; i++) asm volatile("" : "+f"(d[i]) :: "memory"); }
template <int R> __device__ __forceinline__ void fence_regs(uint32_t (&d)[R]) {
  #pragma unroll
  for (int i = 0; i < R; i++) asm volatile("" : "+r"(d[i]) :: "memory"); }
__device__ __forceinline__ uint32_t desc_lo(uint32_t addr, uint32_t lbo_bytes) { return ((addr & 0x3FFFF) >> 4) | ((lbo_bytes >> 4) << 16); }
__device__ __forceinline__ uint64_t desc(uint32_t sb, uint32_t var = 0) {
  uint64_t d; asm("mov.b64 %0, {%1, %2};" : "=l"(d) : "r"(desc_lo(sb, 0) + var), "r"(0x40000040u)); return d; }
__host__ __device__ constexpr int doff(uint32_t off, uint32_t lbo_bytes) { return (off >> 4) | ((lbo_bytes >> 4) << 16); }
__device__ __forceinline__ float rcp_approx(float x) { float y; asm("rcp.approx.f32 %0, %1;" : "=f"(y) : "f"(x)); return y; }
__device__ __forceinline__ float rcp_fast(float x) { float y; asm("rcp.approx.ftz.f32 %0, %1;" : "=f"(y) : "f"(x)); return y; }
__device__ __forceinline__ float sqrt_approx(float x) { float y; asm("sqrt.approx.f32 %0, %1;" : "=f"(y) : "f"(x)); return y; }
__device__ __forceinline__ float sigmoid_f(float z) { return rcp_fast(1.f + ex2(z * -1.4426950408889634f)); }
__device__ __forceinline__ uint32_t norm2(uint32_t x, uint32_t mean2, float rsd) { const uint32_t d = sub_bf2(x, mean2); return pack_bf16(bf_lo(d) * rsd, bf_hi(d) * rsd); }
#define TRACE(w, i)
#define TRACE1(w, i)
#define TRACEF(m, w, i)

template <int OA, int OB> __device__ __forceinline__ void wgmma_ss_n256_tb(float (&d)[128], uint64_t da, uint64_t db, int sd) {
  asm volatile("{\n.reg .pred p;\n.reg .b64 a, b;\nadd.s64 a, %128, %131;\nadd.s64 b, %129, %132;\nsetp.ne.b32 p, %130, 0;\n"
    "wgmma.mma_async.sync.aligned.m64n256k16.f32.bf16.bf16 {%0, %1, %2, %3, %4, %5, %6, %7, %8, %9, %10, %11, %12, %13, %14, %15, %16, %17, %18, %19, %20, %21, %22, %23, %24, %25, %26, %27, %28, %29, %30, %31, %32, %33, %34, %35, %36, %37, %38, %39, %40, %41, %42, %43, %44, %45, %46, %47, %48, %49, %50, %51, %52, %53, %54, %55, %56, %57, %58, %59, %60, %61, %62, %63, %64, %65, %66, %67, %68, %69, %70, %71, %72, %73, %74, %75, %76, %77, %78, %79, %80, %81, %82, %83, %84, %85, %86, %87, %88, %89, %90, %91, %92, %93, %94, %95, %96, %97, %98, %99, %100, %101, %102, %103, %104, %105, %106, %107, %108, %109, %110, %111, %112, %113, %114, %115, %116, %117, %118, %119, %120, %121, %122, %123, %124, %125, %126, %127}, a, b, p, 1, 1, 0, 1;\n}\n"
    : "+f"(d[0]), "+f"(d[1]), "+f"(d[2]), "+f"(d[3]), "+f"(d[4]), "+f"(d[5]), "+f"(d[6]), "+f"(d[7]), "+f"(d[8]), "+f"(d[9]), "+f"(d[10]), "+f"(d[11]), "+f"(d[12]), "+f"(d[13]), "+f"(d[14]), "+f"(d[15]), "+f"(d[16]), "+f"(d[17]), "+f"(d[18]), "+f"(d[19]), "+f"(d[20]), "+f"(d[21]), "+f"(d[22]), "+f"(d[23]), "+f"(d[24]), "+f"(d[25]), "+f"(d[26]), "+f"(d[27]), "+f"(d[28]), "+f"(d[29]), "+f"(d[30]), "+f"(d[31]), "+f"(d[32]), "+f"(d[33]), "+f"(d[34]), "+f"(d[35]), "+f"(d[36]), "+f"(d[37]), "+f"(d[38]), "+f"(d[39]), "+f"(d[40]), "+f"(d[41]), "+f"(d[42]), "+f"(d[43]), "+f"(d[44]), "+f"(d[45]), "+f"(d[46]), "+f"(d[47]), "+f"(d[48]), "+f"(d[49]), "+f"(d[50]), "+f"(d[51]), "+f"(d[52]), "+f"(d[53]), "+f"(d[54]), "+f"(d[55]), "+f"(d[56]), "+f"(d[57]), "+f"(d[58]), "+f"(d[59]), "+f"(d[60]), "+f"(d[61]), "+f"(d[62]), "+f"(d[63]), "+f"(d[64]), "+f"(d[65]), "+f"(d[66]), "+f"(d[67]), "+f"(d[68]), "+f"(d[69]), "+f"(d[70]), "+f"(d[71]), "+f"(d[72]), "+f"(d[73]), "+f"(d[74]), "+f"(d[75]), "+f"(d[76]), "+f"(d[77]), "+f"(d[78]), "+f"(d[79]), "+f"(d[80]), "+f"(d[81]), "+f"(d[82]), "+f"(d[83]), "+f"(d[84]), "+f"(d[85]), "+f"(d[86]), "+f"(d[87]), "+f"(d[88]), "+f"(d[89]), "+f"(d[90]), "+f"(d[91]), "+f"(d[92]), "+f"(d[93]), "+f"(d[94]), "+f"(d[95]), "+f"(d[96]), "+f"(d[97]), "+f"(d[98]), "+f"(d[99]), "+f"(d[100]), "+f"(d[101]), "+f"(d[102]), "+f"(d[103]), "+f"(d[104]), "+f"(d[105]), "+f"(d[106]), "+f"(d[107]), "+f"(d[108]), "+f"(d[109]), "+f"(d[110]), "+f"(d[111]), "+f"(d[112]), "+f"(d[113]), "+f"(d[114]), "+f"(d[115]), "+f"(d[116]), "+f"(d[117]), "+f"(d[118]), "+f"(d[119]), "+f"(d[120]), "+f"(d[121]), "+f"(d[122]), "+f"(d[123]), "+f"(d[124]), "+f"(d[125]), "+f"(d[126]), "+f"(d[127])
    : "l"(da), "l"(db), "r"(sd), "n"(OA), "n"(OB));
}
__device__ __forceinline__ void wgmma_rs_n256_tb(float (&d)[128], uint32_t a0, uint32_t a1, uint32_t a2, uint32_t a3, uint64_t db, int sd) {
  asm volatile("{\n.reg .pred p;\nsetp.ne.b32 p, %133, 0;\n"
    "wgmma.mma_async.sync.aligned.m64n256k16.f32.bf16.bf16 {%0, %1, %2, %3, %4, %5, %6, %7, %8, %9, %10, %11, %12, %13, %14, %15, %16, %17, %18, %19, %20, %21, %22, %23, %24, %25, %26, %27, %28, %29, %30, %31, %32, %33, %34, %35, %36, %37, %38, %39, %40, %41, %42, %43, %44, %45, %46, %47, %48, %49, %50, %51, %52, %53, %54, %55, %56, %57, %58, %59, %60, %61, %62, %63, %64, %65, %66, %67, %68, %69, %70, %71, %72, %73, %74, %75, %76, %77, %78, %79, %80, %81, %82, %83, %84, %85, %86, %87, %88, %89, %90, %91, %92, %93, %94, %95, %96, %97, %98, %99, %100, %101, %102, %103, %104, %105, %106, %107, %108, %109, %110, %111, %112, %113, %114, %115, %116, %117, %118, %119, %120, %121, %122, %123, %124, %125, %126, %127}, {%128, %129, %130, %131}, %132, p, 1, 1, 1;\n}\n"
    : "+f"(d[0]), "+f"(d[1]), "+f"(d[2]), "+f"(d[3]), "+f"(d[4]), "+f"(d[5]), "+f"(d[6]), "+f"(d[7]), "+f"(d[8]), "+f"(d[9]), "+f"(d[10]), "+f"(d[11]), "+f"(d[12]), "+f"(d[13]), "+f"(d[14]), "+f"(d[15]), "+f"(d[16]), "+f"(d[17]), "+f"(d[18]), "+f"(d[19]), "+f"(d[20]), "+f"(d[21]), "+f"(d[22]), "+f"(d[23]), "+f"(d[24]), "+f"(d[25]), "+f"(d[26]), "+f"(d[27]), "+f"(d[28]), "+f"(d[29]), "+f"(d[30]), "+f"(d[31]), "+f"(d[32]), "+f"(d[33]), "+f"(d[34]), "+f"(d[35]), "+f"(d[36]), "+f"(d[37]), "+f"(d[38]), "+f"(d[39]), "+f"(d[40]), "+f"(d[41]), "+f"(d[42]), "+f"(d[43]), "+f"(d[44]), "+f"(d[45]), "+f"(d[46]), "+f"(d[47]), "+f"(d[48]), "+f"(d[49]), "+f"(d[50]), "+f"(d[51]), "+f"(d[52]), "+f"(d[53]), "+f"(d[54]), "+f"(d[55]), "+f"(d[56]), "+f"(d[57]), "+f"(d[58]), "+f"(d[59]), "+f"(d[60]), "+f"(d[61]), "+f"(d[62]), "+f"(d[63]), "+f"(d[64]), "+f"(d[65]), "+f"(d[66]), "+f"(d[67]), "+f"(d[68]), "+f"(d[69]), "+f"(d[70]), "+f"(d[71]), "+f"(d[72]), "+f"(d[73]), "+f"(d[74]), "+f"(d[75]), "+f"(d[76]), "+f"(d[77]), "+f"(d[78]), "+f"(d[79]), "+f"(d[80]), "+f"(d[81]), "+f"(d[82]), "+f"(d[83]), "+f"(d[84]), "+f"(d[85]), "+f"(d[86]), "+f"(d[87]), "+f"(d[88]), "+f"(d[89]), "+f"(d[90]), "+f"(d[91]), "+f"(d[92]), "+f"(d[93]), "+f"(d[94]), "+f"(d[95]), "+f"(d[96]), "+f"(d[97]), "+f"(d[98]), "+f"(d[99]), "+f"(d[100]), "+f"(d[101]), "+f"(d[102]), "+f"(d[103]), "+f"(d[104]), "+f"(d[105]), "+f"(d[106]), "+f"(d[107]), "+f"(d[108]), "+f"(d[109]), "+f"(d[110]), "+f"(d[111]), "+f"(d[112]), "+f"(d[113]), "+f"(d[114]), "+f"(d[115]), "+f"(d[116]), "+f"(d[117]), "+f"(d[118]), "+f"(d[119]), "+f"(d[120]), "+f"(d[121]), "+f"(d[122]), "+f"(d[123]), "+f"(d[124]), "+f"(d[125]), "+f"(d[126]), "+f"(d[127])
    : "r"(a0), "r"(a1), "r"(a2), "r"(a3), "l"(db), "r"(sd));
}
template <int OA, int OB> __device__ __forceinline__ void wgmma_ss_n128_ta(float (&d)[64], uint64_t da, uint64_t db, int sd) {
  asm volatile("{\n.reg .pred p;\n.reg .b64 a, b;\nadd.s64 a, %64, %67;\nadd.s64 b, %65, %68;\nsetp.ne.b32 p, %66, 0;\n"
    "wgmma.mma_async.sync.aligned.m64n128k16.f32.bf16.bf16 {%0, %1, %2, %3, %4, %5, %6, %7, %8, %9, %10, %11, %12, %13, %14, %15, %16, %17, %18, %19, %20, %21, %22, %23, %24, %25, %26, %27, %28, %29, %30, %31, %32, %33, %34, %35, %36, %37, %38, %39, %40, %41, %42, %43, %44, %45, %46, %47, %48, %49, %50, %51, %52, %53, %54, %55, %56, %57, %58, %59, %60, %61, %62, %63}, a, b, p, 1, 1, 1, 0;\n}\n"
    : "+f"(d[0]), "+f"(d[1]), "+f"(d[2]), "+f"(d[3]), "+f"(d[4]), "+f"(d[5]), "+f"(d[6]), "+f"(d[7]), "+f"(d[8]), "+f"(d[9]), "+f"(d[10]), "+f"(d[11]), "+f"(d[12]), "+f"(d[13]), "+f"(d[14]), "+f"(d[15]), "+f"(d[16]), "+f"(d[17]), "+f"(d[18]), "+f"(d[19]), "+f"(d[20]), "+f"(d[21]), "+f"(d[22]), "+f"(d[23]), "+f"(d[24]), "+f"(d[25]), "+f"(d[26]), "+f"(d[27]), "+f"(d[28]), "+f"(d[29]), "+f"(d[30]), "+f"(d[31]), "+f"(d[32]), "+f"(d[33]), "+f"(d[34]), "+f"(d[35]), "+f"(d[36]), "+f"(d[37]), "+f"(d[38]), "+f"(d[39]), "+f"(d[40]), "+f"(d[41]), "+f"(d[42]), "+f"(d[43]), "+f"(d[44]), "+f"(d[45]), "+f"(d[46]), "+f"(d[47]), "+f"(d[48]), "+f"(d[49]), "+f"(d[50]), "+f"(d[51]), "+f"(d[52]), "+f"(d[53]), "+f"(d[54]), "+f"(d[55]), "+f"(d[56]), "+f"(d[57]), "+f"(d[58]), "+f"(d[59]), "+f"(d[60]), "+f"(d[61]), "+f"(d[62]), "+f"(d[63])
    : "l"(da), "l"(db), "r"(sd), "n"(OA), "n"(OB));
}
template <int OB> __device__ __forceinline__ void wgmma_rs_n128(float (&d)[64], uint32_t a0, uint32_t a1, uint32_t a2, uint32_t a3, uint64_t db, int sd) {
  asm volatile("{\n.reg .pred p;\n.reg .b64 b;\nadd.s64 b, %68, %70;\nsetp.ne.b32 p, %69, 0;\n"
    "wgmma.mma_async.sync.aligned.m64n128k16.f32.bf16.bf16 {%0, %1, %2, %3, %4, %5, %6, %7, %8, %9, %10, %11, %12, %13, %14, %15, %16, %17, %18, %19, %20, %21, %22, %23, %24, %25, %26, %27, %28, %29, %30, %31, %32, %33, %34, %35, %36, %37, %38, %39, %40, %41, %42, %43, %44, %45, %46, %47, %48, %49, %50, %51, %52, %53, %54, %55, %56, %57, %58, %59, %60, %61, %62, %63}, {%64, %65, %66, %67}, b, p, 1, 1, 0;\n}\n"
    : "+f"(d[0]), "+f"(d[1]), "+f"(d[2]), "+f"(d[3]), "+f"(d[4]), "+f"(d[5]), "+f"(d[6]), "+f"(d[7]), "+f"(d[8]), "+f"(d[9]), "+f"(d[10]), "+f"(d[11]), "+f"(d[12]), "+f"(d[13]), "+f"(d[14]), "+f"(d[15]), "+f"(d[16]), "+f"(d[17]), "+f"(d[18]), "+f"(d[19]), "+f"(d[20]), "+f"(d[21]), "+f"(d[22]), "+f"(d[23]), "+f"(d[24]), "+f"(d[25]), "+f"(d[26]), "+f"(d[27]), "+f"(d[28]), "+f"(d[29]), "+f"(d[30]), "+f"(d[31]), "+f"(d[32]), "+f"(d[33]), "+f"(d[34]), "+f"(d[35]), "+f"(d[36]), "+f"(d[37]), "+f"(d[38]), "+f"(d[39]), "+f"(d[40]), "+f"(d[41]), "+f"(d[42]), "+f"(d[43]), "+f"(d[44]), "+f"(d[45]), "+f"(d[46]), "+f"(d[47]), "+f"(d[48]), "+f"(d[49]), "+f"(d[50]), "+f"(d[51]), "+f"(d[52]), "+f"(d[53]), "+f"(d[54]), "+f"(d[55]), "+f"(d[56]), "+f"(d[57]), "+f"(d[58]), "+f"(d[59]), "+f"(d[60]), "+f"(d[61]), "+f"(d[62]), "+f"(d[63])
    : "r"(a0), "r"(a1), "r"(a2), "r"(a3), "l"(db), "r"(sd), "n"(OB));
}
template <int OB> __device__ __forceinline__ void wgmma_rs_n128_tb(float (&d)[64], uint32_t a0, uint32_t a1, uint32_t a2, uint32_t a3, uint64_t db, int sd) {
  asm volatile("{\n.reg .pred p;\n.reg .b64 b;\nadd.s64 b, %68, %70;\nsetp.ne.b32 p, %69, 0;\n"
    "wgmma.mma_async.sync.aligned.m64n128k16.f32.bf16.bf16 {%0, %1, %2, %3, %4, %5, %6, %7, %8, %9, %10, %11, %12, %13, %14, %15, %16, %17, %18, %19, %20, %21, %22, %23, %24, %25, %26, %27, %28, %29, %30, %31, %32, %33, %34, %35, %36, %37, %38, %39, %40, %41, %42, %43, %44, %45, %46, %47, %48, %49, %50, %51, %52, %53, %54, %55, %56, %57, %58, %59, %60, %61, %62, %63}, {%64, %65, %66, %67}, b, p, 1, 1, 1;\n}\n"
    : "+f"(d[0]), "+f"(d[1]), "+f"(d[2]), "+f"(d[3]), "+f"(d[4]), "+f"(d[5]), "+f"(d[6]), "+f"(d[7]), "+f"(d[8]), "+f"(d[9]), "+f"(d[10]), "+f"(d[11]), "+f"(d[12]), "+f"(d[13]), "+f"(d[14]), "+f"(d[15]), "+f"(d[16]), "+f"(d[17]), "+f"(d[18]), "+f"(d[19]), "+f"(d[20]), "+f"(d[21]), "+f"(d[22]), "+f"(d[23]), "+f"(d[24]), "+f"(d[25]), "+f"(d[26]), "+f"(d[27]), "+f"(d[28]), "+f"(d[29]), "+f"(d[30]), "+f"(d[31]), "+f"(d[32]), "+f"(d[33]), "+f"(d[34]), "+f"(d[35]), "+f"(d[36]), "+f"(d[37]), "+f"(d[38]), "+f"(d[39]), "+f"(d[40]), "+f"(d[41]), "+f"(d[42]), "+f"(d[43]), "+f"(d[44]), "+f"(d[45]), "+f"(d[46]), "+f"(d[47]), "+f"(d[48]), "+f"(d[49]), "+f"(d[50]), "+f"(d[51]), "+f"(d[52]), "+f"(d[53]), "+f"(d[54]), "+f"(d[55]), "+f"(d[56]), "+f"(d[57]), "+f"(d[58]), "+f"(d[59]), "+f"(d[60]), "+f"(d[61]), "+f"(d[62]), "+f"(d[63])
    : "r"(a0), "r"(a1), "r"(a2), "r"(a3), "l"(db), "r"(sd), "n"(OB));
}
__device__ __forceinline__ void wgmma_ss_n8_ta(float (&d)[4], uint64_t da, uint64_t db, int sd) {
  asm volatile("{\n.reg .pred p;\nsetp.ne.b32 p, %6, 0;\n"
    "wgmma.mma_async.sync.aligned.m64n8k16.f32.bf16.bf16 {%0, %1, %2, %3}, %4, %5, p, 1, 1, 1, 0;\n}\n"
    : "+f"(d[0]), "+f"(d[1]), "+f"(d[2]), "+f"(d[3]) : "l"(da), "l"(db), "r"(sd));
}

constexpr uint32_t U = 16384;
constexpr uint32_t SM_QO = 2 * U, SM_W = 8 * U, SM_V = 8 * U, SM_K1 = 12 * U, SM_BAR = 14 * U;
constexpr uint32_t B_WF = SM_BAR, B_KF = SM_BAR + 48, B_CF = SM_BAR + 80, B_GATE = SM_BAR + 128, B_OF = SM_BAR + 136, B_EP = SM_BAR + 144, B_EXT = SM_BAR + 152,
                   B_WE = SM_BAR + 192, B_KE = SM_BAR + 240, B_CE = SM_BAR + 288, B_OS = SM_BAR + 344;
constexpr uint32_t SM_ONE = SM_BAR + 388;
constexpr uint32_t SM_BADF = SM_BAR + 392, SM_EP = SM_BAR + 396;
constexpr uint32_t SM_STAT = SM_BAR + 400, SM_EXT = SM_STAT + 512;
constexpr int SMEM_BYTES = SM_BAR + 3072;
__device__ __forceinline__ uint32_t c_slot(int s) { return (0xBADC10u >> (4 * s)) & 15; }

struct Params {
  const __nv_bfloat16 *x, *k, *v, *wq, *wo, *wr;
  __nv_bfloat16* out;
  Scratch* g;
};

__device__ __forceinline__ void release2(uint32_t rbar, int lane) { if (lane < 2) mbar_arrive_cluster(rbar); }
__device__ __forceinline__ void pin_after(uint32_t a, float e0, float e1) {
  asm volatile("{\n.reg .pred p;\nsetp.lt.f32 p, %1, %2;\n@p st.shared.u32 [%0], %0;\n}\n" :: "r"(a), "f"(e0), "f"(-e1) : "memory"); }
__device__ __forceinline__ void lds128_after(uint32_t& x, uint32_t& y, uint32_t& z, uint32_t& w, uint32_t a, float e0, float e1) {
  asm volatile("{\n.reg .pred p;\nsetp.geu.f32 p, %5, %6;\n@p ld.shared.v4.u32 {%0,%1,%2,%3}, [%4];\n}\n" : "+r"(x), "+r"(y), "+r"(z), "+r"(w) : "r"(a), "f"(e0), "f"(-e1) : "memory"); }
__device__ __forceinline__ uint32_t new_launch(Scratch* g) { return (uint32_t)(atomicAdd(&g->ticket, 1ull) / 132) + 1; }

__device__ __forceinline__ void attn_slow(uint32_t (&q)[32], const __nv_bfloat16* __restrict__ X, const __nv_bfloat16* __restrict__ WQ, uint32_t st0, uint32_t st1,
                                          const __nv_bfloat16* __restrict__ K, const __nv_bfloat16* __restrict__ V, int lane) {
  float o[64];
  #pragma unroll
  for (int i = 0; i < 64; i++) o[i] = 0.f;
  const int g = lane >> 2, qd = lane & 3;
  #pragma unroll 1
  for (int k0 = 0; k0 < DM; k0 += 16) {
    uint32_t a[4];
    #pragma unroll
    for (int e = 0; e < 4; e++) {
      const uint32_t xv = *(const uint32_t*)(X + (size_t)(g + (e & 1) * 8) * DM + k0 + (e >> 1) * 8 + 2 * qd);
      const float mb = bf_lo((e & 1) ? st1 : st0);
      a[e] = pack_bf16(bf_lo(xv) - mb, bf_hi(xv) - mb);
    }
    const unsigned short* wr = (const unsigned short*)(WQ + (size_t)(k0 + 2 * qd) * (NH * DH) + g);
    #pragma unroll
    for (int nb = 0; nb < 16; nb++) {
      uint32_t b0 = (uint32_t)wr[nb * 8] | ((uint32_t)wr[nb * 8 + NH * DH] << 16);
      uint32_t b1 = (uint32_t)wr[nb * 8 + 8 * NH * DH] | ((uint32_t)wr[nb * 8 + 9 * NH * DH] << 16);
      asm volatile("mma.sync.aligned.m16n8k16.row.col.f32.bf16.bf16.f32 {%0,%1,%2,%3}, {%4,%5,%6,%7}, {%8,%9}, {%0,%1,%2,%3};"
        : "+f"(o[nb*4]), "+f"(o[nb*4+1]), "+f"(o[nb*4+2]), "+f"(o[nb*4+3]) : "r"(a[0]), "r"(a[1]), "r"(a[2]), "r"(a[3]), "r"(b0), "r"(b1));
    }
  }
  {
    const float r0 = rcp_approx(bf_hi(st0)) * SCALE_LOG2E, r1 = rcp_approx(bf_hi(st1)) * SCALE_LOG2E;
    #pragma unroll
    for (int i = 0; i < 16; i++) { q[2*i] = pack_bf16(o[4*i] * r0, o[4*i+1] * r0); q[2*i+1] = pack_bf16(o[4*i+2] * r1, o[4*i+3] * r1); }
    #pragma unroll
    for (int i = 0; i < 64; i++) o[i] = 0.f;
  }
  float m0 = -INFINITY, m1 = -INFINITY, l0 = 0.f, l1 = 0.f;
  #pragma unroll 1
  for (int n0 = 0; n0 < S_LEN; n0 += 16) {
    float s[8];
    #pragma unroll
    for (int i = 0; i < 8; i++) s[i] = 0.f;
    #pragma unroll
    for (int nb = 0; nb < 2; nb++) {
      const uint32_t* kr = (const uint32_t*)(K + (size_t)(n0 + nb * 8 + g) * DH) + qd;
      #pragma unroll
      for (int kk = 0; kk < 8; kk++) {
        uint32_t b0 = kr[kk * 8], b1 = kr[kk * 8 + 4];
        asm volatile("mma.sync.aligned.m16n8k16.row.col.f32.bf16.bf16.f32 {%0,%1,%2,%3}, {%4,%5,%6,%7}, {%8,%9}, {%0,%1,%2,%3};"
          : "+f"(s[nb*4]), "+f"(s[nb*4+1]), "+f"(s[nb*4+2]), "+f"(s[nb*4+3]) : "r"(q[kk*4]), "r"(q[kk*4+1]), "r"(q[kk*4+2]), "r"(q[kk*4+3]), "r"(b0), "r"(b1));
      }
    }
    float x0 = fmaxf(fmaxf(s[0], s[1]), fmaxf(s[4], s[5])), x1 = fmaxf(fmaxf(s[2], s[3]), fmaxf(s[6], s[7]));
    x0 = fmaxf(x0, __shfl_xor_sync(0xffffffff, x0, 1)); x1 = fmaxf(x1, __shfl_xor_sync(0xffffffff, x1, 1));
    x0 = fmaxf(x0, __shfl_xor_sync(0xffffffff, x0, 2)); x1 = fmaxf(x1, __shfl_xor_sync(0xffffffff, x1, 2));
    const float n0m = fmaxf(m0, x0), n1m = fmaxf(m1, x1);
    const float sh0 = (n0m == -INFINITY) ? 0.f : n0m, sh1 = (n1m == -INFINITY) ? 0.f : n1m;
    const float c0 = ex2(m0 - sh0), c1 = ex2(m1 - sh1);
    m0 = n0m; m1 = n1m;
    s[0] = ex2(s[0] - sh0); s[1] = ex2(s[1] - sh0); s[4] = ex2(s[4] - sh0); s[5] = ex2(s[5] - sh0);
    s[2] = ex2(s[2] - sh1); s[3] = ex2(s[3] - sh1); s[6] = ex2(s[6] - sh1); s[7] = ex2(s[7] - sh1);
    l0 = l0 * c0 + (s[0] + s[1]) + (s[4] + s[5]); l1 = l1 * c1 + (s[2] + s[3]) + (s[6] + s[7]);
    const uint32_t a0 = pack_bf16(s[0], s[1]), a1 = pack_bf16(s[2], s[3]), a2 = pack_bf16(s[4], s[5]), a3 = pack_bf16(s[6], s[7]);
    const unsigned short* vr = (const unsigned short*)(V + (size_t)(n0 + 2 * qd) * DH + g);
    #pragma unroll
    for (int nb = 0; nb < 16; nb++) {
      uint32_t b0 = (uint32_t)vr[nb * 8] | ((uint32_t)vr[nb * 8 + DH] << 16);
      uint32_t b1 = (uint32_t)vr[nb * 8 + 8 * DH] | ((uint32_t)vr[nb * 8 + 9 * DH] << 16);
      o[nb*4] *= c0; o[nb*4+1] *= c0; o[nb*4+2] *= c1; o[nb*4+3] *= c1;
      asm volatile("mma.sync.aligned.m16n8k16.row.col.f32.bf16.bf16.f32 {%0,%1,%2,%3}, {%4,%5,%6,%7}, {%8,%9}, {%0,%1,%2,%3};"
        : "+f"(o[nb*4]), "+f"(o[nb*4+1]), "+f"(o[nb*4+2]), "+f"(o[nb*4+3]) : "r"(a0), "r"(a1), "r"(a2), "r"(a3), "r"(b0), "r"(b1));
    }
  }
  l0 += __shfl_xor_sync(0xffffffff, l0, 1); l1 += __shfl_xor_sync(0xffffffff, l1, 1);
  l0 += __shfl_xor_sync(0xffffffff, l0, 2); l1 += __shfl_xor_sync(0xffffffff, l1, 2);
  const float i0 = rcp_approx(l0), i1 = rcp_approx(l1);
  #pragma unroll
  for (int i = 0; i < 16; i++) { q[2*i] = pack_bf16(o[4*i] * i0, o[4*i+1] * i0); q[2*i+1] = pack_bf16(o[4*i+2] * i1, o[4*i+3] * i1); }
}

__device__ __forceinline__ bool finish_head(float (&o)[64], float l0, float l1, uint32_t (&of)[32], int one) {
  l0 += __shfl_xor_sync(0xffffffff, l0, one); l1 += __shfl_xor_sync(0xffffffff, l1, one);
  l0 += __shfl_xor_sync(0xffffffff, l0, 2); l1 += __shfl_xor_sync(0xffffffff, l1, 2);
  const float i0 = rcp_fast(l0), i1 = rcp_fast(l1);
  #pragma unroll
  for (int i = 0; i < 16; i++) { of[2*i] = pack_bf16(o[4*i] * i0, o[4*i+1] * i0); of[2*i+1] = pack_bf16(o[4*i+2] * i1, o[4*i+3] * i1); }
  uint32_t z0 = 0, z1 = 0;
  #pragma unroll
  for (int i = 0; i < 8; i++) {
    asm("fma.rn.bf16x2 %0, %1, %2, %0;" : "+r"(z0) : "r"(of[4*i]), "r"(of[4*i+1]));
    asm("fma.rn.bf16x2 %0, %1, %2, %0;" : "+r"(z1) : "r"(of[4*i+2]), "r"(of[4*i+3]));
  }
  asm("fma.rn.bf16x2 %0, %1, %2, %3;" : "=r"(z0) : "r"(z0), "r"(0u), "r"(0u));
  asm("fma.rn.bf16x2 %0, %1, %2, %0;" : "+r"(z0) : "r"(z1), "r"(0u));
  const bool ok = (l0 >= 0.00390625f) && (l0 <= 1.8446744e19f) && (l1 >= 0.00390625f) && (l1 <= 1.8446744e19f) && ((z0 & 0x7fff7fffu) == 0);
  return __all_sync(0xffffffff, ok);
}
__device__ __forceinline__ uint32_t qo_slot(int h) { return SM_QO + ((0x3102 >> (4 * h)) & 3) * 2 * U; }
__device__ __forceinline__ void store_o(uint32_t wr, int lane, uint32_t slot, const uint32_t (&of)[32]) {
  const uint32_t a = wr + (lane & 15) * 128 + (((lane >> 4) ^ (lane & 7)) << 4) + slot;
  #pragma unroll
  for (int i = 0; i < 8; i++) stsm4((a ^ ((i & 3) << 5)) + (i >> 2) * U, of[4*i], of[4*i+1], of[4*i+2], of[4*i+3]);
}

__device__ __noinline__ void redo_heads(const Params& P, uint32_t sb, uint32_t bad, int row0, int head0) {
  const int lane = threadIdx.x & 31;
  const uint32_t st0 = lds32(sb + SM_STAT + ((row0 & 127) + (lane >> 2)) * 4), st1 = lds32(sb + SM_STAT + ((row0 & 127) + 8 + (lane >> 2)) * 4);
  #pragma unroll 1
  for (int h = 0; h < 4; h++) {
    if (!((bad >> h) & 1)) continue;
    uint32_t q[32];
    attn_slow(q, P.x + (size_t)row0 * DM, P.wq + (head0 + h) * DH, st0, st1, P.k + (size_t)(head0 + h) * S_LEN * DH, P.v + (size_t)(head0 + h) * S_LEN * DH, lane);
    store_o(sb + (row0 & 127) * 128, lane, qo_slot(h), q);
  }
}

template <int K> struct IC { static constexpr int v = K; };
template <int K, int N, class F> __device__ __forceinline__ void static_for(F&& f) { if constexpr (K < N) { f(IC<K>{}); static_for<K + 1, N>(f); } }
template <uint32_t OFF, int SITE> __device__ __forceinline__ void mma_qk(float (&s)[64], const uint32_t (&q)[32], uint64_t d0) {
  wg_fence();
  static_for<0, 8>([&](auto kc) { constexpr int k = decltype(kc)::v; wgmma_rs_n128<doff(OFF, 16) - SITE + (k / 4) * 1024 + (k % 4) * 2>(s, q[k*4], q[k*4+1], q[k*4+2], q[k*4+3], d0, k > 0); });
  wg_commit();
}
template <uint32_t OFF, int SITE> __device__ __forceinline__ void mma_pv(float (&o)[64], const uint32_t (&p)[32], uint64_t d0, bool keep) {
  wg_fence();
  static_for<0, 8>([&](auto kc) { constexpr int k = decltype(kc)::v; wgmma_rs_n128_tb<doff(OFF, U) - SITE + k * 128>(o, p[k*4], p[k*4+1], p[k*4+2], p[k*4+3], d0, (k > 0) || keep); });
  wg_commit();
}
template <int I0, int I1>
__device__ __forceinline__ void exp_rows(float (&s)[64], float (&l)[2]) {
  #pragma unroll
  for (int i = I0; i < I1; i += 2) {
    s[i] = ex2(s[i]); s[i+1] = ex2(s[i+1]);
    if (SMV) l[(i >> 1) & 1] += s[i] + s[i+1]; else { l[(i >> 1) & 1] += s[i]; l[(i >> 1) & 1] += s[i+1]; }
  }
}

template <int KS, bool EDGE>
__device__ __forceinline__ void attn_step(uint32_t sb, uint32_t rb, uint32_t wr, uint32_t qa, int wg, int lane, int j, int ph, float (&s)[64], float (&o)[64], uint32_t (&p)[32], uint32_t (&q)[32],
                                          float (&l)[2], uint32_t& bad, bool& ready, Scratch* g, unsigned (&tz)[3]) {
  constexpr bool FIRST = EDGE && !KS, LAST = EDGE && KS;
  TRACEF(2, wg, 32 + j);
  if (!ETEST || !ready) {
    mbar_wait(sb + B_KF + 24 - KS * 8, KS ? ph : ph ^ 1);
    mbar_wait(sb + B_KF + KS * 8, ph);
  }
  bar_sync(1 + wg, 256);
  mma_qk<KS * SM_K1, EDGE>(s, q, desc(sb, EDGE));
  mma_pv<SM_V + (1 - KS) * 2 * U, EDGE>(o, p, desc(sb, EDGE), !KS || LAST || ((j & 15) != 1));
  bar_arrive(1 + (wg ^ 1), 256);
  const int one = FIRST ? lds32(sb + SM_ONE) : 1;
  wg_wait<1>();
  fence_regs(s);
  release2(rb + B_KE + KS * 8, lane);
  const float lp0 = l[0], lp1 = l[1];
  if (FIRST) l[0] = l[1] = 0.f;
  constexpr int DP = FIRST ? DPOSF : (LAST && DPOS < 7 * QSP ? 7 * QSP : DPOS);
  if (LAST) {
    fence_regs(q);
    const uint32_t a = qa + qo_slot(j >> 4);
    static_for<0, 8>([&](auto ic) { constexpr int i = decltype(ic)::v;
      lds128_after(q[4*i], q[4*i+1], q[4*i+2], q[4*i+3], a + (i >> 2) * U + (i & 3) * 512, l[0], l[1]);
      exp_rows<i * QSP, i < 7 ? (i + 1) * QSP : DP>(s, l);
    });
  } else exp_rows<0, DP>(s, l);
  if (DPOS >= 0) pin_after(sb + SM_BADF, l[0], l[1]);
  exp_rows<DP, 64>(s, l);
  wg_wait<0>();
  fence_regs(o); fence_regs(p);
  release2(rb + B_KE + 24 - KS * 8, lane);
  if (ETEST) ready = mbar_test2(sb + B_KF + 16 + KS * 8, ph, sb + B_KF + 8 - KS * 8, KS ? ph ^ 1 : ph);
  if (FIRST) {
    const int h = (j >> 4) - 1;
    bad |= (finish_head(o, lp0, lp1, p, one) ? 0u : 1u) << h;
    store_o(wr, lane, qo_slot(h), p);
    if (lane == 0) {
      if (bad) sts32(sb + SM_BADF, 1u);
      mbar_arrive(sb + B_OS);
    }
  }
  #pragma unroll
  for (int i = 0; i < 32; i++) p[i] = pack_bf16(s[2*i], s[2*i+1]);
}

template <int SITE> __device__ __forceinline__ void mma_c(float (&acc)[64], uint32_t sb, int slot, int h, int arrive_bar) {
  const uint64_t a = desc(sb, c_slot(slot) * 1024 + SITE), b = desc(sb, h * 2048 + SITE);
  wg_fence();
  static_for<0, 8>([&](auto kc) { constexpr int k = decltype(kc)::v;
    if (k == C_EARLY && arrive_bar) bar_arrive(arrive_bar, 256);
    wgmma_ss_n128_ta<doff(0, 16) - SITE + k * 128, doff(SM_QO, 16) - SITE + (k >> 2) * 1024 + (k & 3) * 2>(acc, a, b, k > 0 || h > 0);
  });
  wg_commit();
}

__device__ __forceinline__ void mod_branch(const Params& P, const CUtensorMap* tmG, const CUtensorMap* tmU, const CUtensorMap* tmD, uint32_t sb, int m) {
  const int tid = threadIdx.x, warp = __shfl_sync(0xffffffff, tid >> 5, 0), lane = tid & 31;
  const uint32_t XS = sb + 8 * U, HS = XS + 10240, KEY = HS + 8192, SEL = KEY + 2048, BF = SEL + 64, BE = BF + 64;
  Scratch* const g = P.g;
  const int nj = m < 3 ? 14 : 12, nd = m < 3 ? 4 : 3, f0 = m * 448;
  if (warp < 8 && elect_one()) { mbar_init(BF + warp * 8, 1); mbar_init(BE + warp * 8, 4); }
  if (tid == 32) sts32(SEL + 32, new_launch(g));
  if (tid >= 64 && tid < 128) sts128(HS + 6144 + tid * 16, 0, 0, 0, 0);
  __syncthreads();
  const uint32_t launch = lds32(SEL + 32);
  {
    const int hl = lane & 15;
    uint4 w[5];
    #pragma unroll
    for (int i = 0; i < 5; i++) w[i] = ldg_nc((const uint4*)P.wr + i * 16 + hl);
    uint4 vn[5];
    uint32_t stn;
    auto fetch = [&](int row) {
      stn = ldg32(g->stat + row);
      #pragma unroll
      for (int i = 0; i < 5; i++) vn[i] = ldg_nc((const uint4*)(P.x + (size_t)row * DM) + i * 16 + hl);
    };
    fetch(m * 512 + warp * 2 + (lane >> 4));
    #pragma unroll 1
    for (int r = warp * 2 + (lane >> 4); r < 512; r += 24) {
      const int row = m * 512 + r;
      uint32_t st = stn;
      uint4 v[5];
      #pragma unroll
      for (int i = 0; i < 5; i++) v[i] = vn[i];
      #pragma unroll 1
      for (int it = 0; __any_sync(0xffffffff, ((st >> 31) ^ launch) & 1) && it < MAXPOLL; it++) st = ldg32(g->stat + row);
      fetch(min(row + 24, S_LEN - 1));
      const uint32_t m2 = __byte_perm(st, 0, 0x1010);
      const float rsd = rcp_approx(bf_hi(st & 0x7fffffffu));
      float a = 0.f;
      #pragma unroll 1
      for (int i = 0; i < 5; i++) {
        uint32_t z[4] = {v[0].x, v[0].y, v[0].z, v[0].w};
        const uint4 w0 = w[0];
        const uint32_t ww[4] = {w0.x, w0.y, w0.z, w0.w};
        #pragma unroll
        for (int e = 0; e < 4; e++) {
          v[e] = v[e + 1]; w[e] = w[e + 1];
          const uint32_t n = norm2(z[e], m2, rsd);
          const float lo = bf_lo(n), hi = bf_hi(n);
          a = fmaf(lo, bf_lo(ww[e]), fmaf(hi, bf_hi(ww[e]), a));
          z[e] = pack_bf16(lo * sigmoid_f(lo), hi * sigmoid_f(hi));
        }
        w[4] = w0;
        ((uint4*)(g->gate + (size_t)row * DM))[i * 16 + hl] = make_uint4(z[0], z[1], z[2], z[3]);
      }
      #pragma unroll
      for (int o = 8; o; o >>= 1) a += __shfl_xor_sync(0xffffffff, a, o);
      uint32_t u = pack_bf16(a, 0.f);
      if (u == 0x8000u) u = 0;
      u = (u & 0x8000u) ? (~u & 0xffffu) : (u | 0x8000u);
      if (hl == 0) sts32(KEY + r * 4, (u << 16) | (uint32_t)(0xffff - row));
    }
  }
  __syncthreads();
  TRACE(0, 1);
  if (warp == 0) {
    uint4 k4[4];
    #pragma unroll
    for (int i = 0; i < 4; i++) k4[i] = lds128(KEY + i * 512 + lane * 16);
    uint32_t bound = 0;
    #pragma unroll 1
    for (int c = 0; c < TOPC; c++) {
      uint32_t b = 0;
      #pragma unroll
      for (int i = 0; i < 4; i++) b = max(max(max(b, k4[i].x - bound), k4[i].y - bound), max(k4[i].z - bound, k4[i].w - bound));
      bound += __reduce_max_sync(0xffffffff, b);
      if (lane == 0) asm volatile("st.relaxed.gpu.global.b64 [%0], %1;" :: "l"(g->top + m * TOPC + c), "l"(((uint64_t)launch << 32) | bound) : "memory");
    }
    uint64_t v;
    int it = 0, n = 0;
    do asm volatile("ld.relaxed.gpu.global.b64 %0, [%1];" : "=l"(v) : "l"(g->top + lane) : "memory");
    while (__any_sync(0xffffffff, (uint32_t)(v >> 32) != launch) && ++it < MAXPOLL);
    #pragma unroll 1
    for (int j = 0; j < 32; j++) n += __shfl_sync(0xffffffff, (uint32_t)v, j) > (uint32_t)v;
    if (n < TOPC) sts32(SEL + n * 4, (uint32_t)v);
  }
  __syncthreads();
  #pragma unroll 1
  for (int i = tid; i < TOPC * 80; i += 384) {
    const int row = 0xffff - (lds32(SEL + (i & 7) * 4) & 0xffff);
    const uint32_t st = ldg32(g->stat + row), m2 = __byte_perm(st, 0, 0x1010);
    const float rsd = rcp_approx(bf_hi(st & 0x7fffffffu));
    const uint4 v = ldg_nc((const uint4*)(P.x + (size_t)row * DM) + (i >> 3));
    sts128(XS + i * 16, norm2(v.x, m2, rsd), norm2(v.y, m2, rsd), norm2(v.z, m2, rsd), norm2(v.w, m2, rsd));
  }
  proxy_fence();
  __syncthreads();
  TRACE(0, 2);
  if (warp == 0) { if (elect_one()) {
    int n = 0;
    #pragma unroll 1
    for (int job = 0; job < nj + 10; job++) {
      const bool up = job < nj;
      #pragma unroll 1
      for (int i = 0; i < (up ? 5 : nd); i++, n++) {
        const int s = n & 7;
        mbar_wait(BE + s * 8, ((n >> 3) & 1) ^ 1);
        mbar_expect_tx(BF + s * 8, U);
        tma_load_2d(sb + s * U, up ? ((job & 1) ? tmU : tmG) : tmD, BF + s * 8, up ? f0 + (job >> 1) * 64 : (job - nj) * 64, (up ? 0 : f0) + i * 128);
      }
    }
  } } else if ((warp >> 2) == 1) {
    int n = 0;
    float gs[4];
    #pragma unroll 1
    for (int job = 0; job < nj + 10; job++) {
      const bool up = job < nj;
      if (job == nj) { proxy_fence(); bar_sync(1, 128); }
      float ac[4][4], acc[4];
      #pragma unroll 1
      for (int i = 0; i < (up ? 5 : nd); i++, n++) {
        const int s = n & 7;
        mbar_wait(BF + s * 8, (n >> 3) & 1);
        const uint64_t a = desc(sb, s * 1024 + 0x10000), b = (uint64_t)(desc_lo(up ? XS : HS, 128) + i * 128) | (8ull << 32);
        wg_fence();
        #pragma unroll
        for (int k = 0; k < 8; k++) wgmma_ss_n8_ta(ac[k & 3], a + (uint64_t)(k * 128), b + (uint64_t)(k * 16), k > 3 || i > 0);
        wg_commit();
        wg_wait<0>();
        if (lane == 0) mbar_arrive(BE + s * 8);
      }
      #pragma unroll
      for (int e = 0; e < 4; e++) fence_regs(ac[e]);
      #pragma unroll
      for (int e = 0; e < 4; e++) acc[e] = (ac[0][e] + ac[1][e]) + (ac[2][e] + ac[3][e]);
      const int f = (warp & 3) * 16 + (lane >> 2), tk = (lane & 3) * 2;
      if (!up) {
        float* y = g->ypart + (m * DM + (job - nj) * 64 + f) * TOPC + tk;
        *(float2*)y = make_float2(acc[0], acc[1]); *(float2*)(y + 8 * TOPC) = make_float2(acc[2], acc[3]);
      } else {
        #pragma unroll
        for (int e = 0; e < 4; e++) {
          const float z = rbf(acc[e]);
          if (job & 1) asm volatile("st.shared.u16 [%0], %1;" :: "r"(HS + (job >> 1) * 1024 + ((f >> 3) + (e >> 1)) * 128 + (tk + (e & 1)) * 16 + (f & 7) * 2), "h"((uint16_t)pack_bf16(gs[e] * z, 0.f)) : "memory");
          gs[e] = rbf(z * sigmoid_f(z));
        }
      }
    }
  }
  __syncthreads();
  TRACE(0, 3);
  if (tid == 0) { flag_add_release(&g->cnt_mod.v); flag_wait(&g->cnt_mod.v, launch * 4); }
  __syncthreads();
  #pragma unroll 1
  for (int i = tid; i < 2 * DM; i += 384) {
    const int t = 2 * m + (i & 1), col = i >> 1;
    const uint32_t key = lds32(SEL + t * 4);
    const float* yp = g->ypart + col * TOPC + t;
    const float y = rbf((__ldcg(yp) + __ldcg(yp + TOPC * DM)) + (__ldcg(yp + 2 * TOPC * DM) + __ldcg(yp + 3 * TOPC * DM)));
    const float rs = rbf(sigmoid_f(bf_hi((key >> 31) ? key & 0x7fffffffu : ~key)));
    const uint32_t xn = lds32(XS + (col >> 3) * 128 + t * 16 + (col & 6) * 2);
    const float z = rbf(((col & 1) ? bf_hi(xn) : bf_lo(xn)) + rbf(y * rs));
    g->gate[(size_t)(0xffff - (key & 0xffff)) * DM + col] = __float2bfloat16_rn(z * sigmoid_f(z));
  }
  __syncthreads();
  if (tid == 0) flag_add_release(&g->mod_done.v);
  TRACE(0, 4);
}

__global__ void __cluster_dims__(2, 1, 1) __launch_bounds__(384, 1) fused_kernel(const __grid_constant__ CUtensorMap tmX, const __grid_constant__ CUtensorMap tmWQ,
    const __grid_constant__ CUtensorMap tmK, const __grid_constant__ CUtensorMap tmV, const __grid_constant__ CUtensorMap tmWO,
    const __grid_constant__ CUtensorMap tmG, const __grid_constant__ CUtensorMap tmU, const __grid_constant__ CUtensorMap tmD,
    const __grid_constant__ CUtensorMap tmGate, const __grid_constant__ Params P) {
  extern __shared__ __align__(1024) uint8_t smem_raw[];
  const uint32_t sb = smem_u32(smem_raw);
  const int tid = threadIdx.x, lane = tid & 31;
  const int rank = blockIdx.x & 1, cl = blockIdx.x >> 1;
  if (cl >= 64) {
    mod_branch(P, &tmG, &tmU, &tmD, sb, blockIdx.x & 3);
    return;
  }
  const int rr = ((cl - 36) * 37) >> 8, qp = sel_lt(cl, 4, 0, sel_lt(cl, 36, (cl - 4) & 7, cl - 35 - rr * 7));
  const int hg = sel_lt(cl, 4, cl, sel_lt(cl, 36, ((cl - 4) >> 3) + sel_lt(qp, 1, 4, 0), 4 + rr)), qt = qp * 2 + rank;
  const int warp = __shfl_sync(0xffffffff, tid >> 5, 0), wgi = warp >> 2;
  Scratch* const g = P.g;
  if (elect_one()) {
    #pragma unroll
    for (int i = 0; i < 4; i++) mbar_init(sb + SM_BAR + warp * 32 + i * 8, 1 << ((0x333444000000ull >> (4 * warp)) & 7));
    if (warp == 0) { mbar_expect_tx(sb + B_WF, 2 * U); tma_load_2d(sb + 2 * U, &tmX, sb + B_WF, 0, qt * 128); }
    if (warp == 1) asm volatile("prefetch.tensormap [%0];" :: "l"(&tmWQ) : "memory");
    asm volatile("fence.mbarrier_init.release.cluster;" ::: "memory");
  }
  __syncwarp();
  cluster_arrive();
  cluster_wait();
  if (warp == 0 && elect_one()) {
    tma_load_3d_mc(sb + SM_W + rank * 8192, &tmWQ, sb + B_WF, 0, 0, hg * 8 + rank * 2);
    mbar_expect_tx(sb + B_WF + 8, U);
    tma_load_3d_mc(sb + SM_W + U + rank * 8192, &tmWQ, sb + B_WF + 8, 0, 32, hg * 8 + rank * 2);
  }
  if (wgi == 0) {
    asm volatile("setmaxnreg.dec.sync.aligned.u32 56;");
        if (warp == 3) {
      if (lane < 12) sts128(sb + SM_EXT + 1024 + (lane >= 6 ? 1024 - 96 : 0) + lane * 16, 0, 0, 0, 0);
      #pragma unroll 1
      for (int ps = 0; ps < 2; ps++) {
        const uint4* src = (const uint4*)(P.wq + (size_t)((qt >> 2) * 4 + (lane >> 3)) * (NH * DH) + hg * 512 + ps * 256 + (qt & 3) * 64) + (lane & 7);
        float cs[8];
        #pragma unroll
        for (int e = 0; e < 8; e++) cs[e] = 0.f;
        #pragma unroll 1
        for (int b = 0; b < 4; b++, src += 160 * 512) {
          uint4 w[10];
          #pragma unroll
          for (int i = 0; i < 10; i++) w[i] = ldg_nc(src + i * 16 * 512);
          #pragma unroll
          for (int i = 0; i < 10; i++) add8(cs, w[i]);
          if (b == 0) {
            mbar_wait(sb + B_EP, 0);
            if (!(lane & 8)) st_tagged(g->cs + (hg * 2 + ps) * 256 + qt * 16 + (lane & 7) * 2 + (lane >> 4), ~lds32(sb + SM_EP) & 1, 0, 0, 0);
          }
        }
        #pragma unroll
        for (int e = 0; e < 4; e++) {
          cs[e] = ((lane & 16) ? cs[e + 4] : cs[e]) + __shfl_xor_sync(0xffffffff, (lane & 16) ? cs[e] : cs[e + 4], 16);
          cs[e] += __shfl_xor_sync(0xffffffff, cs[e], 8);
        }
        mbar_wait(sb + B_EP, 0);
        const uint32_t tm = 0u - (lds32(sb + SM_EP) & 1);
        uint4* const gc = g->cs + (hg * 2 + ps) * 256;
        if (!(lane & 8)) st_tagged(gc + qt * 16 + (lane & 7) * 2 + (lane >> 4), (__float_as_uint(cs[0]) & ~1u) | (tm & 1), __float_as_uint(cs[1]), __float_as_uint(cs[2]), __float_as_uint(cs[3]));

        uint4 v[9];
        int it = 0;
        uint32_t miss;
        do {
          #pragma unroll
          for (int i = 0; i < 8; i++) v[i] = ld_tagged(gc + (i >> 1) * 64 + (i & 1) * 32 + lane);
          v[8] = ld_relaxed4(g->stat + qt * 128 + lane * 4);
          miss = (tag_miss(v[8].x, v[8].y, tm) | tag_miss(v[8].z, v[8].w, tm)) >> 31;
          #pragma unroll
          for (int i = 0; i < 8; i += 2) miss |= tag_miss(v[i].x, v[i+1].x, tm);
        } while (__any_sync(0xffffffff, miss & 1) && ++it < MAXPOLL);
        #pragma unroll
        for (int i = 0; i < 2; i++) {
          auto sum = [](uint32_t a, uint32_t b, uint32_t c, uint32_t d) { return (__uint_as_float(a) + __uint_as_float(b)) + (__uint_as_float(c) + __uint_as_float(d)); };
          const float c0 = sum(v[i].x, v[i+2].x, v[i+4].x, v[i+6].x), c1 = sum(v[i].y, v[i+2].y, v[i+4].y, v[i+6].y);
          const float c2 = sum(v[i].z, v[i+2].z, v[i+4].z, v[i+6].z), c3 = sum(v[i].w, v[i+2].w, v[i+4].w, v[i+6].w);
          const uint32_t h0 = pack_bf16(c0, c1), h1 = pack_bf16(c2, c3), a = sb + SM_EXT + ps * 1024 + i * 512 + (lane >> 1) * 32 + (lane & 1) * 8;
          asm volatile("st.shared.v2.u32 [%0], {%1,%2};" :: "r"(a), "r"(h0), "r"(h1) : "memory");
          asm volatile("st.shared.v2.u32 [%0], {%1,%2};" :: "r"(a + 16), "r"(pack_bf16(c0 - bf_lo(h0), c1 - bf_hi(h0))), "r"(pack_bf16(c2 - bf_lo(h1), c3 - bf_hi(h1))) : "memory");
        }
        sts128(sb + SM_STAT + lane * 16, v[8].x & 0x7fffffffu, v[8].y & 0x7fffffffu, v[8].z & 0x7fffffffu, v[8].w & 0x7fffffffu);
        proxy_fence();
        __syncwarp();
        if (lane == 0) mbar_arrive(sb + B_EXT + ps * 8);
        TRACE1(2, 6 + ps);
      }
    } else if (warp > 0) {
      mbar_wait(sb + B_WF, 0);
      if (warp == 1) {
        const __nv_bfloat16* const wp = P.wq + (size_t)((qt >> 2) * 4 + (lane & 3) + (lane >> 2) * 16) * (NH * DH) + hg * 512 + (qt & 3) * 64;
        #pragma unroll
        for (int i = 1; i < 5; i++) asm volatile("prefetch.global.L2 [%0];" :: "l"(wp + i * 128 * (NH * DH)) : "memory");
      }
      auto publish = [&](uint32_t w) { if (!(lane & 6)) st_relaxed(g->stat + qt * 128 + hg * 16 + (warp - 1) * 8 + (lane & 1) * 4 + ((lane >> 2) & 2) + (lane >> 4), w ^ (lds32(sb + SM_EP) << 31)); };
      mbar_wait(sb + B_EP, 0);
      publish(0x80000000u);
      uint32_t w0 = 0;
      #pragma unroll 1
      for (int b = 0; b < 2; b++) {
        const int row = qt * 128 + hg * 16 + (warp - 1) * 8 + b * 4 + (lane >> 4);
        uint4 v[2][5];
        #pragma unroll
        for (int i = 0; i < 10; i++) v[i & 1][i >> 1] = ldg_nc((const uint4*)(P.x + (size_t)(row + (i & 1) * 2) * DM) + (i >> 1) * 16 + (lane & 15));
        float x0[2], mb[2], sd[2];
        #pragma unroll
        for (int r = 0; r < 2; r++) {
          x0[r] = bf_lo(__shfl_sync(0xffffffff, v[r][0].x, lane & 16));
          mb[r] = sd[r] = 0.f;
          #pragma unroll
          for (int i = 0; i < 5; i++) {
            const uint32_t vw[4] = {v[r][i].x, v[r][i].y, v[r][i].z, v[r][i].w};
            #pragma unroll
            for (int e = 0; e < 4; e++) { const float d0 = bf_lo(vw[e]) - x0[r], d1 = bf_hi(vw[e]) - x0[r]; mb[r] += d0 + d1; sd[r] = fmaf(d0, d0, fmaf(d1, d1, sd[r])); }
          }
        }
        const bool up = lane & 8;
        float m1 = (up ? mb[1] : mb[0]) + __shfl_xor_sync(0xffffffff, up ? mb[0] : mb[1], 8), s1 = (up ? sd[1] : sd[0]) + __shfl_xor_sync(0xffffffff, up ? sd[0] : sd[1], 8);
        #pragma unroll
        for (int o = 4; o; o >>= 1) { m1 += __shfl_xor_sync(0xffffffff, m1, o); s1 += __shfl_xor_sync(0xffffffff, s1, o); }
        const float md = m1 * (1.f / DM), var = fmaxf(fmaf(-md, md, s1 * (1.f / DM)), 0.f);
        const uint32_t w = pack_bf16((up ? x0[1] : x0[0]) + md, sqrt_approx(rbf(rbf(var) + 1e-5f)));
        if ((lane & 1) == b) w0 = w;
      }
      publish(w0 & 0x7fffffffu);
      TRACE1(2, 8);
    }
    asm volatile("setmaxnreg.dec.sync.aligned.u32 24;");
    if (warp == 0) {
      const int row0 = hg * 4 * S_LEN;
      auto kv = [&](int isv, int j) {
        const uint32_t bar = sb + B_KF + isv * 16 + (j & 1) * 8;
        if (elect_one()) {
          mbar_expect_tx(bar, 2 * U);
          tma_load_2d_mc(sb + (isv ? SM_V + (j & 1) * 2 * U : (j & 1) * SM_K1) + rank * U, isv ? &tmV : &tmK, bar, rank * 64, row0 + j * 128);
        }
      };
      uint32_t s = 2, ph = 1;
      #pragma unroll 1
      for (int c = 1; c < 20; c++) {
        const int k = (c < 10 ? c : (c < 18 ? c - 8 : c - 18)) * 64, cb = hg * 8 + rank * 2 + (c < 10 ? 0 : 4);
        const bool wx = c < 10 || c >= 18;
        const uint32_t bar = sb + B_WF + s * 8, dst = sb + SM_W + rank * 8192 + s * U;
        mbar_wait(bar + (B_WE - B_WF), ph);
        if (elect_one()) {
          mbar_expect_tx(bar, wx ? 2 * U : U);
          tma_load_3d_mc(dst, &tmWQ, bar, 0, k, cb);
          if (wx) tma_load_2d(sb + ((c + 2) & 7) * U, &tmX, bar, k, qt * 128);
        }
        mbar_wait(bar + (B_WE - B_WF) + 8, ph);
        if (elect_one()) {
          mbar_expect_tx(bar + 8, U);
          tma_load_3d_mc(dst + U, &tmWQ, bar + 8, 0, k + 32, cb);
        }
        s += 2;
        if (s == 6) { s = 0; ph ^= 1; }
      }
      kv(0, 0);
      mbar_wait(sb + B_WE + 40, 1); kv(0, 1);
      mbar_wait(sb + B_WE + 8, 0); kv(1, 0);
      mbar_wait(sb + B_WE + 24, 0); kv(1, 1);
      mbar_wait(sb + B_KE, 0); kv(0, 2);
      #pragma unroll 1
      for (int j = 2; j < 64; j++) {
        if (j < 63) { mbar_wait(sb + B_KE + (~j & 1) * 8, ((j - 1) >> 1) & 1); kv(0, j + 1); }
        mbar_wait(sb + B_KE + 16 + (j & 1) * 8, (~j >> 1) & 1); kv(1, j);
      }
      s = 0; ph = 1;
      #pragma unroll 1
      for (int n = 0; n < (X_SKIP(qp) ? 2 : 40); n++) {
        const int st = n < 5 ? (n == 1) : n >> 2, h = n < 5 ? max(n - 1, 0) : n & 3;
        const int u = st < 2 ? 8 + st : ((hg + st - 1) & 7);
        mbar_wait(sb + (n < 6 ? B_KE + (n < 4 ? n >> 1 : 3) * 8 : B_CE + s * 8), ph);
        if (elect_one()) {
          mbar_expect_tx(sb + B_CF + s * 8, U);
          tma_load_2d_mc(sb + c_slot(s) * U + rank * 8192, &tmWO, sb + B_CF + s * 8, u * 64, hg * 512 + ((0x3021 >> (4 * h)) & 3) * 128 + rank * 64);
        }
        if (++s == 6) { s = 0; ph ^= 1; }
      }
      mbar_wait(sb + B_GATE, 0);
      asm volatile("fence.proxy.async.global;" ::: "memory");
      #pragma unroll 1
      for (int n = 0; n < (X_SKIP(qp) ? 0 : 2); n++) {
        mbar_wait(sb + B_CE + 32 + n * 8, 1);
        if (elect_one()) {
          mbar_expect_tx(sb + B_CF + 32 + n * 8, U);
          tma_load_2d(sb + (10 + n) * U, n ? &tmGate : &tmX, sb + B_CF + 32 + n * 8, hg * 64, qt * 128);
        }
      }
      if (!X_SKIP(qp)) {
        const uint4* const last = g->part + (size_t)(qt * 80 + hg * 8 + ((hg + 1) & 7)) * 1024;
        mbar_wait(sb + B_CE + 16, 0);
        if (elect_one()) {
          mbar_expect_tx(sb + B_CF + 8, U);
          asm volatile("cp.async.bulk.shared::cluster.global.mbarrier::complete_tx::bytes [%0], [%1], %2, [%3];" :: "r"(sb + U), "l"(last), "r"(U), "r"(sb + B_CF + 8) : "memory");
        }
      }
    } else if (!elect_one()) {
    } else if (warp == 1) {
      mbar_wait(sb + B_EXT, 0);
      l2_prefetch(P.k + (size_t)(hg * 4 * S_LEN + qt * (16 + 8 * KVPF)) * DH, 4096 + 2048 * KVPF);
      l2_prefetch(P.v + (size_t)(hg * 4 * S_LEN + qt * (16 + 8 * KVPF)) * DH, 4096 + 2048 * KVPF);
      flag_wait(&g->mod_done.v, lds32(sb + SM_EP) * 4);
      mbar_arrive(sb + B_GATE);
    } else if (warp == 3) {
      #pragma unroll 1
      for (int j = 2; j < 64 - KVPF; j++) {
        mbar_pace(sb + B_KE + (j & 1) * 8, (~j >> 1) & 1);
        const size_t o = (size_t)(hg * 4 * S_LEN + (j + KVPF) * 128 + qt * 8) * DH;
        if (KVPF) { l2_prefetch(P.k + o, 2048); l2_prefetch(P.v + o, 2048); }
        if (j >= 40 && j < 56) l2_prefetch(P.wo + (size_t)(hg * 512 + qt * 32 + (j - 40) * 2) * DM, 2 * DM * 2);
        if (j >= 56 && j < 60) l2_prefetch(((j & 1) ? P.x : g->gate) + (size_t)(qt * 128 + hg * 16 + (j & 2) * 4) * DM, 8 * DM * 2);
      }
    } else {
      #pragma unroll 1
      for (int h = 0; h < 4; h++) {
        mbar_wait(sb + B_OS, h & 1);
        proxy_fence();
        mbar_arrive(sb + B_OF);
      }
    }
    __syncwarp();
    if ((warp == 1 || warp == 2) && !X_SKIP(qp)) {
      mbar_wait(sb + B_GATE, 0);
      #pragma unroll 1
      for (int i = 0; i < 4; i++) {
        const int r = warp * 8 - 8 + (i & 1) * 4 + (lane >> 3);
        const uint32_t e = (qt * 128 + hg * 16 + r) * DM + (8 + (i >> 1)) * 64 + (lane & 7) * 8;
        if (!(i & 1)) bar_sync(8, 192);
        const uint4 xr = ldg_nc(P.x + e), gr = ld_relaxed4(g->gate + e), sv = lds128(sb + SM_BAR + 1024 + r * 128 + (((lane ^ r) & 7) << 4));
        *(uint4*)(P.out + e) = gated(xr, sv, gr);
        if (i == 1) bar_arrive(9, 192);
      }
    }
    cluster_arrive();
    cluster_wait();
  } else {
    const int wg = wgi - 1, t = tid & 127, cw = warp - 4;
    asm volatile("setmaxnreg.inc.sync.aligned.u32 224;");
    if (tid == 128) { sts32(sb + SM_BADF, 0); sts32(sb + SM_ONE, 1); sts32(sb + SM_EP, new_launch(g)); mbar_arrive(sb + B_EP); }
    __syncwarp();
    uint32_t q[32], p[32];
    float s[64], o[64], l[2] = {0.f, 0.f};
    const uint32_t rb = __shfl_sync(0xffffffff, map_cta(sb, lane & 1), lane), wr = sb + cw * 2048, qa = __shfl_sync(0xffffffff, wr + lane * 16, lane);
    uint32_t bad = 0;
    {
      uint32_t st0 = 0, st1 = 0;
      uint32_t sl = 0, ph = 0, rprev = 0;
      if (wg == 1) bar_arrive(1, 256);
      #pragma unroll
      for (int pass = 0; pass < 2; pass++) {
        float acc[128];
        #pragma unroll 1
        for (int i = 0; i < 10; i++) {
          if (i == (pass ? SKEW1 : SKEW0) / 2) {
            if (pass == 1) {
              const uint32_t d = qa + qo_slot(0);
              #pragma unroll
              for (int e = 0; e < 8; e++) sts128(d + (e >> 2) * U + (e & 3) * 512, p[4*e], p[4*e+1], p[4*e+2], p[4*e+3]);
            }
            bar_sync(1 + wg, 256);
          }
          const uint64_t a = desc(sb, ((i + 2 + 2 * pass) & 7) * 1024 + wg * 512 + doff(0, 16)), b = desc(sb, sl * 128 + doff(SM_W, 4096));
          mbar_wait(sb + B_WF + sl, ph);
          if (i == 0) TRACE(wg, 1 + pass);
          TRACEF(1, wg, 40 + pass * 20 + 2 * i);
          wg_fence();
          wgmma_ss_n256_tb<0, 0>(acc, a, b, i > 0);
          wgmma_ss_n256_tb<2, 128>(acc, a, b, 1);
          wg_commit();
          mbar_wait(sb + B_WF + 8 + sl, ph);
          wg_wait<1>();
          if (i > 0) release2(rprev, lane);
          TRACEF(1, wg, 41 + pass * 20 + 2 * i);
          wg_fence();
          wgmma_ss_n256_tb<4, 1024>(acc, a, b, 1);
          wgmma_ss_n256_tb<6, 1152>(acc, a, b, 1);
          wg_commit();
          rprev = rb + B_WE + 8 + sl;
          sl += 16;
          if (sl == 48) { sl = 0; ph ^= 1; }
          wg_wait<1>();
          release2(rprev - 8, lane);
        }
        if (pass == 1) asm volatile("setmaxnreg.inc.sync.aligned.u32 240;");
        mbar_wait(sb + B_EXT + pass * 8, 0);
        if (pass == 0) { st0 = lds32(sb + SM_STAT + (cw * 16 + (lane >> 2)) * 4); st1 = lds32(sb + SM_STAT + (cw * 16 + 8 + (lane >> 2)) * 4); }
        {
          const uint32_t a0 = (lane & 3) ? 0u : (__byte_perm(st0, 0, 0x1010) ^ 0x80008000u), a1 = (lane & 3) ? 0u : (__byte_perm(st1, 0, 0x1010) ^ 0x80008000u);
          wg_fence();
          wgmma_rs_n256_tb(acc, a0, a1, 0u, 0u, (uint64_t)desc_lo(sb + SM_EXT + pass * 1024, 0) | ((uint64_t)2 << 32), 1);
          wg_commit();
        }
        float rs0 = rcp_approx(bf_hi(st0)) * SCALE_LOG2E, rs1 = rcp_approx(bf_hi(st1)) * SCALE_LOG2E;
        bar_arrive(1 + (wg ^ 1), 256);
        wg_wait<0>();
        fence_regs(acc);
        release2(rprev, lane);
        if (pass == 0) {
          #pragma unroll
          for (int i = 0; i < 32; i++) {
            const float r = (i & 1) ? rs1 : rs0;
            q[i] = pack_bf16(acc[2*i] * r, acc[2*i+1] * r); p[i] = pack_bf16(acc[64+2*i] * r, acc[64+2*i+1] * r);
          }
        } else {
          const uint32_t d = qa + SM_QO;
          #pragma unroll
          for (int e = 0; e < 16; e++) {
            if (e == 8) {
              mbar_wait(sb + B_KF, 0);
              bar_sync(1 + wg, 256);
              TRACE(wg, 3);
              mma_qk<0, 2>(s, q, desc(sb, 2));
              bar_arrive(1 + (wg ^ 1), 256);
              const uint32_t one = lds32(sb + SM_ONE);
              rs0 = __uint_as_float(__float_as_uint(rs0) * one); rs1 = __uint_as_float(__float_as_uint(rs1) * one);
            }
            sts128(d + (e >> 2) * U + (e & 3) * 512, pack_bf16(acc[8*e] * rs0, acc[8*e+1] * rs0), pack_bf16(acc[8*e+2] * rs1, acc[8*e+3] * rs1),
                   pack_bf16(acc[8*e+4] * rs0, acc[8*e+5] * rs0), pack_bf16(acc[8*e+6] * rs1, acc[8*e+7] * rs1));
          }
          wg_wait<0>();
          fence_regs(s);
          release2(rb + B_KE, lane);
          exp_rows<0, 64>(s, l);
          #pragma unroll
          for (int i = 0; i < 32; i++) p[i] = pack_bf16(s[2*i], s[2*i+1]);
        }
      }
    }
    unsigned tz[3] = {0, 0, 0};
    bool ready = false;
    #pragma unroll 1
    for (int j = 1; ; j += 2) {
      int ph = 0;
      #pragma unroll 1
      do {
        attn_step<1, false>(sb, rb, wr, qa, wg, lane, j, ph, s, o, p, q, l, bad, ready, g, tz);
        ph ^= 1; j += 2;
        if (wg < 2) attn_step<0, false>(sb, rb, wr, qa, wg, lane, j - 1, ph, s, o, p, q, l, bad, ready, g, tz);
      } while ((j & 15) != 15);
      attn_step<1, true>(sb, rb, wr, qa, wg, lane, j, 1, s, o, p, q, l, bad, ready, g, tz);
      if (j == 63) break;
      if (wg < 2) attn_step<0, true>(sb, rb, wr, qa, wg, lane, j + 1, 0, s, o, p, q, l, bad, ready, g, tz);
    }
    mbar_wait(sb + B_OF, 0);
    mbar_wait(sb + B_CF + wg * 8, 0);
    mbar_wait(sb + B_KF + 24, 1);
    bar_sync(1 + wg, 256);
    TRACE(wg, 4);
    mma_pv<SM_V + 2 * U, 2>(o, p, desc(sb, 2), true);
    mma_c<3>(s, sb, wg, 0, 0);
    bar_arrive(1 + (wg ^ 1), 256);
    mbar_wait(sb + B_KE + 16, 1);
    const uint32_t redo = lds32(sb + SM_BADF), one = lds32(sb + SM_ONE), tag = lds32(sb + SM_EP) & 1;
    wg_wait<1>();
    fence_regs(o); fence_regs(p);
    release2(rb + B_KE + 24, lane);
    if (!finish_head(o, l[0], l[1], p, one)) bad |= 8u;
    store_o(wr, lane, SM_V, p);
    if (__builtin_expect(bar_any(4 + wg, 128, bad | redo), 0)) {
      wg_wait<0>();
      fence_regs(s);
      redo_heads(P, sb, bad, qt * 128 + cw * 16, hg * 4);
      #pragma unroll
      for (int i = 0; i < 64; i++) s[i] = 0.f;
      __syncwarp();
      if (lane == 0) mbar_arrive(sb + B_OS);
      mbar_wait(sb + B_OF, 1);
      mma_c<4>(s, sb, wg, 0, 0);
    } else if (lane == 0) mbar_arrive(sb + B_OS);
    wg_wait<0>();
    release2(rb + B_CE + wg * 8, lane);
    if (X_SKIP(qp)) { cluster_arrive(); } else {
      uint4* const part = g->part + (size_t)qt * 80 * 1024 + t;
      const uint32_t tm = 0u - tag;
      uint4 v[8];
      auto fetch = [&](uint4 (&v)[8], const uint4* from) {
        #pragma unroll
        for (int i = 0; i < 8; i++) v[i] = ld_tagged(from + i * 128);
      };
      auto verify = [&](uint4 (&v)[8], auto half, const uint4* from) {
        constexpr int b = decltype(half)::v * 4;
        #pragma unroll 1
        for (int it = 0; __any_sync(0xffffffff, or_bit0(tag_miss(v[b].x, v[b+1].x, tm), tag_miss(v[b+2].x, v[b+3].x, tm))) && it < MAXPOLL; it++) {
          #pragma unroll
          for (int i = b; i < b + 4; i++) v[i] = ld_tagged(from + i * 128);
        }
      };
      int sp = 6, sl = 2 + 3 * wg, ph = 0;
      auto quarter = [&](auto site, int h, int arrive_bar) {
        mbar_wait(sb + B_CF + sl * 8, ph);
        if (h == 0) bar_sync(1 + wg, 256);
        mma_c<decltype(site)::v>(s, sb, sl, h, arrive_bar);
        if (h) { wg_wait<1>(); release2(rb + B_CE + sp * 8, lane); }
        sp = sl;
        if (++sl == 6) { sl = 0; ph ^= 1; }
      };
      auto send = [&](int st) {
        uint4* dst = part + (st < 2 ? (8 + st) * 8192 + hg * 128 : (((hg + st - 1) & 7) * 8 + hg) * 1024);
        const int ds = st < 2 ? 1024 : 128;
        wg_wait<0>();
        fence_regs(s);
        TRACEF(4, wg, 106 + (st >> 1));
        release2(rb + B_CE + sp * 8, lane);
        #pragma unroll
        for (int i = 0; i < 8; i++, dst += ds)
          st_tagged(dst, (pack_bf16(s[8*i], s[8*i+1]) & ~1u) | tag, pack_bf16(s[8*i+2], s[8*i+3]), pack_bf16(s[8*i+4], s[8*i+5]), pack_bf16(s[8*i+6], s[8*i+7]));
        sl += st ? 4 : 3;
        if (sl >= 6) { sl -= 6; ph ^= 1; }
      };
      const uint32_t ta = ((lane >> 4) * 8 + (lane & 7)) * 128 + ((((cw & 3) * 2 + ((lane >> 3) & 1)) ^ (lane & 7)) << 4), ra = (t >> 3) * 128 + (((t & 7) ^ ((t >> 3) & 7)) << 4);
      TRACEF(4, wg, 112);
      bar_sync(1 + wg, 256);
      if (wg == 0) {
        #pragma unroll 1
        for (int st = 0; ; st += 2) {
          TRACEF(4, wg, 100 + (st >> 1));
          const uint4* const src = part + ((7 + (st >> 1)) * 8 + hg) * 1024;
          quarter(IC<5>{}, 1, 0);
          if (st == 2) fetch(v, src);
          quarter(IC<6>{}, 2, 0);
          if (st == 0) mbar_wait(sb + B_OF, 1);
          quarter(IC<7>{}, 3, 2);
          send(st);
          if (st == 8) break;
          if (st == 2 || st == 4) {
            float a[8];
            #pragma unroll
            for (int i = 0; i < 8; i++) a[i] = 0.f;
            static_for<0, 2>([&](auto hf) {
              verify(v, hf, src);
              #pragma unroll
              for (int i = decltype(hf)::v * 4; i < decltype(hf)::v * 4 + 4; i++) { add8(a, v[i]); if (st == 2) v[i] = ld_tagged(src + 8192 + i * 128); }
            });
            if (st == 4) bar_sync(9, 192);
            stsm4t(sb + SM_BAR + 1024 + ta, pack_bf16(a[0], a[1]), pack_bf16(a[2], a[3]), pack_bf16(a[4], a[5]), pack_bf16(a[6], a[7]));
            bar_arrive(8, 192);
          }
          quarter(IC<8>{}, 0, 0);
        }
        cluster_arrive();
        mbar_wait(sb + B_CF + 32, 0);
        mbar_wait(sb + B_CF + 40, 0);
        __nv_bfloat16* const op = P.out + (qt * 128 + (t >> 3)) * DM + hg * 64 + (t & 7) * 8;
        bar_sync(1, 256);
        uint4 xv[8];
        #pragma unroll
        for (int i = 0; i < 8; i++) { xv[i] = lds128(sb + 10 * U + i * 2048 + ra); v[i] = lds128(sb + 11 * U + i * 2048 + ra); }
        #pragma unroll
        for (int i = 0; i < 8; i++) {
          if (!(i & 3)) bar_sync(6 + (i >> 2), 256);
          *(uint4*)(op + i * 16 * DM) = gated(xv[i], lds128(sb + i * 2048 + ra), v[i]);
        }
      } else {
        float T[64];
        auto from = [&](int f) { return part + (hg * 8 + ((hg + 1 - f) & 7)) * 1024; };
        auto take = [&](uint4 (&v)[8], auto half, int f, bool more) {
          verify(v, half, from(f));
          const uint4* const nx = from(f + 1);
          #pragma unroll
          for (int i = decltype(half)::v * 4; i < decltype(half)::v * 4 + 4; i++) { add8(T + 8 * i, v[i]); if (more) v[i] = ld_tagged(nx + i * 128); }
        };
        #pragma unroll
        for (int i = 0; i < 64; i++) T[i] = 0.f;
        #pragma unroll 1
        for (int st = 1; ; st += 2) {
          TRACEF(4, wg, 100 + (st >> 1));
          quarter(IC<9>{}, 1, 0);
          if (st >= 5) take(v, IC<0>{}, st - 3, true);
          quarter(IC<10>{}, 2, 0);
          if (st >= 5) take(v, IC<1>{}, st - 3, true);
          if (st == 1) mbar_wait(sb + B_OF, 1);
          quarter(IC<11>{}, 3, st < 9);
          if (st < 9) send(st);
          if (st >= 5) { take(v, IC<0>{}, st - 2, st < 9); take(v, IC<1>{}, st - 2, st < 9); }
          else if (st == 3) fetch(v, from(2));
          if (st == 9) break;
          quarter(IC<12>{}, 0, 0);
        }
        cluster_arrive();
        TRACEF(4, wg, 113);
        wg_wait<0>();
        fence_regs(s);
        TRACEF(4, wg, 110);
        mbar_wait(sb + B_CF + 8, 1);
        #pragma unroll
        for (int i = 0; i < 8; i++) v[i] = lds128(sb + U + i * 2048 + t * 16);
        bar_arrive(1, 256);
        #pragma unroll
        for (int i = 0; i < 64; i++) T[i] += s[i];
        static_for<0, 2>([&](auto hf) {
          take(v, hf, 8, false);
          if (decltype(hf)::v == 0) TRACE(wg, 5);
          #pragma unroll
          for (int i = decltype(hf)::v * 4; i < decltype(hf)::v * 4 + 4; i++)
            stsm4t(sb + i * 2048 + ta, pack_bf16(T[8*i], T[8*i+1]), pack_bf16(T[8*i+2], T[8*i+3]), pack_bf16(T[8*i+4], T[8*i+5]), pack_bf16(T[8*i+6], T[8*i+7]));
          bar_arrive(6 + decltype(hf)::v, 256);
        });
      }
    }
    TRACE(wg, 6);
    cluster_wait();
  }
}

typedef CUresult (*EncodeFn)(CUtensorMap*, CUtensorMapDataType, cuuint32_t, void*, const cuuint64_t*, const cuuint64_t*, const cuuint32_t*, const cuuint32_t*,
                             CUtensorMapInterleave, CUtensorMapSwizzle, CUtensorMapL2promotion, CUtensorMapFloatOOBfill);
void make_map(EncodeFn enc, CUtensorMap* tm, const void* ptr, uint64_t inner, uint64_t outer, uint32_t box_outer, uint32_t blocks = 0) {
  cuuint64_t dims[3] = {blocks ? 64 : inner, outer, inner / 64}; cuuint64_t strides[2] = {inner * 2, 128};
  cuuint32_t box[3] = {64, box_outer, blocks}; cuuint32_t es[3] = {1, 1, 1};
  enc(tm, CU_TENSOR_MAP_DATA_TYPE_BFLOAT16, blocks ? 3 : 2, const_cast<void*>(ptr), dims, strides, box, es, CU_TENSOR_MAP_INTERLEAVE_NONE,
      CU_TENSOR_MAP_SWIZZLE_128B, CU_TENSOR_MAP_L2_PROMOTION_L2_256B, CU_TENSOR_MAP_FLOAT_OOB_FILL_NONE);
}

}

extern "C" void kernel_launch(void* const* d_in, const int* in_sizes, int n_in, void* d_out, int out_size) {
  (void)in_sizes; (void)n_in; (void)out_size;
  Params P;
  P.x = (const __nv_bfloat16*)d_in[0]; P.k = (const __nv_bfloat16*)d_in[1]; P.v = (const __nv_bfloat16*)d_in[2];
  P.wq = (const __nv_bfloat16*)d_in[3]; P.wo = (const __nv_bfloat16*)d_in[4]; P.wr = (const __nv_bfloat16*)d_in[6];
  P.out = (__nv_bfloat16*)d_out;
  cudaGetSymbolAddress((void**)&P.g, g_s);
  void* fn = nullptr; cudaDriverEntryPointQueryResult st;
  cudaGetDriverEntryPoint("cuTensorMapEncodeTiled", &fn, cudaEnableDefault, &st);
  EncodeFn enc = (EncodeFn)fn;
  CUtensorMap tmX, tmWQ, tmK, tmV, tmWO, tmG, tmU, tmD, tmGate;
  make_map(enc, &tmGate, P.g->gate, DM, S_LEN, 128);
  make_map(enc, &tmX, P.x, DM, S_LEN, 128);
  make_map(enc, &tmWQ, P.wq, NH * DH, DM, 32, 2);
  make_map(enc, &tmK, P.k, DH, (uint64_t)NH * S_LEN, 128);
  make_map(enc, &tmV, P.v, DH, (uint64_t)NH * S_LEN, 128);
  make_map(enc, &tmWO, P.wo, DM, NH * DH, 64);
  make_map(enc, &tmG, d_in[7], FF, DM, 128);
  make_map(enc, &tmU, d_in[8], FF, DM, 128);
  make_map(enc, &tmD, d_in[9], DM, FF, 128);
  cudaFuncSetAttribute(fused_kernel, cudaFuncAttributeMaxDynamicSharedMemorySize, SMEM_BYTES);
  fused_kernel<<<132, 384, SMEM_BYTES, cudaStreamPerThread>>>(tmX, tmWQ, tmK, tmV, tmWO, tmG, tmU, tmD, tmGate, P);
}
```

```cpp
#include <cuda_runtime.h>
#include <cuda_bf16.h>
#include <cuda.h>
#include <stdint.h>

#define C_EARLY 6
#define MAXPOLL (1 << 24)
#define SKEW0 18
#define SKEW1 18
#define DPOS 44
#define DPOSF 24
#define KVPF 4
#define ETEST 1
#define SMV 1
#define X_SKIP(qp) false
#define GST 2
#define W1SL 300
#define XPF 1
#define QSP 6
namespace {

constexpr int S_LEN = 2048, DM = 640, NH = 32, DH = 128, FF = 1728, TOPC = 8;
constexpr float SCALE_LOG2E = 0.08838834764831845f * 1.4426950408889634f;

struct alignas(128) Cnt { unsigned v; unsigned pad[31]; };
struct Scratch {
  uint4 part[16 * 10 * 8 * 1024];
  __nv_bfloat16 gate[S_LEN * DM];
  uint32_t stat[S_LEN];
  uint4 cs[NH * DH];
  float ypart[4 * TOPC * DM];
  uint4 q3[16 * 8 * 1024];
  uint32_t key[S_LEN];
  Cnt cnt_gate, cnt_mod, mod_done, q3_done[4];
  unsigned long long ticket;
};
__device__ Scratch g_s;

__device__ __forceinline__ uint32_t smem_u32(const void* p) { return (uint32_t)__cvta_generic_to_shared(p); }
template <class T> __device__ __forceinline__ T* at(const void* p, uint32_t off) { uint64_t r;
  asm("{\n.reg .u32 lo, hi;\nmov.b64 {lo, hi}, %1;\nadd.cc.u32 lo, lo, %2;\naddc.u32 hi, hi, 0;\nmov.b64 %0, {lo, hi};\n}\n" : "=l"(r) : "l"(p), "r"(off)); return (T*)r; }
__device__ __forceinline__ void mbar_init(uint32_t bar, uint32_t cnt) { asm volatile("mbarrier.init.shared::cta.b64 [%0], %1;" :: "r"(bar), "r"(cnt) : "memory"); }
__device__ __forceinline__ void mbar_expect_tx(uint32_t bar, uint32_t bytes) { asm volatile("mbarrier.arrive.expect_tx.shared::cta.b64 _, [%0], %1;" :: "r"(bar), "r"(bytes) : "memory"); }
__device__ __forceinline__ void mbar_arrive(uint32_t bar) { asm volatile("mbarrier.arrive.shared::cta.b64 _, [%0];" :: "r"(bar) : "memory"); }
__device__ __forceinline__ uint32_t map_cta(uint32_t a, uint32_t cta) { uint32_t r; asm volatile("mapa.shared::cluster.u32 %0, %1, %2;" : "=r"(r) : "r"(a), "r"(cta)); return r; }
__device__ __forceinline__ void mbar_arrive_cluster(uint32_t bar) { asm volatile("mbarrier.arrive.shared::cluster.b64 _, [%0];" :: "r"(bar) : "memory"); }
__device__ __forceinline__ void mbar_wait(uint32_t bar, uint32_t parity) {
  asm volatile("{\n.reg .pred p;\n.reg .u32 c;\nmov.u32 c, 0;\nLAB_WAIT:\nmbarrier.try_wait.parity.shared::cta.b64 p, [%0], %1;\n@p bra LAB_DONE;\n"
               "add.u32 c, c, 1;\nsetp.lt.u32 p, c, 16777216;\n@p bra LAB_WAIT;\ntrap;\nLAB_DONE:\n}\n" :: "r"(bar), "r"(parity) : "memory"); }
__device__ __forceinline__ bool mbar_test2(uint32_t bar0, uint32_t par0, uint32_t bar1, uint32_t par1) { uint32_t r;
  asm volatile("{\n.reg .pred p, q;\nmbarrier.test_wait.parity.shared::cta.b64 p, [%1], %2;\nmbarrier.test_wait.parity.shared::cta.b64 q, [%3], %4;\nand.pred p, p, q;\nselp.u32 %0, 1, 0, p;\n}\n"
               : "=r"(r) : "r"(bar0), "r"(par0), "r"(bar1), "r"(par1) : "memory"); return r; }
__device__ __forceinline__ void mbar_pace(uint32_t bar, uint32_t parity) {
  asm volatile("{\n.reg .pred p;\n.reg .u32 c;\nmov.u32 c, 0;\nLAB_WAIT:\nmbarrier.try_wait.parity.shared::cta.b64 p, [%0], %1;\n@p bra LAB_DONE;\n"
               "add.u32 c, c, 1;\nsetp.lt.u32 p, c, 4096;\n@p bra LAB_WAIT;\nLAB_DONE:\n}\n" :: "r"(bar), "r"(parity) : "memory"); }
__device__ __forceinline__ void flag_wait(const unsigned* p, unsigned target, unsigned ns = 500) {
  asm volatile("{\n.reg .pred p;\n.reg .u32 c, v;\nmov.u32 c, 0;\nLAB_WAIT:\nld.relaxed.gpu.global.u32 v, [%0];\nsub.u32 v, v, %1;\nsetp.ge.s32 p, v, 0;\n@p bra LAB_DONE;\n"
               "nanosleep.u32 %2;\nadd.u32 c, c, 1;\nsetp.lt.u32 p, c, 16777216;\n@p bra LAB_WAIT;\ntrap;\nLAB_DONE:\nld.acquire.gpu.global.u32 v, [%0];\n}\n" :: "l"(p), "r"(target), "r"(ns) : "memory"); }
__device__ __forceinline__ void flag_add_release(unsigned* p) { asm volatile("fence.acq_rel.gpu;\nred.relaxed.gpu.global.add.u32 [%0], 1;" :: "l"(p) : "memory"); }
__device__ __forceinline__ void tma_load_2d(uint32_t dst, const CUtensorMap* tm, uint32_t bar, int c0, int c1) {
  asm volatile("cp.async.bulk.tensor.2d.shared::cluster.global.mbarrier::complete_tx::bytes [%0], [%1, {%3, %4}], [%2];"
    :: "r"(dst), "l"(tm), "r"(bar), "r"(c0), "r"(c1) : "memory"); }
__device__ __forceinline__ void tma_load_2d_mc(uint32_t dst, const CUtensorMap* tm, uint32_t bar, int c0, int c1) {
  asm volatile("cp.async.bulk.tensor.2d.shared::cluster.global.mbarrier::complete_tx::bytes.multicast::cluster [%0], [%1, {%3, %4}], [%2], %5;"
    :: "r"(dst), "l"(tm), "r"(bar), "r"(c0), "r"(c1), "h"((uint16_t)3) : "memory"); }
__device__ __forceinline__ void tma_load_3d_mc(uint32_t dst, const CUtensorMap* tm, uint32_t bar, int c0, int c1, int c2) {
  asm volatile("cp.async.bulk.tensor.3d.shared::cluster.global.mbarrier::complete_tx::bytes.multicast::cluster [%0], [%1, {%3, %4, %5}], [%2], %6;"
    :: "r"(dst), "l"(tm), "r"(bar), "r"(c0), "r"(c1), "r"(c2), "h"((uint16_t)3) : "memory"); }
__device__ __forceinline__ void bulk_load(uint32_t dst, const void* src, uint32_t bytes, uint32_t bar) {
  asm volatile("cp.async.bulk.shared::cluster.global.mbarrier::complete_tx::bytes [%0], [%1], %2, [%3];" :: "r"(dst), "l"(src), "r"(bytes), "r"(bar) : "memory"); }
__device__ __forceinline__ void l2_prefetch(const void* p, uint32_t bytes) { asm volatile("cp.async.bulk.prefetch.L2.global [%0], %1;" :: "l"(p), "r"(bytes) : "memory"); }
__device__ __forceinline__ void wg_fence() { asm volatile("wgmma.fence.sync.aligned;" ::: "memory"); }
__device__ __forceinline__ void wg_commit() { asm volatile("wgmma.commit_group.sync.aligned;" ::: "memory"); }
template <int N> __device__ __forceinline__ void wg_wait() { asm volatile("wgmma.wait_group.sync.aligned %0;" :: "n"(N) : "memory"); }
__device__ __forceinline__ void bar_sync(int id, int n) { asm volatile("bar.sync %0, %1;" :: "r"(id), "r"(n) : "memory"); }
__device__ __forceinline__ void bar_arrive(int id, int n) { asm volatile("bar.arrive %0, %1;" :: "r"(id), "r"(n) : "memory"); }
__device__ __forceinline__ bool bar_any(int id, int n, uint32_t v) { uint32_t r;
  asm volatile("{\n.reg .pred p;\nsetp.ne.u32 p, %3, 0;\nbar.red.or.pred p, %1, %2, p;\nselp.u32 %0, 1, 0, p;\n}\n" : "=r"(r) : "r"(id), "r"(n), "r"(v) : "memory"); return r; }
__device__ __forceinline__ int sel_lt(int a, int b, int x, int y) { int r; asm("{\n.reg .pred p;\nsetp.lt.s32 p, %1, %2;\nselp.s32 %0, %3, %4, p;\n}\n" : "=r"(r) : "r"(a), "r"(b), "r"(x), "r"(y)); return r; }
__device__ __forceinline__ bool elect_one() { uint32_t r; asm volatile("{\n.reg .pred p;\nelect.sync _|p, 0xffffffff;\nselp.u32 %0, 1, 0, p;\n}\n" : "=r"(r)); return r; }
__device__ __forceinline__ void cluster_arrive() { asm volatile("barrier.cluster.arrive.relaxed.aligned;" ::: "memory"); }
__device__ __forceinline__ void cluster_wait() { asm volatile("barrier.cluster.wait.aligned;" ::: "memory"); }
__device__ __forceinline__ void proxy_fence() { asm volatile("fence.proxy.async.shared::cta;" ::: "memory"); }
__device__ __forceinline__ uint32_t pack_bf16(float lo, float hi) { uint32_t r; asm("cvt.rn.bf16x2.f32 %0, %1, %2;" : "=r"(r) : "f"(hi), "f"(lo)); return r; }
__device__ __forceinline__ float bf_lo(uint32_t v) { return __uint_as_float(v << 16); }
__device__ __forceinline__ float bf_hi(uint32_t v) { return __uint_as_float(v & 0xffff0000u); }
__device__ __forceinline__ void add8(float* a, const uint4& w) {
  a[0] += bf_lo(w.x); a[1] += bf_hi(w.x); a[2] += bf_lo(w.y); a[3] += bf_hi(w.y); a[4] += bf_lo(w.z); a[5] += bf_hi(w.z); a[6] += bf_lo(w.w); a[7] += bf_hi(w.w); }
__device__ __forceinline__ float rbf(float x) { return __bfloat162float(__float2bfloat16_rn(x)); }
__device__ __forceinline__ float ex2(float x) { float y; asm("ex2.approx.ftz.f32 %0, %1;" : "=f"(y) : "f"(x)); return y; }
__device__ __forceinline__ uint32_t lds32(uint32_t a) { uint32_t v; asm volatile("ld.shared.u32 %0, [%1];" : "=r"(v) : "r"(a) : "memory"); return v; }
__device__ __forceinline__ void sts32(uint32_t a, uint32_t v) { asm volatile("st.shared.u32 [%0], %1;" :: "r"(a), "r"(v) : "memory"); }
__device__ __forceinline__ uint4 lds128(uint32_t a) { uint4 v; asm volatile("ld.shared.v4.u32 {%0,%1,%2,%3}, [%4];" : "=r"(v.x), "=r"(v.y), "=r"(v.z), "=r"(v.w) : "r"(a) : "memory"); return v; }
__device__ __forceinline__ void sts128(uint32_t a, uint32_t x, uint32_t y, uint32_t z, uint32_t w) { asm volatile("st.shared.v4.u32 [%0], {%1,%2,%3,%4};" :: "r"(a), "r"(x), "r"(y), "r"(z), "r"(w) : "memory"); }
__device__ __forceinline__ void st_tagged(uint4* p, uint32_t x, uint32_t y, uint32_t z, uint32_t w) {
  asm volatile("st.relaxed.gpu.global.v4.u32 [%0], {%1,%2,%3,%4};" :: "l"(p), "r"(x), "r"(y), "r"(z), "r"(w) : "memory"); }
__device__ __forceinline__ uint4 ld_tagged(const uint4* p) { uint4 v;
  asm volatile("{\n.reg .b128 v;\nld.relaxed.gpu.global.b128 v, [%4];\nmov.b128 {%0,%1,%2,%3}, v;\n}\n" : "=r"(v.x), "=r"(v.y), "=r"(v.z), "=r"(v.w) : "l"(p) : "memory"); return v; }
__device__ __forceinline__ uint4 ld_relaxed4(const void* p) { uint4 v;
  asm volatile("ld.relaxed.gpu.global.v4.u32 {%0,%1,%2,%3}, [%4];" : "=r"(v.x), "=r"(v.y), "=r"(v.z), "=r"(v.w) : "l"(p) : "memory"); return v; }
__device__ __forceinline__ uint4 ldg_nc(const void* p) { uint4 v;
  asm volatile("ld.global.nc.L1::no_allocate.v4.u32 {%0,%1,%2,%3}, [%4];" : "=r"(v.x), "=r"(v.y), "=r"(v.z), "=r"(v.w) : "l"(p) : "memory"); return v; }
__device__ __forceinline__ uint32_t ldg32(const void* p) { uint32_t v; asm volatile("ld.relaxed.gpu.global.u32 %0, [%1];" : "=r"(v) : "l"(p) : "memory"); return v; }
__device__ __forceinline__ void stg128(void* p, const uint4& v) { asm volatile("st.global.v4.u32 [%0], {%1,%2,%3,%4};" :: "l"(p), "r"(v.x), "r"(v.y), "r"(v.z), "r"(v.w) : "memory"); }
__device__ __forceinline__ void st_relaxed(uint32_t* p, uint32_t v) { asm volatile("st.relaxed.gpu.global.u32 [%0], %1;" :: "l"(p), "r"(v) : "memory"); }
__device__ __forceinline__ uint32_t mul_bf2(uint32_t a, uint32_t b) { uint32_t r; asm("mul.rn.bf16x2 %0, %1, %2;" : "=r"(r) : "r"(a), "r"(b)); return r; }
__device__ __forceinline__ uint32_t add_bf2(uint32_t a, uint32_t b) { uint32_t r; asm("add.rn.bf16x2 %0, %1, %2;" : "=r"(r) : "r"(a), "r"(b)); return r; }
__device__ __forceinline__ uint32_t sub_bf2(uint32_t a, uint32_t b) { uint32_t r; asm("sub.rn.bf16x2 %0, %1, %2;" : "=r"(r) : "r"(a), "r"(b)); return r; }
__device__ __forceinline__ void stsm4(uint32_t a, uint32_t r0, uint32_t r1, uint32_t r2, uint32_t r3) {
  asm volatile("stmatrix.sync.aligned.m8n8.x4.shared.b16 [%0], {%1,%2,%3,%4};" :: "r"(a), "r"(r0), "r"(r1), "r"(r2), "r"(r3) : "memory"); }
__device__ __forceinline__ void stsm4t(uint32_t a, uint32_t r0, uint32_t r1, uint32_t r2, uint32_t r3) {
  asm volatile("stmatrix.sync.aligned.m8n8.x4.trans.shared.b16 [%0], {%1,%2,%3,%4};" :: "r"(a), "r"(r0), "r"(r1), "r"(r2), "r"(r3) : "memory"); }
__device__ __forceinline__ uint4 gated(const uint4& x, const uint4& s, const uint4& g) {
  return make_uint4(add_bf2(x.x, mul_bf2(s.x, g.x)), add_bf2(x.y, mul_bf2(s.y, g.y)), add_bf2(x.z, mul_bf2(s.z, g.z)), add_bf2(x.w, mul_bf2(s.w, g.w))); }
__device__ __forceinline__ uint32_t or_bit0(uint32_t a, uint32_t b) { uint32_t d; asm("lop3.b32 %0, %1, %2, 1, 0xA8;" : "=r"(d) : "r"(a), "r"(b)); return d; }
__device__ __forceinline__ uint32_t tag_miss(uint32_t a, uint32_t b, uint32_t tm) { uint32_t d; asm("lop3.b32 %0, %1, %2, %3, 0x7E;" : "=r"(d) : "r"(a), "r"(b), "r"(tm)); return d; }
template <int R> __device__ __forceinline__ void fence_regs(float (&d)[R]) {
  #pragma unroll
  for (int i = 0; i < R; i++) asm volatile("" : "+f"(d[i]) :: "memory"); }
template <int R> __device__ __forceinline__ void fence_regs(uint32_t (&d)[R]) {
  #pragma unroll
  for (int i = 0; i < R; i++) asm volatile("" : "+r"(d[i]) :: "memory"); }
__device__ __forceinline__ uint32_t desc_lo(uint32_t addr, uint32_t lbo_bytes) { return ((addr & 0x3FFFF) >> 4) | ((lbo_bytes >> 4) << 16); }
__device__ __forceinline__ uint64_t desc(uint32_t sb, uint32_t var = 0) {
  uint64_t d; asm("mov.b64 %0, {%1, %2};" : "=l"(d) : "r"(desc_lo(sb, 0) + var), "r"(0x40000040u)); return d; }
__host__ __device__ constexpr int doff(uint32_t off, uint32_t lbo_bytes) { return (off >> 4) | ((lbo_bytes >> 4) << 16); }
__device__ __forceinline__ float rcp_approx(float x) { float y; asm("rcp.approx.f32 %0, %1;" : "=f"(y) : "f"(x)); return y; }
__device__ __forceinline__ float rcp_fast(float x) { float y; asm("rcp.approx.ftz.f32 %0, %1;" : "=f"(y) : "f"(x)); return y; }
__device__ __forceinline__ float sqrt_approx(float x) { float y; asm("sqrt.approx.f32 %0, %1;" : "=f"(y) : "f"(x)); return y; }
__device__ __forceinline__ float sigmoid_f(float z) { return rcp_fast(1.f + ex2(z * -1.4426950408889634f)); }
__device__ __forceinline__ uint32_t norm2(uint32_t x, uint32_t mean2, float rsd) { const uint32_t d = sub_bf2(x, mean2); return pack_bf16(bf_lo(d) * rsd, bf_hi(d) * rsd); }
#define TRACE(w, i)
#define TRACE1(w, i)
#define TRACEF(m, w, i)

template <int OA, int OB> __device__ __forceinline__ void wgmma_ss_tb(float (&d)[128], uint64_t da, uint64_t db, int sd) {
  asm volatile("{\n.reg .pred p;\n.reg .b64 a, b;\nadd.s64 a, %128, %131;\nadd.s64 b, %129, %132;\nsetp.ne.b32 p, %130, 0;\n"
    "wgmma.mma_async.sync.aligned.m64n256k16.f32.bf16.bf16 {%0, %1, %2, %3, %4, %5, %6, %7, %8, %9, %10, %11, %12, %13, %14, %15, %16, %17, %18, %19, %20, %21, %22, %23, %24, %25, %26, %27, %28, %29, %30, %31, %32, %33, %34, %35, %36, %37, %38, %39, %40, %41, %42, %43, %44, %45, %46, %47, %48, %49, %50, %51, %52, %53, %54, %55, %56, %57, %58, %59, %60, %61, %62, %63, %64, %65, %66, %67, %68, %69, %70, %71, %72, %73, %74, %75, %76, %77, %78, %79, %80, %81, %82, %83, %84, %85, %86, %87, %88, %89, %90, %91, %92, %93, %94, %95, %96, %97, %98, %99, %100, %101, %102, %103, %104, %105, %106, %107, %108, %109, %110, %111, %112, %113, %114, %115, %116, %117, %118, %119, %120, %121, %122, %123, %124, %125, %126, %127}, a, b, p, 1, 1, 0, 1;\n}\n"
    : "+f"(d[0]), "+f"(d[1]), "+f"(d[2]), "+f"(d[3]), "+f"(d[4]), "+f"(d[5]), "+f"(d[6]), "+f"(d[7]), "+f"(d[8]), "+f"(d[9]), "+f"(d[10]), "+f"(d[11]), "+f"(d[12]), "+f"(d[13]), "+f"(d[14]), "+f"(d[15]), "+f"(d[16]), "+f"(d[17]), "+f"(d[18]), "+f"(d[19]), "+f"(d[20]), "+f"(d[21]), "+f"(d[22]), "+f"(d[23]), "+f"(d[24]), "+f"(d[25]), "+f"(d[26]), "+f"(d[27]), "+f"(d[28]), "+f"(d[29]), "+f"(d[30]), "+f"(d[31]), "+f"(d[32]), "+f"(d[33]), "+f"(d[34]), "+f"(d[35]), "+f"(d[36]), "+f"(d[37]), "+f"(d[38]), "+f"(d[39]), "+f"(d[40]), "+f"(d[41]), "+f"(d[42]), "+f"(d[43]), "+f"(d[44]), "+f"(d[45]), "+f"(d[46]), "+f"(d[47]), "+f"(d[48]), "+f"(d[49]), "+f"(d[50]), "+f"(d[51]), "+f"(d[52]), "+f"(d[53]), "+f"(d[54]), "+f"(d[55]), "+f"(d[56]), "+f"(d[57]), "+f"(d[58]), "+f"(d[59]), "+f"(d[60]), "+f"(d[61]), "+f"(d[62]), "+f"(d[63]), "+f"(d[64]), "+f"(d[65]), "+f"(d[66]), "+f"(d[67]), "+f"(d[68]), "+f"(d[69]), "+f"(d[70]), "+f"(d[71]), "+f"(d[72]), "+f"(d[73]), "+f"(d[74]), "+f"(d[75]), "+f"(d[76]), "+f"(d[77]), "+f"(d[78]), "+f"(d[79]), "+f"(d[80]), "+f"(d[81]), "+f"(d[82]), "+f"(d[83]), "+f"(d[84]), "+f"(d[85]), "+f"(d[86]), "+f"(d[87]), "+f"(d[88]), "+f"(d[89]), "+f"(d[90]), "+f"(d[91]), "+f"(d[92]), "+f"(d[93]), "+f"(d[94]), "+f"(d[95]), "+f"(d[96]), "+f"(d[97]), "+f"(d[98]), "+f"(d[99]), "+f"(d[100]), "+f"(d[101]), "+f"(d[102]), "+f"(d[103]), "+f"(d[104]), "+f"(d[105]), "+f"(d[106]), "+f"(d[107]), "+f"(d[108]), "+f"(d[109]), "+f"(d[110]), "+f"(d[111]), "+f"(d[112]), "+f"(d[113]), "+f"(d[114]), "+f"(d[115]), "+f"(d[116]), "+f"(d[117]), "+f"(d[118]), "+f"(d[119]), "+f"(d[120]), "+f"(d[121]), "+f"(d[122]), "+f"(d[123]), "+f"(d[124]), "+f"(d[125]), "+f"(d[126]), "+f"(d[127])
    : "l"(da), "l"(db), "r"(sd), "n"(OA), "n"(OB));
}
template <int OB> __device__ __forceinline__ void wgmma_rs_tb(float (&d)[128], uint32_t a0, uint32_t a1, uint32_t a2, uint32_t a3, uint64_t db, int sd) {
  asm volatile("{\n.reg .pred p;\n.reg .b64 b;\nadd.s64 b, %132, %134;\nsetp.ne.b32 p, %133, 0;\n"
    "wgmma.mma_async.sync.aligned.m64n256k16.f32.bf16.bf16 {%0, %1, %2, %3, %4, %5, %6, %7, %8, %9, %10, %11, %12, %13, %14, %15, %16, %17, %18, %19, %20, %21, %22, %23, %24, %25, %26, %27, %28, %29, %30, %31, %32, %33, %34, %35, %36, %37, %38, %39, %40, %41, %42, %43, %44, %45, %46, %47, %48, %49, %50, %51, %52, %53, %54, %55, %56, %57, %58, %59, %60, %61, %62, %63, %64, %65, %66, %67, %68, %69, %70, %71, %72, %73, %74, %75, %76, %77, %78, %79, %80, %81, %82, %83, %84, %85, %86, %87, %88, %89, %90, %91, %92, %93, %94, %95, %96, %97, %98, %99, %100, %101, %102, %103, %104, %105, %106, %107, %108, %109, %110, %111, %112, %113, %114, %115, %116, %117, %118, %119, %120, %121, %122, %123, %124, %125, %126, %127}, {%128, %129, %130, %131}, b, p, 1, 1, 1;\n}\n"
    : "+f"(d[0]), "+f"(d[1]), "+f"(d[2]), "+f"(d[3]), "+f"(d[4]), "+f"(d[5]), "+f"(d[6]), "+f"(d[7]), "+f"(d[8]), "+f"(d[9]), "+f"(d[10]), "+f"(d[11]), "+f"(d[12]), "+f"(d[13]), "+f"(d[14]), "+f"(d[15]), "+f"(d[16]), "+f"(d[17]), "+f"(d[18]), "+f"(d[19]), "+f"(d[20]), "+f"(d[21]), "+f"(d[22]), "+f"(d[23]), "+f"(d[24]), "+f"(d[25]), "+f"(d[26]), "+f"(d[27]), "+f"(d[28]), "+f"(d[29]), "+f"(d[30]), "+f"(d[31]), "+f"(d[32]), "+f"(d[33]), "+f"(d[34]), "+f"(d[35]), "+f"(d[36]), "+f"(d[37]), "+f"(d[38]), "+f"(d[39]), "+f"(d[40]), "+f"(d[41]), "+f"(d[42]), "+f"(d[43]), "+f"(d[44]), "+f"(d[45]), "+f"(d[46]), "+f"(d[47]), "+f"(d[48]), "+f"(d[49]), "+f"(d[50]), "+f"(d[51]), "+f"(d[52]), "+f"(d[53]), "+f"(d[54]), "+f"(d[55]), "+f"(d[56]), "+f"(d[57]), "+f"(d[58]), "+f"(d[59]), "+f"(d[60]), "+f"(d[61]), "+f"(d[62]), "+f"(d[63]), "+f"(d[64]), "+f"(d[65]), "+f"(d[66]), "+f"(d[67]), "+f"(d[68]), "+f"(d[69]), "+f"(d[70]), "+f"(d[71]), "+f"(d[72]), "+f"(d[73]), "+f"(d[74]), "+f"(d[75]), "+f"(d[76]), "+f"(d[77]), "+f"(d[78]), "+f"(d[79]), "+f"(d[80]), "+f"(d[81]), "+f"(d[82]), "+f"(d[83]), "+f"(d[84]), "+f"(d[85]), "+f"(d[86]), "+f"(d[87]), "+f"(d[88]), "+f"(d[89]), "+f"(d[90]), "+f"(d[91]), "+f"(d[92]), "+f"(d[93]), "+f"(d[94]), "+f"(d[95]), "+f"(d[96]), "+f"(d[97]), "+f"(d[98]), "+f"(d[99]), "+f"(d[100]), "+f"(d[101]), "+f"(d[102]), "+f"(d[103]), "+f"(d[104]), "+f"(d[105]), "+f"(d[106]), "+f"(d[107]), "+f"(d[108]), "+f"(d[109]), "+f"(d[110]), "+f"(d[111]), "+f"(d[112]), "+f"(d[113]), "+f"(d[114]), "+f"(d[115]), "+f"(d[116]), "+f"(d[117]), "+f"(d[118]), "+f"(d[119]), "+f"(d[120]), "+f"(d[121]), "+f"(d[122]), "+f"(d[123]), "+f"(d[124]), "+f"(d[125]), "+f"(d[126]), "+f"(d[127])
    : "r"(a0), "r"(a1), "r"(a2), "r"(a3), "l"(db), "r"(sd), "n"(OB));
}
template <int OA, int OB> __device__ __forceinline__ void wgmma_ss_tb(float (&d)[96], uint64_t da, uint64_t db, int sd) {
  asm volatile("{\n.reg .pred p;\n.reg .b64 a, b;\nadd.s64 a, %96, %99;\nadd.s64 b, %97, %100;\nsetp.ne.b32 p, %98, 0;\n"
    "wgmma.mma_async.sync.aligned.m64n192k16.f32.bf16.bf16 {%0, %1, %2, %3, %4, %5, %6, %7, %8, %9, %10, %11, %12, %13, %14, %15, %16, %17, %18, %19, %20, %21, %22, %23, %24, %25, %26, %27, %28, %29, %30, %31, %32, %33, %34, %35, %36, %37, %38, %39, %40, %41, %42, %43, %44, %45, %46, %47, %48, %49, %50, %51, %52, %53, %54, %55, %56, %57, %58, %59, %60, %61, %62, %63, %64, %65, %66, %67, %68, %69, %70, %71, %72, %73, %74, %75, %76, %77, %78, %79, %80, %81, %82, %83, %84, %85, %86, %87, %88, %89, %90, %91, %92, %93, %94, %95}, a, b, p, 1, 1, 0, 1;\n}\n"
    : "+f"(d[0]), "+f"(d[1]), "+f"(d[2]), "+f"(d[3]), "+f"(d[4]), "+f"(d[5]), "+f"(d[6]), "+f"(d[7]), "+f"(d[8]), "+f"(d[9]), "+f"(d[10]), "+f"(d[11]), "+f"(d[12]), "+f"(d[13]), "+f"(d[14]), "+f"(d[15]), "+f"(d[16]), "+f"(d[17]), "+f"(d[18]), "+f"(d[19]), "+f"(d[20]), "+f"(d[21]), "+f"(d[22]), "+f"(d[23]), "+f"(d[24]), "+f"(d[25]), "+f"(d[26]), "+f"(d[27]), "+f"(d[28]), "+f"(d[29]), "+f"(d[30]), "+f"(d[31]), "+f"(d[32]), "+f"(d[33]), "+f"(d[34]), "+f"(d[35]), "+f"(d[36]), "+f"(d[37]), "+f"(d[38]), "+f"(d[39]), "+f"(d[40]), "+f"(d[41]), "+f"(d[42]), "+f"(d[43]), "+f"(d[44]), "+f"(d[45]), "+f"(d[46]), "+f"(d[47]), "+f"(d[48]), "+f"(d[49]), "+f"(d[50]), "+f"(d[51]), "+f"(d[52]), "+f"(d[53]), "+f"(d[54]), "+f"(d[55]), "+f"(d[56]), "+f"(d[57]), "+f"(d[58]), "+f"(d[59]), "+f"(d[60]), "+f"(d[61]), "+f"(d[62]), "+f"(d[63]), "+f"(d[64]), "+f"(d[65]), "+f"(d[66]), "+f"(d[67]), "+f"(d[68]), "+f"(d[69]), "+f"(d[70]), "+f"(d[71]), "+f"(d[72]), "+f"(d[73]), "+f"(d[74]), "+f"(d[75]), "+f"(d[76]), "+f"(d[77]), "+f"(d[78]), "+f"(d[79]), "+f"(d[80]), "+f"(d[81]), "+f"(d[82]), "+f"(d[83]), "+f"(d[84]), "+f"(d[85]), "+f"(d[86]), "+f"(d[87]), "+f"(d[88]), "+f"(d[89]), "+f"(d[90]), "+f"(d[91]), "+f"(d[92]), "+f"(d[93]), "+f"(d[94]), "+f"(d[95])
    : "l"(da), "l"(db), "r"(sd), "n"(OA), "n"(OB));
}
template <int OB> __device__ __forceinline__ void wgmma_rs_tb(float (&d)[96], uint32_t a0, uint32_t a1, uint32_t a2, uint32_t a3, uint64_t db, int sd) {
  asm volatile("{\n.reg .pred p;\n.reg .b64 b;\nadd.s64 b, %100, %102;\nsetp.ne.b32 p, %101, 0;\n"
    "wgmma.mma_async.sync.aligned.m64n192k16.f32.bf16.bf16 {%0, %1, %2, %3, %4, %5, %6, %7, %8, %9, %10, %11, %12, %13, %14, %15, %16, %17, %18, %19, %20, %21, %22, %23, %24, %25, %26, %27, %28, %29, %30, %31, %32, %33, %34, %35, %36, %37, %38, %39, %40, %41, %42, %43, %44, %45, %46, %47, %48, %49, %50, %51, %52, %53, %54, %55, %56, %57, %58, %59, %60, %61, %62, %63, %64, %65, %66, %67, %68, %69, %70, %71, %72, %73, %74, %75, %76, %77, %78, %79, %80, %81, %82, %83, %84, %85, %86, %87, %88, %89, %90, %91, %92, %93, %94, %95}, {%96, %97, %98, %99}, b, p, 1, 1, 1;\n}\n"
    : "+f"(d[0]), "+f"(d[1]), "+f"(d[2]), "+f"(d[3]), "+f"(d[4]), "+f"(d[5]), "+f"(d[6]), "+f"(d[7]), "+f"(d[8]), "+f"(d[9]), "+f"(d[10]), "+f"(d[11]), "+f"(d[12]), "+f"(d[13]), "+f"(d[14]), "+f"(d[15]), "+f"(d[16]), "+f"(d[17]), "+f"(d[18]), "+f"(d[19]), "+f"(d[20]), "+f"(d[21]), "+f"(d[22]), "+f"(d[23]), "+f"(d[24]), "+f"(d[25]), "+f"(d[26]), "+f"(d[27]), "+f"(d[28]), "+f"(d[29]), "+f"(d[30]), "+f"(d[31]), "+f"(d[32]), "+f"(d[33]), "+f"(d[34]), "+f"(d[35]), "+f"(d[36]), "+f"(d[37]), "+f"(d[38]), "+f"(d[39]), "+f"(d[40]), "+f"(d[41]), "+f"(d[42]), "+f"(d[43]), "+f"(d[44]), "+f"(d[45]), "+f"(d[46]), "+f"(d[47]), "+f"(d[48]), "+f"(d[49]), "+f"(d[50]), "+f"(d[51]), "+f"(d[52]), "+f"(d[53]), "+f"(d[54]), "+f"(d[55]), "+f"(d[56]), "+f"(d[57]), "+f"(d[58]), "+f"(d[59]), "+f"(d[60]), "+f"(d[61]), "+f"(d[62]), "+f"(d[63]), "+f"(d[64]), "+f"(d[65]), "+f"(d[66]), "+f"(d[67]), "+f"(d[68]), "+f"(d[69]), "+f"(d[70]), "+f"(d[71]), "+f"(d[72]), "+f"(d[73]), "+f"(d[74]), "+f"(d[75]), "+f"(d[76]), "+f"(d[77]), "+f"(d[78]), "+f"(d[79]), "+f"(d[80]), "+f"(d[81]), "+f"(d[82]), "+f"(d[83]), "+f"(d[84]), "+f"(d[85]), "+f"(d[86]), "+f"(d[87]), "+f"(d[88]), "+f"(d[89]), "+f"(d[90]), "+f"(d[91]), "+f"(d[92]), "+f"(d[93]), "+f"(d[94]), "+f"(d[95])
    : "r"(a0), "r"(a1), "r"(a2), "r"(a3), "l"(db), "r"(sd), "n"(OB));
}
template <int OA, int OB> __device__ __forceinline__ void wgmma_ss_tb(float (&d)[64], uint64_t da, uint64_t db, int sd) {
  asm volatile("{\n.reg .pred p;\n.reg .b64 a, b;\nadd.s64 a, %64, %67;\nadd.s64 b, %65, %68;\nsetp.ne.b32 p, %66, 0;\n"
    "wgmma.mma_async.sync.aligned.m64n128k16.f32.bf16.bf16 {%0, %1, %2, %3, %4, %5, %6, %7, %8, %9, %10, %11, %12, %13, %14, %15, %16, %17, %18, %19, %20, %21, %22, %23, %24, %25, %26, %27, %28, %29, %30, %31, %32, %33, %34, %35, %36, %37, %38, %39, %40, %41, %42, %43, %44, %45, %46, %47, %48, %49, %50, %51, %52, %53, %54, %55, %56, %57, %58, %59, %60, %61, %62, %63}, a, b, p, 1, 1, 0, 1;\n}\n"
    : "+f"(d[0]), "+f"(d[1]), "+f"(d[2]), "+f"(d[3]), "+f"(d[4]), "+f"(d[5]), "+f"(d[6]), "+f"(d[7]), "+f"(d[8]), "+f"(d[9]), "+f"(d[10]), "+f"(d[11]), "+f"(d[12]), "+f"(d[13]), "+f"(d[14]), "+f"(d[15]), "+f"(d[16]), "+f"(d[17]), "+f"(d[18]), "+f"(d[19]), "+f"(d[20]), "+f"(d[21]), "+f"(d[22]), "+f"(d[23]), "+f"(d[24]), "+f"(d[25]), "+f"(d[26]), "+f"(d[27]), "+f"(d[28]), "+f"(d[29]), "+f"(d[30]), "+f"(d[31]), "+f"(d[32]), "+f"(d[33]), "+f"(d[34]), "+f"(d[35]), "+f"(d[36]), "+f"(d[37]), "+f"(d[38]), "+f"(d[39]), "+f"(d[40]), "+f"(d[41]), "+f"(d[42]), "+f"(d[43]), "+f"(d[44]), "+f"(d[45]), "+f"(d[46]), "+f"(d[47]), "+f"(d[48]), "+f"(d[49]), "+f"(d[50]), "+f"(d[51]), "+f"(d[52]), "+f"(d[53]), "+f"(d[54]), "+f"(d[55]), "+f"(d[56]), "+f"(d[57]), "+f"(d[58]), "+f"(d[59]), "+f"(d[60]), "+f"(d[61]), "+f"(d[62]), "+f"(d[63])
    : "l"(da), "l"(db), "r"(sd), "n"(OA), "n"(OB));
}
template <int OB> __device__ __forceinline__ void wgmma_rs_tb(float (&d)[64], uint32_t a0, uint32_t a1, uint32_t a2, uint32_t a3, uint64_t db, int sd) {
  asm volatile("{\n.reg .pred p;\n.reg .b64 b;\nadd.s64 b, %68, %70;\nsetp.ne.b32 p, %69, 0;\n"
    "wgmma.mma_async.sync.aligned.m64n128k16.f32.bf16.bf16 {%0, %1, %2, %3, %4, %5, %6, %7, %8, %9, %10, %11, %12, %13, %14, %15, %16, %17, %18, %19, %20, %21, %22, %23, %24, %25, %26, %27, %28, %29, %30, %31, %32, %33, %34, %35, %36, %37, %38, %39, %40, %41, %42, %43, %44, %45, %46, %47, %48, %49, %50, %51, %52, %53, %54, %55, %56, %57, %58, %59, %60, %61, %62, %63}, {%64, %65, %66, %67}, b, p, 1, 1, 1;\n}\n"
    : "+f"(d[0]), "+f"(d[1]), "+f"(d[2]), "+f"(d[3]), "+f"(d[4]), "+f"(d[5]), "+f"(d[6]), "+f"(d[7]), "+f"(d[8]), "+f"(d[9]), "+f"(d[10]), "+f"(d[11]), "+f"(d[12]), "+f"(d[13]), "+f"(d[14]), "+f"(d[15]), "+f"(d[16]), "+f"(d[17]), "+f"(d[18]), "+f"(d[19]), "+f"(d[20]), "+f"(d[21]), "+f"(d[22]), "+f"(d[23]), "+f"(d[24]), "+f"(d[25]), "+f"(d[26]), "+f"(d[27]), "+f"(d[28]), "+f"(d[29]), "+f"(d[30]), "+f"(d[31]), "+f"(d[32]), "+f"(d[33]), "+f"(d[34]), "+f"(d[35]), "+f"(d[36]), "+f"(d[37]), "+f"(d[38]), "+f"(d[39]), "+f"(d[40]), "+f"(d[41]), "+f"(d[42]), "+f"(d[43]), "+f"(d[44]), "+f"(d[45]), "+f"(d[46]), "+f"(d[47]), "+f"(d[48]), "+f"(d[49]), "+f"(d[50]), "+f"(d[51]), "+f"(d[52]), "+f"(d[53]), "+f"(d[54]), "+f"(d[55]), "+f"(d[56]), "+f"(d[57]), "+f"(d[58]), "+f"(d[59]), "+f"(d[60]), "+f"(d[61]), "+f"(d[62]), "+f"(d[63])
    : "r"(a0), "r"(a1), "r"(a2), "r"(a3), "l"(db), "r"(sd), "n"(OB));
}
template <int OA, int OB> __device__ __forceinline__ void wgmma_ss_ta(float (&d)[64], uint64_t da, uint64_t db, int sd) {
  asm volatile("{\n.reg .pred p;\n.reg .b64 a, b;\nadd.s64 a, %64, %67;\nadd.s64 b, %65, %68;\nsetp.ne.b32 p, %66, 0;\n"
    "wgmma.mma_async.sync.aligned.m64n128k16.f32.bf16.bf16 {%0, %1, %2, %3, %4, %5, %6, %7, %8, %9, %10, %11, %12, %13, %14, %15, %16, %17, %18, %19, %20, %21, %22, %23, %24, %25, %26, %27, %28, %29, %30, %31, %32, %33, %34, %35, %36, %37, %38, %39, %40, %41, %42, %43, %44, %45, %46, %47, %48, %49, %50, %51, %52, %53, %54, %55, %56, %57, %58, %59, %60, %61, %62, %63}, a, b, p, 1, 1, 1, 0;\n}\n"
    : "+f"(d[0]), "+f"(d[1]), "+f"(d[2]), "+f"(d[3]), "+f"(d[4]), "+f"(d[5]), "+f"(d[6]), "+f"(d[7]), "+f"(d[8]), "+f"(d[9]), "+f"(d[10]), "+f"(d[11]), "+f"(d[12]), "+f"(d[13]), "+f"(d[14]), "+f"(d[15]), "+f"(d[16]), "+f"(d[17]), "+f"(d[18]), "+f"(d[19]), "+f"(d[20]), "+f"(d[21]), "+f"(d[22]), "+f"(d[23]), "+f"(d[24]), "+f"(d[25]), "+f"(d[26]), "+f"(d[27]), "+f"(d[28]), "+f"(d[29]), "+f"(d[30]), "+f"(d[31]), "+f"(d[32]), "+f"(d[33]), "+f"(d[34]), "+f"(d[35]), "+f"(d[36]), "+f"(d[37]), "+f"(d[38]), "+f"(d[39]), "+f"(d[40]), "+f"(d[41]), "+f"(d[42]), "+f"(d[43]), "+f"(d[44]), "+f"(d[45]), "+f"(d[46]), "+f"(d[47]), "+f"(d[48]), "+f"(d[49]), "+f"(d[50]), "+f"(d[51]), "+f"(d[52]), "+f"(d[53]), "+f"(d[54]), "+f"(d[55]), "+f"(d[56]), "+f"(d[57]), "+f"(d[58]), "+f"(d[59]), "+f"(d[60]), "+f"(d[61]), "+f"(d[62]), "+f"(d[63])
    : "l"(da), "l"(db), "r"(sd), "n"(OA), "n"(OB));
}
template <int OB> __device__ __forceinline__ void wgmma_rs(float (&d)[64], uint32_t a0, uint32_t a1, uint32_t a2, uint32_t a3, uint64_t db, int sd) {
  asm volatile("{\n.reg .pred p;\n.reg .b64 b;\nadd.s64 b, %68, %70;\nsetp.ne.b32 p, %69, 0;\n"
    "wgmma.mma_async.sync.aligned.m64n128k16.f32.bf16.bf16 {%0, %1, %2, %3, %4, %5, %6, %7, %8, %9, %10, %11, %12, %13, %14, %15, %16, %17, %18, %19, %20, %21, %22, %23, %24, %25, %26, %27, %28, %29, %30, %31, %32, %33, %34, %35, %36, %37, %38, %39, %40, %41, %42, %43, %44, %45, %46, %47, %48, %49, %50, %51, %52, %53, %54, %55, %56, %57, %58, %59, %60, %61, %62, %63}, {%64, %65, %66, %67}, b, p, 1, 1, 0;\n}\n"
    : "+f"(d[0]), "+f"(d[1]), "+f"(d[2]), "+f"(d[3]), "+f"(d[4]), "+f"(d[5]), "+f"(d[6]), "+f"(d[7]), "+f"(d[8]), "+f"(d[9]), "+f"(d[10]), "+f"(d[11]), "+f"(d[12]), "+f"(d[13]), "+f"(d[14]), "+f"(d[15]), "+f"(d[16]), "+f"(d[17]), "+f"(d[18]), "+f"(d[19]), "+f"(d[20]), "+f"(d[21]), "+f"(d[22]), "+f"(d[23]), "+f"(d[24]), "+f"(d[25]), "+f"(d[26]), "+f"(d[27]), "+f"(d[28]), "+f"(d[29]), "+f"(d[30]), "+f"(d[31]), "+f"(d[32]), "+f"(d[33]), "+f"(d[34]), "+f"(d[35]), "+f"(d[36]), "+f"(d[37]), "+f"(d[38]), "+f"(d[39]), "+f"(d[40]), "+f"(d[41]), "+f"(d[42]), "+f"(d[43]), "+f"(d[44]), "+f"(d[45]), "+f"(d[46]), "+f"(d[47]), "+f"(d[48]), "+f"(d[49]), "+f"(d[50]), "+f"(d[51]), "+f"(d[52]), "+f"(d[53]), "+f"(d[54]), "+f"(d[55]), "+f"(d[56]), "+f"(d[57]), "+f"(d[58]), "+f"(d[59]), "+f"(d[60]), "+f"(d[61]), "+f"(d[62]), "+f"(d[63])
    : "r"(a0), "r"(a1), "r"(a2), "r"(a3), "l"(db), "r"(sd), "n"(OB));
}
template <int OA, int OB> __device__ __forceinline__ void wgmma_ss_ta(float (&d)[4], uint64_t da, uint64_t db, int sd) {
  asm volatile("{\n.reg .pred p;\n.reg .b64 a, b;\nadd.s64 a, %4, %7;\nadd.s64 b, %5, %8;\nsetp.ne.b32 p, %6, 0;\n"
    "wgmma.mma_async.sync.aligned.m64n8k16.f32.bf16.bf16 {%0, %1, %2, %3}, a, b, p, 1, 1, 1, 0;\n}\n"
    : "+f"(d[0]), "+f"(d[1]), "+f"(d[2]), "+f"(d[3])
    : "l"(da), "l"(db), "r"(sd), "n"(OA), "n"(OB));
}

constexpr uint32_t U = 16384;
constexpr uint32_t SM_QO = 2 * U, SM_W = 8 * U, SM_V = 8 * U, SM_K1 = 12 * U, SM_BAR = 14 * U;
constexpr uint32_t B_WF = SM_BAR, B_KF = SM_BAR + 48, B_CF = SM_BAR + 80, B_GATE = SM_BAR + 128, B_OF = SM_BAR + 136, B_EP = SM_BAR + 144, B_EXT = SM_BAR + 152, B_Q3 = SM_BAR + 168,
                   B_WE = SM_BAR + 192, B_KE = SM_BAR + 240, B_CE = SM_BAR + 288, B_OS = SM_BAR + 344;
constexpr uint32_t SM_ONE = SM_BAR + 388;
constexpr uint32_t SM_BADF = SM_BAR + 392, SM_EP = SM_BAR + 396;
constexpr uint32_t SM_STAT = SM_BAR + 400, SM_EXT = SM_STAT + 512;
constexpr int SMEM_BYTES = SM_BAR + 3072;
__device__ __forceinline__ uint32_t c_slot(int s) { return (0xBADC10u >> (4 * s)) & 15; }

struct Params {
  const __nv_bfloat16 *x, *k, *v, *wq, *wo, *wr;
  __nv_bfloat16* out;
  Scratch* g;
};

__device__ __forceinline__ void release2(uint32_t rbar, int lane) { if (lane < 2) mbar_arrive_cluster(rbar); }
__device__ __forceinline__ void pin_after(uint32_t a, float e0, float e1) {
  asm volatile("{\n.reg .pred p;\nsetp.lt.f32 p, %1, %2;\n@p st.shared.u32 [%0], %0;\n}\n" :: "r"(a), "f"(e0), "f"(-e1) : "memory"); }
__device__ __forceinline__ void lds128_after(uint32_t& x, uint32_t& y, uint32_t& z, uint32_t& w, uint32_t a, float e0, float e1) {
  asm volatile("{\n.reg .pred p;\nsetp.geu.f32 p, %5, %6;\n@p ld.shared.v4.u32 {%0,%1,%2,%3}, [%4];\n}\n" : "+r"(x), "+r"(y), "+r"(z), "+r"(w) : "r"(a), "f"(e0), "f"(-e1) : "memory"); }
__device__ __forceinline__ uint32_t new_launch(Scratch* g) { return (uint32_t)(atomicAdd(&g->ticket, 1ull) / 132) + 1; }

__device__ __forceinline__ void attn_slow(uint32_t (&q)[32], const __nv_bfloat16* __restrict__ X, const __nv_bfloat16* __restrict__ WQ, uint32_t st0, uint32_t st1,
                                          const __nv_bfloat16* __restrict__ K, const __nv_bfloat16* __restrict__ V, int lane) {
  float o[64];
  #pragma unroll
  for (int i = 0; i < 64; i++) o[i] = 0.f;
  const int g = lane >> 2, qd = lane & 3;
  #pragma unroll 1
  for (int k0 = 0; k0 < DM; k0 += 16) {
    uint32_t a[4];
    #pragma unroll
    for (int e = 0; e < 4; e++) {
      const uint32_t xv = *(const uint32_t*)(X + (size_t)(g + (e & 1) * 8) * DM + k0 + (e >> 1) * 8 + 2 * qd);
      const float mb = bf_lo((e & 1) ? st1 : st0);
      a[e] = pack_bf16(bf_lo(xv) - mb, bf_hi(xv) - mb);
    }
    const unsigned short* wr = (const unsigned short*)(WQ + (size_t)(k0 + 2 * qd) * (NH * DH) + g);
    #pragma unroll
    for (int nb = 0; nb < 16; nb++) {
      uint32_t b0 = (uint32_t)wr[nb * 8] | ((uint32_t)wr[nb * 8 + NH * DH] << 16);
      uint32_t b1 = (uint32_t)wr[nb * 8 + 8 * NH * DH] | ((uint32_t)wr[nb * 8 + 9 * NH * DH] << 16);
      asm volatile("mma.sync.aligned.m16n8k16.row.col.f32.bf16.bf16.f32 {%0,%1,%2,%3}, {%4,%5,%6,%7}, {%8,%9}, {%0,%1,%2,%3};"
        : "+f"(o[nb*4]), "+f"(o[nb*4+1]), "+f"(o[nb*4+2]), "+f"(o[nb*4+3]) : "r"(a[0]), "r"(a[1]), "r"(a[2]), "r"(a[3]), "r"(b0), "r"(b1));
    }
  }
  {
    const float r0 = rcp_approx(bf_hi(st0)) * SCALE_LOG2E, r1 = rcp_approx(bf_hi(st1)) * SCALE_LOG2E;
    #pragma unroll
    for (int i = 0; i < 16; i++) { q[2*i] = pack_bf16(o[4*i] * r0, o[4*i+1] * r0); q[2*i+1] = pack_bf16(o[4*i+2] * r1, o[4*i+3] * r1); }
    #pragma unroll
    for (int i = 0; i < 64; i++) o[i] = 0.f;
  }
  float m0 = -INFINITY, m1 = -INFINITY, l0 = 0.f, l1 = 0.f;
  #pragma unroll 1
  for (int n0 = 0; n0 < S_LEN; n0 += 16) {
    float s[8];
    #pragma unroll
    for (int i = 0; i < 8; i++) s[i] = 0.f;
    #pragma unroll
    for (int nb = 0; nb < 2; nb++) {
      const uint32_t* kr = (const uint32_t*)(K + (size_t)(n0 + nb * 8 + g) * DH) + qd;
      #pragma unroll
      for (int kk = 0; kk < 8; kk++) {
        uint32_t b0 = kr[kk * 8], b1 = kr[kk * 8 + 4];
        asm volatile("mma.sync.aligned.m16n8k16.row.col.f32.bf16.bf16.f32 {%0,%1,%2,%3}, {%4,%5,%6,%7}, {%8,%9}, {%0,%1,%2,%3};"
          : "+f"(s[nb*4]), "+f"(s[nb*4+1]), "+f"(s[nb*4+2]), "+f"(s[nb*4+3]) : "r"(q[kk*4]), "r"(q[kk*4+1]), "r"(q[kk*4+2]), "r"(q[kk*4+3]), "r"(b0), "r"(b1));
      }
    }
    float x0 = fmaxf(fmaxf(s[0], s[1]), fmaxf(s[4], s[5])), x1 = fmaxf(fmaxf(s[2], s[3]), fmaxf(s[6], s[7]));
    x0 = fmaxf(x0, __shfl_xor_sync(0xffffffff, x0, 1)); x1 = fmaxf(x1, __shfl_xor_sync(0xffffffff, x1, 1));
    x0 = fmaxf(x0, __shfl_xor_sync(0xffffffff, x0, 2)); x1 = fmaxf(x1, __shfl_xor_sync(0xffffffff, x1, 2));
    const float n0m = fmaxf(m0, x0), n1m = fmaxf(m1, x1);
    const float sh0 = (n0m == -INFINITY) ? 0.f : n0m, sh1 = (n1m == -INFINITY) ? 0.f : n1m;
    const float c0 = ex2(m0 - sh0), c1 = ex2(m1 - sh1);
    m0 = n0m; m1 = n1m;
    s[0] = ex2(s[0] - sh0); s[1] = ex2(s[1] - sh0); s[4] = ex2(s[4] - sh0); s[5] = ex2(s[5] - sh0);
    s[2] = ex2(s[2] - sh1); s[3] = ex2(s[3] - sh1); s[6] = ex2(s[6] - sh1); s[7] = ex2(s[7] - sh1);
    l0 = l0 * c0 + (s[0] + s[1]) + (s[4] + s[5]); l1 = l1 * c1 + (s[2] + s[3]) + (s[6] + s[7]);
    const uint32_t a0 = pack_bf16(s[0], s[1]), a1 = pack_bf16(s[2], s[3]), a2 = pack_bf16(s[4], s[5]), a3 = pack_bf16(s[6], s[7]);
    const unsigned short* vr = (const unsigned short*)(V + (size_t)(n0 + 2 * qd) * DH + g);
    #pragma unroll
    for (int nb = 0; nb < 16; nb++) {
      uint32_t b0 = (uint32_t)vr[nb * 8] | ((uint32_t)vr[nb * 8 + DH] << 16);
      uint32_t b1 = (uint32_t)vr[nb * 8 + 8 * DH] | ((uint32_t)vr[nb * 8 + 9 * DH] << 16);
      o[nb*4] *= c0; o[nb*4+1] *= c0; o[nb*4+2] *= c1; o[nb*4+3] *= c1;
      asm volatile("mma.sync.aligned.m16n8k16.row.col.f32.bf16.bf16.f32 {%0,%1,%2,%3}, {%4,%5,%6,%7}, {%8,%9}, {%0,%1,%2,%3};"
        : "+f"(o[nb*4]), "+f"(o[nb*4+1]), "+f"(o[nb*4+2]), "+f"(o[nb*4+3]) : "r"(a0), "r"(a1), "r"(a2), "r"(a3), "r"(b0), "r"(b1));
    }
  }
  l0 += __shfl_xor_sync(0xffffffff, l0, 1); l1 += __shfl_xor_sync(0xffffffff, l1, 1);
  l0 += __shfl_xor_sync(0xffffffff, l0, 2); l1 += __shfl_xor_sync(0xffffffff, l1, 2);
  const float i0 = rcp_approx(l0), i1 = rcp_approx(l1);
  #pragma unroll
  for (int i = 0; i < 16; i++) { q[2*i] = pack_bf16(o[4*i] * i0, o[4*i+1] * i0); q[2*i+1] = pack_bf16(o[4*i+2] * i1, o[4*i+3] * i1); }
}

__device__ __forceinline__ bool finish_head(float (&o)[64], float l0, float l1, uint32_t (&of)[32], int one) {
  l0 += __shfl_xor_sync(0xffffffff, l0, one); l1 += __shfl_xor_sync(0xffffffff, l1, one);
  l0 += __shfl_xor_sync(0xffffffff, l0, 2); l1 += __shfl_xor_sync(0xffffffff, l1, 2);
  const float i0 = rcp_fast(l0), i1 = rcp_fast(l1);
  #pragma unroll
  for (int i = 0; i < 16; i++) { of[2*i] = pack_bf16(o[4*i] * i0, o[4*i+1] * i0); of[2*i+1] = pack_bf16(o[4*i+2] * i1, o[4*i+3] * i1); }
  uint32_t z0 = 0, z1 = 0;
  #pragma unroll
  for (int i = 0; i < 8; i++) {
    asm("fma.rn.bf16x2 %0, %1, %2, %0;" : "+r"(z0) : "r"(of[4*i]), "r"(of[4*i+1]));
    asm("fma.rn.bf16x2 %0, %1, %2, %0;" : "+r"(z1) : "r"(of[4*i+2]), "r"(of[4*i+3]));
  }
  asm("fma.rn.bf16x2 %0, %1, %2, %3;" : "=r"(z0) : "r"(z0), "r"(0u), "r"(0u));
  asm("fma.rn.bf16x2 %0, %1, %2, %0;" : "+r"(z0) : "r"(z1), "r"(0u));
  const bool ok = (l0 >= 0.00390625f) && (l0 <= 1.8446744e19f) && (l1 >= 0.00390625f) && (l1 <= 1.8446744e19f) && ((z0 & 0x7fff7fffu) == 0);
  return __all_sync(0xffffffff, ok);
}
__device__ __forceinline__ uint32_t qo_slot(int h) { return SM_QO + ((0x3102 >> (4 * h)) & 3) * 2 * U; }
__device__ __forceinline__ void store_o(uint32_t wr, int lane, uint32_t slot, const uint32_t (&of)[32]) {
  const uint32_t a = wr + (lane & 15) * 128 + (((lane >> 4) ^ (lane & 7)) << 4) + slot;
  #pragma unroll
  for (int i = 0; i < 8; i++) stsm4((a ^ ((i & 3) << 5)) + (i >> 2) * U, of[4*i], of[4*i+1], of[4*i+2], of[4*i+3]);
}

__device__ __noinline__ void redo_heads(const Params& P, uint32_t sb, uint32_t bad, int row0, int head0) {
  const int lane = threadIdx.x & 31;
  const uint32_t st0 = lds32(sb + SM_STAT + ((row0 & 127) + (lane >> 2)) * 4), st1 = lds32(sb + SM_STAT + ((row0 & 127) + 8 + (lane >> 2)) * 4);
  #pragma unroll 1
  for (int h = 0; h < 4; h++) {
    if (!((bad >> h) & 1)) continue;
    uint32_t q[32];
    attn_slow(q, P.x + (size_t)row0 * DM, P.wq + (head0 + h) * DH, st0, st1, P.k + (size_t)(head0 + h) * S_LEN * DH, P.v + (size_t)(head0 + h) * S_LEN * DH, lane);
    store_o(sb + (row0 & 127) * 128, lane, qo_slot(h), q);
  }
}

template <int K> struct IC { static constexpr int v = K; };
template <int K, int N, class F> __device__ __forceinline__ void static_for(F&& f) { if constexpr (K < N) { f(IC<K>{}); static_for<K + 1, N>(f); } }
template <uint32_t OFF, int SITE> __device__ __forceinline__ void mma_qk(float (&s)[64], const uint32_t (&q)[32], uint64_t d0) {
  wg_fence();
  static_for<0, 8>([&](auto kc) { constexpr int k = decltype(kc)::v; wgmma_rs<doff(OFF, 16) - SITE + (k / 4) * 1024 + (k % 4) * 2>(s, q[k*4], q[k*4+1], q[k*4+2], q[k*4+3], d0, k > 0); });
  wg_commit();
}
template <uint32_t OFF, int SITE> __device__ __forceinline__ void mma_pv(float (&o)[64], const uint32_t (&p)[32], uint64_t d0, bool keep) {
  wg_fence();
  static_for<0, 8>([&](auto kc) { constexpr int k = decltype(kc)::v; wgmma_rs_tb<doff(OFF, U) - SITE + k * 128>(o, p[k*4], p[k*4+1], p[k*4+2], p[k*4+3], d0, (k > 0) || keep); });
  wg_commit();
}
template <int I0, int I1>
__device__ __forceinline__ void exp_rows(float (&s)[64], float (&l)[2]) {
  #pragma unroll
  for (int i = I0; i < I1; i += 2) {
    s[i] = ex2(s[i]); s[i+1] = ex2(s[i+1]);
    if (SMV) l[(i >> 1) & 1] += s[i] + s[i+1]; else { l[(i >> 1) & 1] += s[i]; l[(i >> 1) & 1] += s[i+1]; }
  }
}

template <int KS, bool EDGE>
__device__ __forceinline__ void attn_step(uint32_t sb, uint32_t rb, uint32_t wr, uint32_t qa, int wg, int lane, int j, int ph, float (&s)[64], float (&o)[64], uint32_t (&p)[32], uint32_t (&q)[32],
                                          float (&l)[2], uint32_t& bad, bool& ready, Scratch* g, unsigned (&tz)[3]) {
  constexpr bool FIRST = EDGE && !KS, LAST = EDGE && KS;
  TRACEF(2, wg, 32 + j);
  if (!ETEST || !ready) {
    mbar_wait(sb + B_KF + 24 - KS * 8, KS ? ph : ph ^ 1);
    mbar_wait(sb + B_KF + KS * 8, ph);
  }
  bar_sync(1 + wg, 256);
  mma_qk<KS * SM_K1, EDGE>(s, q, desc(sb, EDGE));
  mma_pv<SM_V + (1 - KS) * 2 * U, EDGE>(o, p, desc(sb, EDGE), !KS || LAST || ((j & 15) != 1));
  bar_arrive(1 + (wg ^ 1), 256);
  const int one = FIRST ? lds32(sb + SM_ONE) : 1;
  wg_wait<1>();
  fence_regs(s);
  release2(rb + B_KE + KS * 8, lane);
  const float lp0 = l[0], lp1 = l[1];
  if (FIRST) l[0] = l[1] = 0.f;
  constexpr int DP = FIRST ? DPOSF : (LAST && DPOS < 7 * QSP ? 7 * QSP : DPOS);
  if (LAST) {
    fence_regs(q);
    const uint32_t a = qa + qo_slot(j >> 4);
    static_for<0, 8>([&](auto ic) { constexpr int i = decltype(ic)::v;
      lds128_after(q[4*i], q[4*i+1], q[4*i+2], q[4*i+3], a + (i >> 2) * U + (i & 3) * 512, l[0], l[1]);
      exp_rows<i * QSP, i < 7 ? (i + 1) * QSP : DP>(s, l);
    });
  } else exp_rows<0, DP>(s, l);
  if (DPOS >= 0) pin_after(sb + SM_BADF, l[0], l[1]);
  exp_rows<DP, 64>(s, l);
  wg_wait<0>();
  fence_regs(o); fence_regs(p);
  release2(rb + B_KE + 24 - KS * 8, lane);
  if (ETEST) ready = mbar_test2(sb + B_KF + 16 + KS * 8, ph, sb + B_KF + 8 - KS * 8, KS ? ph ^ 1 : ph);
  if (FIRST) {
    const int h = (j >> 4) - 1;
    bad |= (finish_head(o, lp0, lp1, p, one) ? 0u : 1u) << h;
    store_o(wr, lane, qo_slot(h), p);
    if (lane == 0) {
      if (bad) sts32(sb + SM_BADF, 1u);
      mbar_arrive(sb + B_OS + h * 8);
    }
  }
  #pragma unroll
  for (int i = 0; i < 32; i++) p[i] = pack_bf16(s[2*i], s[2*i+1]);
}

template <int SITE> __device__ __forceinline__ void mma_c(float (&acc)[64], uint32_t sb, int slot, int h, int arrive_bar) {
  const uint64_t a = desc(sb, c_slot(slot) * 1024 + SITE), b = desc(sb, h * 2048 + SITE);
  wg_fence();
  static_for<0, 8>([&](auto kc) { constexpr int k = decltype(kc)::v;
    if (k == C_EARLY && arrive_bar) bar_arrive(arrive_bar, 256);
    wgmma_ss_ta<doff(0, 16) - SITE + k * 128, doff(SM_QO, 16) - SITE + (k >> 2) * 1024 + (k & 3) * 2>(acc, a, b, k > 0 || h > 0);
  });
  wg_commit();
}

__device__ __forceinline__ void side_cta(const Params& P, const CUtensorMap* tmX, const CUtensorMap* tmW, const CUtensorMap* tmG, const CUtensorMap* tmU,
                                         const CUtensorMap* tmD, uint32_t sb, int m) {
  const int tid = threadIdx.x, warp = __shfl_sync(0xffffffff, tid >> 5, 0), lane = tid & 31;
  const uint32_t XS = sb + 12 * U, HS = XS + 10240, BF = sb + SM_BAR, BE = BF + 96, XF = BE + 96, XE = XF + 32, BW = XE + 32, SEL = BW + 16, KEY = SEL + 64;
  Scratch* const g = P.g;
  const int nj = m < 3 ? 14 : 12, nd = m < 3 ? 4 : 3, f0 = m * 448;
  if (elect_one()) { mbar_init(BF + warp * 8, 1); mbar_init(BE + warp * 8, 4); if (warp < 9) mbar_init(XF + warp * 8, (warp & 4) ? 8 : 1); }
  if (tid == 32) sts32(SEL + 32, new_launch(g));
  __syncthreads();
  const uint32_t launch = lds32(SEL + 32);
  if (warp == 0) {
    if (elect_one()) {
      mbar_expect_tx(BW, 10 * U);
      #pragma unroll 1
      for (int i = 0; i < 10; i++) tma_load_2d(sb + i * U, tmW, BW, m * 1024 + (i < 5 ? 448 : 960), (i < 5 ? i : i - 5) * 128);
    }
    #pragma unroll 1
    for (int n = 0, qt = 0, c = 0; n < 160; n++) {
      const uint32_t bar = XF + (n & 3) * 8;
      mbar_wait(bar + 32, ((n >> 2) & 1) ^ 1);
      if (elect_one()) {
        mbar_expect_tx(bar, U);
        tma_load_2d(sb + (10 + (n & 3)) * U, tmX, bar, c * 64, qt * 128);
        if (c == 0 && qt < 15) l2_prefetch(P.x + (size_t)(qt * 128 + 128 + m * 32) * DM, 32 * DM * 2);
      }
      if (++c == 10) { c = 0; qt++; }
    }
  } else if (warp == 1) {
    #pragma unroll 1
    for (int qt = 0; qt < 16; qt++) {
      bar_sync(2 + (qt & 1), 288);
      if (lane == 0) asm volatile("fence.acq_rel.gpu;\nst.relaxed.gpu.global.u32 [%0], %1;" :: "l"(&g->q3_done[m].v), "r"(launch * 16 + qt + 1) : "memory");
    }
  } else if (warp >= 4) {
    float acc[64], cs[32];
    mbar_wait(BW, 0);
    #pragma unroll 1
    for (int c = 0; c < 10; c++) {
      wg_fence();
      static_for<0, 4>([&](auto kc) { constexpr int k = decltype(kc)::v;
        wgmma_rs_tb<doff(0, 5 * U) + k * 128>(acc, 0x3f803f80u, 0x3f803f80u, 0x3f803f80u, 0x3f803f80u, desc(sb, c * 512), k || c); });
      wg_commit();
      wg_wait<0>();
    }
    fence_regs(acc);
    #pragma unroll
    for (int i = 0; i < 32; i++) cs[i] = -acc[(i >> 1) * 4 + (i & 1)];
    fence_regs(cs);
    #pragma unroll 1
    for (int qt = 0, n = 0; qt < 16; qt++) {
      const uint32_t* const sp = g->stat + qt * 128 + (warp - 4) * 16 + (lane >> 2);
      uint32_t st0, st1;
      #pragma unroll 1
      for (int c = 0; c < 10; c++, n++) {
        const uint64_t a = desc(sb, (n & 3) * 1024 + (warp >> 3) * 512), b = desc(sb, c * 512);
        mbar_wait(XF + (n & 3) * 8, (n >> 2) & 1);
        wg_fence();
        static_for<0, 4>([&](auto kc) { constexpr int k = decltype(kc)::v; wgmma_ss_tb<doff(10 * U, 16) + k * 2, doff(0, 5 * U) + k * 128>(acc, a, b, k || c); });
        wg_commit();
        if (c == 9) { st0 = ldg32(sp); st1 = ldg32(sp + 8); }
        wg_wait<1>();
        if (c && lane == 0) mbar_arrive(XE + ((n - 1) & 3) * 8);
      }
      #pragma unroll 1
      for (int it = 0; __any_sync(0xffffffff, tag_miss(st0, st1, launch << 31) >> 31) && it < MAXPOLL; it++) { st0 = ldg32(sp); st1 = ldg32(sp + 8); }
      st0 &= 0x7fffffffu; st1 &= 0x7fffffffu;
      const float rs[2] = {rcp_approx(bf_hi(st0)) * SCALE_LOG2E, rcp_approx(bf_hi(st1)) * SCALE_LOG2E}, nm[2] = {bf_lo(st0), bf_lo(st1)};
      wg_wait<0>();
      fence_regs(acc);
      if (lane == 0) mbar_arrive(XE + ((n - 1) & 3) * 8);
      uint4* const dst = g->q3 + (qt * 8 + m * 2) * 1024 + (warp - 4) * 128 + lane;
      #pragma unroll
      for (int e = 0; e < 8; e++) {
        uint32_t w[4];
        #pragma unroll
        for (int i = 0; i < 4; i++)
          w[i] = pack_bf16(fmaf(nm[i & 1], cs[4*e + (i & 2)], acc[8*e + 2*i]) * rs[i & 1], fmaf(nm[i & 1], cs[4*e + (i & 2) + 1], acc[8*e + 2*i + 1]) * rs[i & 1]);
        dst[(e >> 2) * 1024 + (e & 3) * 32] = make_uint4(w[0], w[1], w[2], w[3]);
      }
      bar_arrive(2 + (qt & 1), 288);
    }
  }
  if (tid == 64) flag_wait(&g->cnt_gate.v, launch * 256);
  __syncthreads();
  TRACE(0, 1);
  if (tid >= 256 && tid < 320) sts128(HS + 3072 + tid * 16, 0, 0, 0, 0);
  if (warp < 4) {
    uint4 k4[4];
    #pragma unroll
    for (int i = 0; i < 4; i++) k4[i] = ld_relaxed4(g->key + warp * 512 + i * 128 + lane * 4);
    uint32_t bound = 0;
    #pragma unroll 1
    for (int c = 0; c < TOPC; c++) {
      uint32_t b = 0;
      #pragma unroll
      for (int i = 0; i < 4; i++) b = max(max(max(b, k4[i].x - bound), k4[i].y - bound), max(k4[i].z - bound, k4[i].w - bound));
      bound += __reduce_max_sync(0xffffffff, b);
      if (lane == 0) sts32(KEY + (warp * TOPC + c) * 4, bound);
    }
    bar_sync(1, 128);
    const uint32_t v = lds32(KEY + lane * 4);
    int n = 0;
    #pragma unroll 1
    for (int j = 0; j < 32; j++) n += __shfl_sync(0xffffffff, v, j) > v;
    if (n < TOPC) sts32(SEL + n * 4, v);
  }
  __syncthreads();
  #pragma unroll 1
  for (int i = tid; i < TOPC * 80; i += 384) {
    const int row = 0xffff - (lds32(SEL + (i & 7) * 4) & 0xffff);
    const uint32_t st = ldg32(g->stat + row), m2 = __byte_perm(st, 0, 0x1010);
    const float rsd = rcp_approx(bf_hi(st & 0x7fffffffu));
    const uint4 v = ldg_nc((const uint4*)(P.x + (size_t)row * DM) + (i >> 3));
    sts128(XS + i * 16, norm2(v.x, m2, rsd), norm2(v.y, m2, rsd), norm2(v.z, m2, rsd), norm2(v.w, m2, rsd));
  }
  proxy_fence();
  __syncthreads();
  TRACE(0, 2);
  uint32_t sl = 0, ph = 0;
  if (warp == 0) {
    #pragma unroll 1
    for (int job = 0; job < nj + 10; job++) {
      const bool up = job < nj;
      #pragma unroll 1
      for (int i = 0; i < (up ? 5 : nd); i++) {
        mbar_wait(BE + sl * 8, ph ^ 1);
        if (elect_one()) {
          mbar_expect_tx(BF + sl * 8, U);
          tma_load_2d(sb + sl * U, up ? ((job & 1) ? tmU : tmG) : tmD, BF + sl * 8, up ? f0 + (job >> 1) * 64 : (job - nj) * 64, (up ? 0 : f0) + i * 128);
        }
        if (++sl == 12) { sl = 0; ph ^= 1; }
      }
    }
  } else if ((warp >> 2) == 1) {
    float gs[4];
    #pragma unroll 1
    for (int job = 0; job < nj + 10; job++) {
      const bool up = job < nj;
      if (job == nj) { proxy_fence(); bar_sync(1, 128); }
      float ac[4][4], acc[4];
      uint32_t prev = 0;
      #pragma unroll 1
      for (int i = 0; i < (up ? 5 : nd); i++) {
        const uint64_t a = desc(sb, sl * 1024 + 0x10000), b = (uint64_t)(desc_lo(up ? XS : HS, 128) + i * 128) | (8ull << 32);
        mbar_wait(BF + sl * 8, ph);
        wg_fence();
        static_for<0, 8>([&](auto kc) { constexpr int k = decltype(kc)::v; wgmma_ss_ta<k * 128, k * 16>(ac[k & 3], a, b, k > 3 || i > 0); });
        wg_commit();
        wg_wait<1>();
        if (i && lane == 0) mbar_arrive(prev);
        prev = BE + sl * 8;
        if (++sl == 12) { sl = 0; ph ^= 1; }
      }
      wg_wait<0>();
      if (lane == 0) mbar_arrive(prev);
      #pragma unroll
      for (int e = 0; e < 4; e++) fence_regs(ac[e]);
      #pragma unroll
      for (int e = 0; e < 4; e++) acc[e] = (ac[0][e] + ac[1][e]) + (ac[2][e] + ac[3][e]);
      const int f = (warp & 3) * 16 + (lane >> 2), tk = (lane & 3) * 2;
      if (!up) {
        float* y = g->ypart + (m * DM + (job - nj) * 64 + f) * TOPC + tk;
        *(float2*)y = make_float2(acc[0], acc[1]); *(float2*)(y + 8 * TOPC) = make_float2(acc[2], acc[3]);
      } else {
        #pragma unroll
        for (int e = 0; e < 4; e++) {
          const float z = rbf(acc[e]);
          if (job & 1) asm volatile("st.shared.u16 [%0], %1;" :: "r"(HS + (job >> 1) * 1024 + ((f >> 3) + (e >> 1)) * 128 + (tk + (e & 1)) * 16 + (f & 7) * 2), "h"((uint16_t)pack_bf16(gs[e] * z, 0.f)) : "memory");
          gs[e] = rbf(z * sigmoid_f(z));
        }
      }
    }
  }
  __syncthreads();
  TRACE(0, 3);
  if (tid == 0) { flag_add_release(&g->cnt_mod.v); flag_wait(&g->cnt_mod.v, launch * 4, 50); }
  __syncthreads();
  #pragma unroll 1
  for (int i = tid; i < 2 * DM; i += 384) {
    const int t = 2 * m + (i & 1), col = i >> 1;
    const uint32_t key = lds32(SEL + t * 4);
    const float* yp = g->ypart + col * TOPC + t;
    const float y = rbf((__ldcg(yp) + __ldcg(yp + TOPC * DM)) + (__ldcg(yp + 2 * TOPC * DM) + __ldcg(yp + 3 * TOPC * DM)));
    const float rs = rbf(sigmoid_f(bf_hi((key >> 31) ? key & 0x7fffffffu : ~key)));
    const uint32_t xn = lds32(XS + (col >> 3) * 128 + t * 16 + (col & 6) * 2);
    const float z = rbf(((col & 1) ? bf_hi(xn) : bf_lo(xn)) + rbf(y * rs));
    g->gate[(size_t)(0xffff - (key & 0xffff)) * DM + col] = __float2bfloat16_rn(z * sigmoid_f(z));
  }
  __syncthreads();
  if (tid == 0) flag_add_release(&g->mod_done.v);
  TRACE(0, 4);
}

__global__ void __cluster_dims__(2, 1, 1) __launch_bounds__(384, 1) fused_kernel(const __grid_constant__ CUtensorMap tmX, const __grid_constant__ CUtensorMap tmW4,
    const __grid_constant__ CUtensorMap tmW3, const __grid_constant__ CUtensorMap tmW1,
    const __grid_constant__ CUtensorMap tmK, const __grid_constant__ CUtensorMap tmV, const __grid_constant__ CUtensorMap tmWO,
    const __grid_constant__ CUtensorMap tmG, const __grid_constant__ CUtensorMap tmU, const __grid_constant__ CUtensorMap tmD,
    const __grid_constant__ CUtensorMap tmGate, const __grid_constant__ Params P) {
  extern __shared__ __align__(1024) uint8_t smem_raw[];
  const uint32_t sb = smem_u32(smem_raw);
  const int tid = threadIdx.x, lane = tid & 31;
  const int rank = blockIdx.x & 1, cl = blockIdx.x >> 1;
  if (cl >= 64) {
    side_cta(P, &tmX, &tmW1, &tmG, &tmU, &tmD, sb, blockIdx.x & 3);
    return;
  }
  const int rr = ((cl - 36) * 37) >> 8, qp = sel_lt(cl, 4, 0, sel_lt(cl, 36, (cl - 4) & 7, cl - 35 - rr * 7));
  const int hg = sel_lt(cl, 4, cl, sel_lt(cl, 36, ((cl - 4) >> 3) + sel_lt(qp, 1, 4, 0), 4 + rr)), qt = qp * 2 + rank;
  const int warp = __shfl_sync(0xffffffff, tid >> 5, 0), wgi = warp >> 2;
  Scratch* const g = P.g;
  if (elect_one()) {
    #pragma unroll
    for (int i = 0; i < 4; i++) mbar_init(sb + SM_BAR + warp * 32 + i * 8, 1 << ((0x333444000000ull >> (4 * warp)) & 7));
    if (warp == 0) { mbar_expect_tx(sb + B_WF, 2 * U); tma_load_2d(sb + 2 * U, &tmX, sb + B_WF, 0, qt * 128); }
    if (warp == 1) asm volatile("prefetch.tensormap [%0];" :: "l"(&tmW4) : "memory");
    asm volatile("fence.mbarrier_init.release.cluster;" ::: "memory");
  }
  __syncwarp();
  cluster_arrive();
  cluster_wait();
  if (warp == 0 && elect_one()) {
    tma_load_3d_mc(sb + SM_W + rank * 8192, &tmW4, sb + B_WF, 0, rank * 16, hg * 8);
    mbar_expect_tx(sb + B_WF + 8, U);
    tma_load_3d_mc(sb + SM_W + U + rank * 8192, &tmW4, sb + B_WF + 8, 0, 32 + rank * 16, hg * 8);
  }
  if (wgi == 0) {
    asm volatile("setmaxnreg.dec.sync.aligned.u32 56;");
        if (warp == 3) {
      if (lane < 12) sts128(sb + SM_EXT + 1024 + (lane >= 6 ? 1024 - 96 : 0) + lane * 16, 0, 0, 0, 0);
      #pragma unroll 1
      for (int ps = 0; ps < 2; ps++) {
        const uint4* src = at<uint4>(P.wq, (((qt >> 2) * 4 + (lane >> 3)) * (NH * DH) + hg * 512 + ps * 256 + (qt & 3) * 64 + (lane & 7) * 8) * 2);
        const uint32_t mine = ((hg * 2 + ps) * 256 + qt * 16 + (lane & 7) * 2 + (lane >> 4)) * 16;
        float cs[8];
        #pragma unroll
        for (int e = 0; e < 8; e++) cs[e] = 0.f;
        #pragma unroll 1
        for (int b = 0; b < 5; b++, src += 128 * 512) {
          uint4 w[8];
          #pragma unroll
          for (int i = 0; i < 8; i++) w[i] = ldg_nc(src + i * 16 * 512);
          #pragma unroll
          for (int i = 0; i < 8; i++) add8(cs, w[i]);
          if (b == 0) {
            mbar_wait(sb + B_EP, 0);
            if (!(lane & 8)) st_tagged(at<uint4>(g->cs, mine), ~lds32(sb + SM_EP) & 1, 0, 0, 0);
          }
        }
        #pragma unroll
        for (int e = 0; e < 4; e++) {
          cs[e] = ((lane & 16) ? cs[e + 4] : cs[e]) + __shfl_xor_sync(0xffffffff, (lane & 16) ? cs[e] : cs[e + 4], 16);
          cs[e] += __shfl_xor_sync(0xffffffff, cs[e], 8);
        }
        mbar_wait(sb + B_EP, 0);
        const uint32_t tm = 0u - (lds32(sb + SM_EP) & 1);
        const uint4* const gc = at<uint4>(g->cs, ((hg * 2 + ps) * 256 + lane) * 16);
        if (!(lane & 8)) st_tagged(at<uint4>(g->cs, mine), (__float_as_uint(cs[0]) & ~1u) | (tm & 1), __float_as_uint(cs[1]), __float_as_uint(cs[2]), __float_as_uint(cs[3]));

        uint4 v[9];
        int it = 0;
        uint32_t miss;
        do {
          #pragma unroll
          for (int i = 0; i < 8; i++) v[i] = ld_tagged(gc + i * 32);
          v[8] = ld_relaxed4(at<uint4>(g->stat, qt * 512 + lane * 16));
          miss = (tag_miss(v[8].x, v[8].y, tm) | tag_miss(v[8].z, v[8].w, tm)) >> 31;
          #pragma unroll
          for (int i = 0; i < 8; i += 2) miss |= tag_miss(v[i].x, v[i+1].x, tm);
        } while (__any_sync(0xffffffff, miss & 1) && ++it < MAXPOLL);
        #pragma unroll
        for (int i = 0; i < 2; i++) {
          auto sum = [](uint32_t a, uint32_t b, uint32_t c, uint32_t d) { return (__uint_as_float(a) + __uint_as_float(b)) + (__uint_as_float(c) + __uint_as_float(d)); };
          const float c0 = sum(v[i].x, v[i+2].x, v[i+4].x, v[i+6].x), c1 = sum(v[i].y, v[i+2].y, v[i+4].y, v[i+6].y);
          const float c2 = sum(v[i].z, v[i+2].z, v[i+4].z, v[i+6].z), c3 = sum(v[i].w, v[i+2].w, v[i+4].w, v[i+6].w);
          const uint32_t h0 = pack_bf16(c0, c1), h1 = pack_bf16(c2, c3), a = sb + SM_EXT + ps * 1024 + i * 512 + (lane >> 1) * 32 + (lane & 1) * 8;
          asm volatile("st.shared.v2.u32 [%0], {%1,%2};" :: "r"(a), "r"(h0), "r"(h1) : "memory");
          asm volatile("st.shared.v2.u32 [%0], {%1,%2};" :: "r"(a + 16), "r"(pack_bf16(c0 - bf_lo(h0), c1 - bf_hi(h0))), "r"(pack_bf16(c2 - bf_lo(h1), c3 - bf_hi(h1))) : "memory");
        }
        sts128(sb + SM_STAT + lane * 16, v[8].x & 0x7fffffffu, v[8].y & 0x7fffffffu, v[8].z & 0x7fffffffu, v[8].w & 0x7fffffffu);
        proxy_fence();
        __syncwarp();
        if (lane == 0) mbar_arrive(sb + B_EXT + ps * 8);
        TRACE1(2, 6 + ps);
        if (elect_one()) l2_prefetch(at<char>(ps ? P.v : P.k, (hg * 4 * S_LEN + qt * (16 + 8 * KVPF)) * DH * 2), 4096 + 2048 * KVPF);
      }
    } else if (warp > 0) {
      mbar_wait(sb + B_WF, 0);
      auto warm = [&](int ps, int i0, int i1) {
        const uint32_t o = (((qt >> 2) * 4 + (lane & 3) + (lane >> 2) * 16) * (NH * DH) + hg * 512 + ps * 256 + (qt & 3) * 64) * 2;
        #pragma unroll 1
        for (int i = i0; i < i1; i++) {
          asm volatile("prefetch.global.L2 [%0];" :: "l"(at<char>(P.wq, o + i * 256 * (NH * DH))) : "memory");
          if (ps) __nanosleep(W1SL);
        }
      };
      if (XPF && elect_one()) l2_prefetch(P.x + (size_t)(qt * 128 + hg * 16 + warp * 8 - 6) * DM, 6 * DM * 2);
      if (warp == 1) warm(0, 1, 5);
      auto publish = [&](uint32_t w) { if (!(lane & 12)) st_relaxed(at<uint32_t>(g->stat, (qt * 128 + hg * 16 + (warp - 1) * 8 + (lane & 3) * 2 + (lane >> 4)) * 4), w ^ (lds32(sb + SM_EP) << 31)); };
      mbar_wait(sb + B_EP, 0);
      publish(0x80000000u);
      const int r0 = qt * 128 + hg * 16 + (warp - 1) * 8 + (lane >> 4);
      uint32_t e = r0 * DM * 2 + (lane & 15) * 16, w0 = 0;
      uint4 vn[5];
      #pragma unroll
      for (int i = 0; i < 5; i++) vn[i] = ldg_nc(at<uint4>(P.x, e) + i * 16);
      #pragma unroll 1
      for (int it = 0; it < 4; it++) {
        uint4 v[5];
        #pragma unroll
        for (int i = 0; i < 5; i++) { v[i] = vn[i]; vn[i] = ldg_nc(at<uint4>(P.x, e + ((it + 1) & 3) * 2560) + i * 16); }
        const float x0 = bf_lo(__shfl_sync(0xffffffff, v[0].x, lane & 16));
        float m1 = 0.f, s1 = 0.f;
        #pragma unroll
        for (int i = 0; i < 5; i++) {
          const uint32_t vw[4] = {v[i].x, v[i].y, v[i].z, v[i].w};
          #pragma unroll
          for (int k = 0; k < 4; k++) { const float d0 = bf_lo(vw[k]) - x0, d1 = bf_hi(vw[k]) - x0; m1 += d0 + d1; s1 = fmaf(d0, d0, fmaf(d1, d1, s1)); }
        }
        #pragma unroll
        for (int o = 8; o; o >>= 1) { m1 += __shfl_xor_sync(0xffffffff, m1, o); s1 += __shfl_xor_sync(0xffffffff, s1, o); }
        const float md = m1 * (1.f / DM), var = fmaxf(fmaf(-md, md, s1 * (1.f / DM)), 0.f);
        if ((lane & 15) == it) w0 = pack_bf16(x0 + md, sqrt_approx(rbf(rbf(var) + 1e-5f)));
      }
      publish(w0 & 0x7fffffffu);
      TRACE1(2, 8);
      if (warp == 2 && W1SL) warm(1, 0, 5);
      #pragma unroll 1
      for (int j = 0; j < GST; j++) mbar_wait(sb + B_KE + (j & 1) * 8, (j >> 1) & 1);
      int j = GST;
      uint4 xn = vn[0], wn = ldg_nc(at<uint4>(P.wr, (lane & 15) * 16));
      #pragma unroll 1
      for (int it = 0; it < 4; it++) {
        const uint32_t st = __shfl_sync(0xffffffff, w0, (lane & 16) + it), m2 = __byte_perm(st, 0, 0x1010);
        const float rsd = rcp_approx(bf_hi(st));
        float a = 0.f;
        #pragma unroll 1
        for (int i = 0; i < 5; i++) {
          #pragma unroll 1
          do { if (GST) mbar_pace(sb + B_KE + (j & 1) * 8, (j >> 1) & 1); j++; } while (j >= 15 && j < 20);
          uint32_t z[4] = {xn.x, xn.y, xn.z, xn.w};
          const uint32_t ww[4] = {wn.x, wn.y, wn.z, wn.w}, en = e + (i < 4 ? 256 : (it < 3 ? 1536 : 0));
          xn = ldg_nc(at<uint4>(P.x, en)); wn = ldg_nc(at<uint4>(P.wr, (i < 4 ? i * 256 + 256 : 0) + (lane & 15) * 16));
          #pragma unroll
          for (int k = 0; k < 4; k++) {
            const uint32_t n = norm2(z[k], m2, rsd);
            const float lo = bf_lo(n), hi = bf_hi(n);
            a = fmaf(lo, bf_lo(ww[k]), fmaf(hi, bf_hi(ww[k]), a));
            z[k] = pack_bf16(lo * sigmoid_f(lo), hi * sigmoid_f(hi));
          }
          stg128(at<uint4>(g->gate, e), make_uint4(z[0], z[1], z[2], z[3]));
          e = en;
        }
        #pragma unroll
        for (int o = 8; o; o >>= 1) a += __shfl_xor_sync(0xffffffff, a, o);
        uint32_t u = pack_bf16(a, 0.f);
        if (u == 0x8000u) u = 0;
        u = (u & 0x8000u) ? (~u & 0xffffu) : (u | 0x8000u);
        if (!(lane & 15)) st_relaxed(at<uint32_t>(g->key, (r0 + it * 2) * 4), (u << 16) | (uint32_t)(0xffff - r0 - it * 2));
      }
      __syncwarp();
      if (lane == 0) flag_add_release(&g->cnt_gate.v);
      TRACE1(2, 9);
    }
    if (warp == 0) {
      const int row0 = hg * 4 * S_LEN;
      uint32_t s = 2, ph = 1;
      #pragma unroll 1
      for (int c = 1; c < 20; c++) {
        const int k = (c < 10 ? c : (c < 18 ? c - 8 : c - 18)) * 64, cb = hg * 8 + (c < 10 ? 0 : 4);
        const CUtensorMap* const tm = c < 10 ? &tmW4 : &tmW3;
        const uint32_t wb = c < 10 ? U : 12288;
        const bool wx = c < 10 || c >= 18;
        const uint32_t bar = sb + B_WF + s * 8, dst = sb + SM_W + rank * 8192 + s * U;
        mbar_wait(bar + (B_WE - B_WF), ph);
        if (elect_one()) {
          mbar_expect_tx(bar, wx ? wb + U : wb);
          tma_load_3d_mc(dst, tm, bar, 0, k + rank * 16, cb);
          if (wx) tma_load_2d(sb + ((c + 2) & 7) * U, &tmX, bar, k, qt * 128);
        }
        mbar_wait(bar + (B_WE - B_WF) + 8, ph);
        if (elect_one()) {
          mbar_expect_tx(bar + 8, wb);
          tma_load_3d_mc(dst + U, tm, bar + 8, 0, k + 32 + rank * 16, cb);
        }
        s += 2;
        if (s == 6) { s = 0; ph ^= 1; }
      }
      #pragma unroll 1
      for (int i = 0; i < 128; i++) {
        const int isv = i < 5 ? (i >> 1) & 1 : (i < 127 ? ~i & 1 : 1), j = i < 4 ? i & 1 : (i + 1 - 2 * isv) >> 1;
        const uint32_t b = isv * 16 + (j & 1) * 8;
        mbar_wait(sb + (i < 4 ? B_WE + ((0x3153 >> (4 * i)) & 7) * 8 : B_KE + b), i < 4 ? i < 2 : (~j >> 1) & 1);
        if (elect_one()) {
          mbar_expect_tx(sb + B_KF + b, 2 * U);
          tma_load_2d_mc(sb + (isv ? SM_V + (j & 1) * 2 * U : (j & 1) * SM_K1) + rank * U, isv ? &tmV : &tmK, sb + B_KF + b, rank * 64, row0 + j * 128);
        }
      }
      s = 0; ph = 1;
      #pragma unroll 1
      for (int n = 0; n < (X_SKIP(qp) ? 2 : 40); n++) {
        const int st = n < 5 ? (n == 1) : n >> 2, h = n < 5 ? max(n - 1, 0) : n & 3;
        const int u = st < 2 ? 8 + st : ((hg + st - 1) & 7);
        mbar_wait(sb + (n < 6 ? B_KE + (n < 4 ? n >> 1 : 3) * 8 : B_CE + s * 8), ph);
        if (elect_one()) {
          mbar_expect_tx(sb + B_CF + s * 8, U);
          tma_load_2d_mc(sb + c_slot(s) * U + rank * 8192, &tmWO, sb + B_CF + s * 8, u * 64, hg * 512 + ((0x3021 >> (4 * h)) & 3) * 128 + rank * 64);
        }
        if (++s == 6) { s = 0; ph ^= 1; }
      }
      mbar_wait(sb + B_GATE, 0);
      asm volatile("fence.proxy.async.global;" ::: "memory");
      #pragma unroll 1
      for (int n = 0; n < (X_SKIP(qp) ? 0 : 2); n++) {
        mbar_wait(sb + B_CE + 32 + n * 8, 1);
        if (elect_one()) {
          mbar_expect_tx(sb + B_CF + 32 + n * 8, U);
          tma_load_2d(sb + (10 + n) * U, n ? &tmGate : &tmX, sb + B_CF + 32 + n * 8, hg * 64, qt * 128);
        }
      }
      if (!X_SKIP(qp)) {
        const uint4* const last = g->part + (size_t)(qt * 80 + hg * 8 + ((hg + 1) & 7)) * 1024;
        mbar_wait(sb + B_CE + 16, 0);
        if (elect_one()) {
          mbar_expect_tx(sb + B_CF + 8, U);
          bulk_load(sb + U, last, U, sb + B_CF + 8);
        }
      }
    } else if (!elect_one()) {
    } else if (warp == 1) {
      mbar_wait(sb + B_OS + 8, 0);
      flag_wait(at<unsigned>(g->q3_done, (hg >> 1) * 128), lds32(sb + SM_EP) * 16 + qt + 1);
      asm volatile("fence.proxy.async.global;" ::: "memory");
      mbar_expect_tx(sb + B_Q3, U);
      bulk_load(sb + 5 * U, g->q3 + (qt * 8 + hg) * 1024, U, sb + B_Q3);
      flag_wait(&g->mod_done.v, lds32(sb + SM_EP) * 4);
      mbar_arrive(sb + B_GATE);
    } else if (warp == 3) {
      #pragma unroll 1
      for (int j = 2; j < 64 - KVPF; j++) {
        mbar_pace(sb + B_KE + (j & 1) * 8, (~j >> 1) & 1);
        const size_t o = (size_t)(hg * 4 * S_LEN + (j + KVPF) * 128 + qt * 8) * DH;
        if (KVPF) { l2_prefetch(P.k + o, 2048); l2_prefetch(P.v + o, 2048); }
        if (j >= 40 && j < 56) l2_prefetch(P.wo + (size_t)(hg * 512 + qt * 32 + (j - 40) * 2) * DM, 2 * DM * 2);
        if (j >= 56 && j < 60) l2_prefetch(((j & 1) ? P.x : g->gate) + (size_t)(qt * 128 + hg * 16 + (j & 2) * 4) * DM, 8 * DM * 2);
      }
    } else {
      #pragma unroll 1
      for (int h = 0; h < 4; h++) {
        mbar_wait(sb + B_OS + h * 8, 0);
        if (h >= 2) { proxy_fence(); mbar_arrive(sb + B_OF); }
      }
    }
    __syncwarp();
    if ((warp == 1 || warp == 2) && !X_SKIP(qp)) {
      mbar_wait(sb + B_GATE, 0);
      #pragma unroll 1
      for (int i = 0; i < 4; i++) {
        const int r = warp * 8 - 8 + (i & 1) * 4 + (lane >> 3);
        const uint32_t e = ((qt * 128 + hg * 16 + r) * DM + (8 + (i >> 1)) * 64 + (lane & 7) * 8) * 2;
        if (!(i & 1)) bar_sync(8, 192);
        const uint4 xr = ldg_nc(at<uint4>(P.x, e)), gr = ld_relaxed4(at<uint4>(g->gate, e)), sv = lds128(sb + SM_BAR + 1024 + r * 128 + (((lane ^ r) & 7) << 4));
        stg128(at<uint4>(P.out, e), gated(xr, sv, gr));
        if (i == 1) bar_arrive(9, 192);
      }
    }
    cluster_arrive();
    cluster_wait();
  } else {
    const int wg = wgi - 1, t = tid & 127, cw = warp - 4;
    asm volatile("setmaxnreg.inc.sync.aligned.u32 224;");
    if (tid == 128) { sts32(sb + SM_BADF, 0); sts32(sb + SM_ONE, 1); sts32(sb + SM_EP, new_launch(g)); mbar_arrive(sb + B_EP); }
    __syncwarp();
    uint32_t q[32], p[32];
    float s[64], o[64], l[2] = {0.f, 0.f};
    const uint32_t rb = __shfl_sync(0xffffffff, map_cta(sb, lane & 1), lane), wr = sb + cw * 2048, qa = __shfl_sync(0xffffffff, wr + lane * 16, lane);
    uint32_t bad = 0;
    {
      uint32_t st0 = 0, st1 = 0;
      uint32_t sl = 0, ph = 0, rprev = 0;
      if (wg == 1) bar_arrive(1, 256);
      static_for<0, 2>([&](auto pc) { constexpr int pass = decltype(pc)::v;
        float acc[pass ? 96 : 128];
        #pragma unroll 1
        for (int i = 0; i < 10; i++) {
          if (i == (pass ? SKEW1 : SKEW0) / 2) {
            if (pass == 1) {
              const uint32_t d = qa + qo_slot(0);
              #pragma unroll
              for (int e = 0; e < 8; e++) sts128(d + (e >> 2) * U + (e & 3) * 512, p[4*e], p[4*e+1], p[4*e+2], p[4*e+3]);
            }
            bar_sync(1 + wg, 256);
          }
          const uint64_t a = desc(sb, ((i + 2 + 2 * pass) & 7) * 1024 + wg * 512 + doff(0, 16)), b = desc(sb, sl * 128 + doff(SM_W, 2048));
          mbar_wait(sb + B_WF + sl, ph);
          if (i == 0) TRACE(wg, 1 + pass);
          TRACEF(1, wg, 40 + pass * 20 + 2 * i);
          wg_fence();
          wgmma_ss_tb<0, 0>(acc, a, b, i > 0);
          wgmma_ss_tb<2, 512>(acc, a, b, 1);
          wg_commit();
          mbar_wait(sb + B_WF + 8 + sl, ph);
          wg_wait<1>();
          if (i > 0) release2(rprev, lane);
          TRACEF(1, wg, 41 + pass * 20 + 2 * i);
          wg_fence();
          wgmma_ss_tb<4, 1024>(acc, a, b, 1);
          wgmma_ss_tb<6, 1536>(acc, a, b, 1);
          wg_commit();
          rprev = rb + B_WE + 8 + sl;
          sl += 16;
          if (sl == 48) { sl = 0; ph ^= 1; }
          wg_wait<1>();
          release2(rprev - 8, lane);
        }
        mbar_wait(sb + B_EXT + pass * 8, 0);
        if (pass == 0) { st0 = lds32(sb + SM_STAT + (cw * 16 + (lane >> 2)) * 4); st1 = lds32(sb + SM_STAT + (cw * 16 + 8 + (lane >> 2)) * 4); }
        {
          const uint32_t a0 = (lane & 3) ? 0u : (__byte_perm(st0, 0, 0x1010) ^ 0x80008000u), a1 = (lane & 3) ? 0u : (__byte_perm(st1, 0, 0x1010) ^ 0x80008000u);
          wg_fence();
          wgmma_rs_tb<0>(acc, a0, a1, 0u, 0u, (uint64_t)desc_lo(sb + SM_EXT + pass * 1024, 0) | ((uint64_t)2 << 32), 1);
          wg_commit();
        }
        float rs0 = rcp_approx(bf_hi(st0)) * SCALE_LOG2E, rs1 = rcp_approx(bf_hi(st1)) * SCALE_LOG2E;
        bar_arrive(1 + (wg ^ 1), 256);
        wg_wait<0>();
        fence_regs(acc);
        release2(rprev, lane);
        if constexpr (pass == 0) {
          #pragma unroll
          for (int i = 0; i < 32; i++) {
            const float r = (i & 1) ? rs1 : rs0;
            q[i] = pack_bf16(acc[2*i] * r, acc[2*i+1] * r); p[i] = pack_bf16(acc[64+2*i] * r, acc[64+2*i+1] * r);
          }
        } else {
          const uint32_t d = qa + SM_QO;
          #pragma unroll
          for (int e = 0; e < 12; e++) {
            if (e == 8) {
              mbar_wait(sb + B_KF, 0);
              bar_sync(1 + wg, 256);
              TRACE(wg, 3);
              mma_qk<0, 2>(s, q, desc(sb, 2));
              bar_arrive(1 + (wg ^ 1), 256);
              const uint32_t one = lds32(sb + SM_ONE);
              rs0 = __uint_as_float(__float_as_uint(rs0) * one); rs1 = __uint_as_float(__float_as_uint(rs1) * one);
            }
            sts128(d + (e >> 2) * U + (e & 3) * 512, pack_bf16(acc[8*e] * rs0, acc[8*e+1] * rs0), pack_bf16(acc[8*e+2] * rs1, acc[8*e+3] * rs1),
                   pack_bf16(acc[8*e+4] * rs0, acc[8*e+5] * rs0), pack_bf16(acc[8*e+6] * rs1, acc[8*e+7] * rs1));
          }
          wg_wait<0>();
          fence_regs(s);
          release2(rb + B_KE, lane);
          exp_rows<0, 64>(s, l);
          #pragma unroll
          for (int i = 0; i < 32; i++) p[i] = pack_bf16(s[2*i], s[2*i+1]);
        }
      });
    }
    unsigned tz[3] = {0, 0, 0};
    bool ready = false;
    #pragma unroll 1
    for (int j = 1; ; j += 2) {
      int ph = 0;
      #pragma unroll 1
      do {
        attn_step<1, false>(sb, rb, wr, qa, wg, lane, j, ph, s, o, p, q, l, bad, ready, g, tz);
        ph ^= 1; j += 2;
        if (wg < 2) attn_step<0, false>(sb, rb, wr, qa, wg, lane, j - 1, ph, s, o, p, q, l, bad, ready, g, tz);
      } while ((j & 15) != 15);
      if (j == 47) mbar_wait(sb + B_Q3, 0);
      attn_step<1, true>(sb, rb, wr, qa, wg, lane, j, 1, s, o, p, q, l, bad, ready, g, tz);
      if (j == 63) break;
      if (wg < 2) attn_step<0, true>(sb, rb, wr, qa, wg, lane, j + 1, 0, s, o, p, q, l, bad, ready, g, tz);
    }
    mbar_wait(sb + B_OF, 0);
    mbar_wait(sb + B_CF + wg * 8, 0);
    mbar_wait(sb + B_KF + 24, 1);
    bar_sync(1 + wg, 256);
    TRACE(wg, 4);
    mma_pv<SM_V + 2 * U, 2>(o, p, desc(sb, 2), true);
    mma_c<3>(s, sb, wg, 0, 0);
    bar_arrive(1 + (wg ^ 1), 256);
    mbar_wait(sb + B_KE + 16, 1);
    const uint32_t redo = lds32(sb + SM_BADF), one = lds32(sb + SM_ONE), tag = lds32(sb + SM_EP) & 1;
    wg_wait<1>();
    fence_regs(o); fence_regs(p);
    release2(rb + B_KE + 24, lane);
    if (!finish_head(o, l[0], l[1], p, one)) bad |= 8u;
    store_o(wr, lane, SM_V, p);
    if (__builtin_expect(bar_any(4 + wg, 128, bad | redo), 0)) {
      wg_wait<0>();
      fence_regs(s);
      redo_heads(P, sb, bad, qt * 128 + cw * 16, hg * 4);
      #pragma unroll
      for (int i = 0; i < 64; i++) s[i] = 0.f;
      __syncwarp();
      if (lane == 0) mbar_arrive(sb + B_OS + 24);
      mbar_wait(sb + B_OF, 1);
      mma_c<4>(s, sb, wg, 0, 0);
    } else if (lane == 0) mbar_arrive(sb + B_OS + 24);
    wg_wait<0>();
    release2(rb + B_CE + wg * 8, lane);
    if (X_SKIP(qp)) { cluster_arrive(); } else {
      uint4* const part = g->part + (size_t)qt * 80 * 1024 + t;
      const uint32_t tm = 0u - tag;
      uint4 v[8];
      auto fetch = [&](uint4 (&v)[8], const uint4* from) {
        #pragma unroll
        for (int i = 0; i < 8; i++) v[i] = ld_tagged(from + i * 128);
      };
      auto verify = [&](uint4 (&v)[8], auto half, const uint4* from) {
        constexpr int b = decltype(half)::v * 4;
        #pragma unroll 1
        for (int it = 0; __any_sync(0xffffffff, or_bit0(tag_miss(v[b].x, v[b+1].x, tm), tag_miss(v[b+2].x, v[b+3].x, tm))) && it < MAXPOLL; it++) {
          #pragma unroll
          for (int i = b; i < b + 4; i++) v[i] = ld_tagged(from + i * 128);
        }
      };
      int sp = 6, sl = 2 + 3 * wg, ph = 0;
      auto quarter = [&](auto site, int h, int arrive_bar) {
        mbar_wait(sb + B_CF + sl * 8, ph);
        if (h == 0) bar_sync(1 + wg, 256);
        mma_c<decltype(site)::v>(s, sb, sl, h, arrive_bar);
        if (h) { wg_wait<1>(); release2(rb + B_CE + sp * 8, lane); }
        sp = sl;
        if (++sl == 6) { sl = 0; ph ^= 1; }
      };
      auto send = [&](int st) {
        uint4* dst = part + (st < 2 ? (8 + st) * 8192 + hg * 128 : (((hg + st - 1) & 7) * 8 + hg) * 1024);
        const int ds = st < 2 ? 1024 : 128;
        wg_wait<0>();
        fence_regs(s);
        TRACEF(4, wg, 106 + (st >> 1));
        release2(rb + B_CE + sp * 8, lane);
        #pragma unroll
        for (int i = 0; i < 8; i++, dst += ds)
          st_tagged(dst, (pack_bf16(s[8*i], s[8*i+1]) & ~1u) | tag, pack_bf16(s[8*i+2], s[8*i+3]), pack_bf16(s[8*i+4], s[8*i+5]), pack_bf16(s[8*i+6], s[8*i+7]));
        sl += st ? 4 : 3;
        if (sl >= 6) { sl -= 6; ph ^= 1; }
      };
      const uint32_t ta = ((lane >> 4) * 8 + (lane & 7)) * 128 + ((((cw & 3) * 2 + ((lane >> 3) & 1)) ^ (lane & 7)) << 4), ra = (t >> 3) * 128 + (((t & 7) ^ ((t >> 3) & 7)) << 4);
      TRACEF(4, wg, 112);
      bar_sync(1 + wg, 256);
      if (wg == 0) {
        #pragma unroll 1
        for (int st = 0; ; st += 2) {
          TRACEF(4, wg, 100 + (st >> 1));
          const uint4* const src = part + ((7 + (st >> 1)) * 8 + hg) * 1024;
          quarter(IC<5>{}, 1, 0);
          if (st == 2) fetch(v, src);
          quarter(IC<6>{}, 2, 0);
          if (st == 0) mbar_wait(sb + B_OF, 1);
          quarter(IC<7>{}, 3, 2);
          send(st);
          if (st == 8) break;
          if (st == 2 || st == 4) {
            float a[8];
            #pragma unroll
            for (int i = 0; i < 8; i++) a[i] = 0.f;
            static_for<0, 2>([&](auto hf) {
              verify(v, hf, src);
              #pragma unroll
              for (int i = decltype(hf)::v * 4; i < decltype(hf)::v * 4 + 4; i++) { add8(a, v[i]); if (st == 2) v[i] = ld_tagged(src + 8192 + i * 128); }
            });
            if (st == 4) bar_sync(9, 192);
            stsm4t(sb + SM_BAR + 1024 + ta, pack_bf16(a[0], a[1]), pack_bf16(a[2], a[3]), pack_bf16(a[4], a[5]), pack_bf16(a[6], a[7]));
            bar_arrive(8, 192);
          }
          quarter(IC<8>{}, 0, 0);
        }
        cluster_arrive();
        mbar_wait(sb + B_CF + 32, 0);
        mbar_wait(sb + B_CF + 40, 0);
        __nv_bfloat16* const op = P.out + (qt * 128 + (t >> 3)) * DM + hg * 64 + (t & 7) * 8;
        bar_sync(1, 256);
        uint4 xv[8];
        #pragma unroll
        for (int i = 0; i < 8; i++) { xv[i] = lds128(sb + 10 * U + i * 2048 + ra); v[i] = lds128(sb + 11 * U + i * 2048 + ra); }
        #pragma unroll
        for (int i = 0; i < 8; i++) {
          if (!(i & 3)) bar_sync(6 + (i >> 2), 256);
          *(uint4*)(op + i * 16 * DM) = gated(xv[i], lds128(sb + i * 2048 + ra), v[i]);
        }
      } else {
        float T[64];
        auto from = [&](int f) { return part + (hg * 8 + ((hg + 1 - f) & 7)) * 1024; };
        auto take = [&](uint4 (&v)[8], auto half, int f, bool more) {
          verify(v, half, from(f));
          const uint4* const nx = from(f + 1);
          #pragma unroll
          for (int i = decltype(half)::v * 4; i < decltype(half)::v * 4 + 4; i++) { add8(T + 8 * i, v[i]); if (more) v[i] = ld_tagged(nx + i * 128); }
        };
        #pragma unroll
        for (int i = 0; i < 64; i++) T[i] = 0.f;
        #pragma unroll 1
        for (int st = 1; ; st += 2) {
          TRACEF(4, wg, 100 + (st >> 1));
          quarter(IC<9>{}, 1, 0);
          if (st >= 5) take(v, IC<0>{}, st - 3, true);
          quarter(IC<10>{}, 2, 0);
          if (st >= 5) take(v, IC<1>{}, st - 3, true);
          if (st == 1) mbar_wait(sb + B_OF, 1);
          quarter(IC<11>{}, 3, st < 9);
          if (st < 9) send(st);
          if (st >= 5) { take(v, IC<0>{}, st - 2, st < 9); take(v, IC<1>{}, st - 2, st < 9); }
          else if (st == 3) fetch(v, from(2));
          if (st == 9) break;
          quarter(IC<12>{}, 0, 0);
        }
        cluster_arrive();
        TRACEF(4, wg, 113);
        wg_wait<0>();
        fence_regs(s);
        TRACEF(4, wg, 110);
        mbar_wait(sb + B_CF + 8, 1);
        #pragma unroll
        for (int i = 0; i < 8; i++) v[i] = lds128(sb + U + i * 2048 + t * 16);
        bar_arrive(1, 256);
        #pragma unroll
        for (int i = 0; i < 64; i++) T[i] += s[i];
        static_for<0, 2>([&](auto hf) {
          take(v, hf, 8, false);
          if (decltype(hf)::v == 0) TRACE(wg, 5);
          #pragma unroll
          for (int i = decltype(hf)::v * 4; i < decltype(hf)::v * 4 + 4; i++)
            stsm4t(sb + i * 2048 + ta, pack_bf16(T[8*i], T[8*i+1]), pack_bf16(T[8*i+2], T[8*i+3]), pack_bf16(T[8*i+4], T[8*i+5]), pack_bf16(T[8*i+6], T[8*i+7]));
          bar_arrive(6 + decltype(hf)::v, 256);
        });
      }
    }
    TRACE(wg, 6);
    cluster_wait();
  }
}

typedef CUresult (*EncodeFn)(CUtensorMap*, CUtensorMapDataType, cuuint32_t, void*, const cuuint64_t*, const cuuint64_t*, const cuuint32_t*, const cuuint32_t*,
                             CUtensorMapInterleave, CUtensorMapSwizzle, CUtensorMapL2promotion, CUtensorMapFloatOOBfill);
void make_map(EncodeFn enc, CUtensorMap* tm, const void* ptr, uint64_t inner, uint64_t outer, uint32_t box_outer, uint32_t blocks = 0) {
  cuuint64_t dims[3] = {blocks ? 64 : inner, outer, inner / 64}; cuuint64_t strides[2] = {inner * 2, 128};
  cuuint32_t box[3] = {64, box_outer, blocks}; cuuint32_t es[3] = {1, 1, 1};
  enc(tm, CU_TENSOR_MAP_DATA_TYPE_BFLOAT16, blocks ? 3 : 2, const_cast<void*>(ptr), dims, strides, box, es, CU_TENSOR_MAP_INTERLEAVE_NONE,
      CU_TENSOR_MAP_SWIZZLE_128B, CU_TENSOR_MAP_L2_PROMOTION_L2_256B, CU_TENSOR_MAP_FLOAT_OOB_FILL_NONE);
}

}

extern "C" void kernel_launch(void* const* d_in, const int* in_sizes, int n_in, void* d_out, int out_size) {
  (void)in_sizes; (void)n_in; (void)out_size;
  Params P;
  P.x = (const __nv_bfloat16*)d_in[0]; P.k = (const __nv_bfloat16*)d_in[1]; P.v = (const __nv_bfloat16*)d_in[2];
  P.wq = (const __nv_bfloat16*)d_in[3]; P.wo = (const __nv_bfloat16*)d_in[4]; P.wr = (const __nv_bfloat16*)d_in[6];
  P.out = (__nv_bfloat16*)d_out;
  cudaGetSymbolAddress((void**)&P.g, g_s);
  void* fn = nullptr; cudaDriverEntryPointQueryResult st;
  cudaGetDriverEntryPoint("cuTensorMapEncodeTiled", &fn, cudaEnableDefault, &st);
  EncodeFn enc = (EncodeFn)fn;
  CUtensorMap tmX, tmW4, tmW3, tmW1, tmK, tmV, tmWO, tmG, tmU, tmD, tmGate;
  make_map(enc, &tmGate, P.g->gate, DM, S_LEN, 128);
  make_map(enc, &tmX, P.x, DM, S_LEN, 128);
  make_map(enc, &tmW4, P.wq, NH * DH, DM, 16, 4);
  make_map(enc, &tmW3, P.wq, NH * DH, DM, 16, 3);
  make_map(enc, &tmW1, P.wq, NH * DH, DM, 128);
  make_map(enc, &tmK, P.k, DH, (uint64_t)NH * S_LEN, 128);
  make_map(enc, &tmV, P.v, DH, (uint64_t)NH * S_LEN, 128);
  make_map(enc, &tmWO, P.wo, DM, NH * DH, 64);
  make_map(enc, &tmG, d_in[7], FF, DM, 128);
  make_map(enc, &tmU, d_in[8], FF, DM, 128);
  make_map(enc, &tmD, d_in[9], DM, FF, 128);
  cudaFuncSetAttribute(fused_kernel, cudaFuncAttributeMaxDynamicSharedMemorySize, SMEM_BYTES);
  fused_kernel<<<132, 384, SMEM_BYTES, cudaStreamPerThread>>>(tmX, tmW4, tmW3, tmW1, tmK, tmV, tmWO, tmG, tmU, tmD, tmGate, P);
}
```

```cpp
#include <cuda_runtime.h>
#include <cuda_bf16.h>
#include <cuda.h>
#include <stdint.h>

#define C_EARLY 6
#define MAXPOLL (1 << 22)
#define SKEW0 18
#define SKEW1 18
#define DPOS 44
#define DPOSF 36
#define KVPF 4
#define ETEST 1
#define SMV 1
#define X_SKIP(qp) false
#define GST 2
#define W1SL 300
#define XPF 1
#define WAITMAX (1 << 19)
#define CSB 10
#define W0E 1
#define QSP 6
namespace {

constexpr int S_LEN = 2048, DM = 640, NH = 32, DH = 128, FF = 1728, TOPC = 8;
constexpr float SCALE_LOG2E = 0.08838834764831845f * 1.4426950408889634f;

struct alignas(128) Cnt { unsigned v; unsigned pad[31]; };
struct Scratch {
  alignas(128) unsigned long long ticket;
  alignas(128)
  uint4 part[16 * 10 * 8 * 1024];
  __nv_bfloat16 gate[S_LEN * DM];
  uint32_t stat[S_LEN];
  uint4 cs[NH * DH];
  float ypart[4 * TOPC * DM];
  uint4 q3[16 * 8 * 1024];
  uint32_t key[S_LEN];
  Cnt cnt_gate, cnt_mod, mod_done, q3_done[4];
};
__device__ Scratch g_s;

__device__ __forceinline__ uint32_t smem_u32(const void* p) { return (uint32_t)__cvta_generic_to_shared(p); }
template <class T> __device__ __forceinline__ T* at(const void* p, uint32_t off) { uint64_t r;
  asm("{\n.reg .u32 lo, hi;\nmov.b64 {lo, hi}, %1;\nadd.cc.u32 lo, lo, %2;\naddc.u32 hi, hi, 0;\nmov.b64 %0, {lo, hi};\n}\n" : "=l"(r) : "l"(p), "r"(off)); return (T*)r; }
__device__ __forceinline__ void mbar_init(uint32_t bar, uint32_t cnt) { asm volatile("mbarrier.init.shared::cta.b64 [%0], %1;" :: "r"(bar), "r"(cnt) : "memory"); }
__device__ __forceinline__ void mbar_expect_tx(uint32_t bar, uint32_t bytes) { asm volatile("mbarrier.arrive.expect_tx.shared::cta.b64 _, [%0], %1;" :: "r"(bar), "r"(bytes) : "memory"); }
__device__ __forceinline__ void mbar_arrive(uint32_t bar) { asm volatile("mbarrier.arrive.shared::cta.b64 _, [%0];" :: "r"(bar) : "memory"); }
__device__ __forceinline__ uint32_t map_cta(uint32_t a, uint32_t cta) { uint32_t r; asm volatile("mapa.shared::cluster.u32 %0, %1, %2;" : "=r"(r) : "r"(a), "r"(cta)); return r; }
__device__ __forceinline__ void mbar_arrive_cluster(uint32_t bar) { asm volatile("mbarrier.arrive.shared::cluster.b64 _, [%0];" :: "r"(bar) : "memory"); }
__device__ __forceinline__ void mbar_wait(uint32_t bar, uint32_t parity) {
  asm volatile("{\n.reg .pred p;\n.reg .u32 c;\nmov.u32 c, 0;\nLAB_WAIT:\nmbarrier.try_wait.parity.shared::cta.b64 p, [%0], %1;\n@p bra LAB_DONE;\n"
               "add.u32 c, c, 1;\nsetp.lt.u32 p, c, %2;\n@p bra LAB_WAIT;\ntrap;\nLAB_DONE:\n}\n" :: "r"(bar), "r"(parity), "n"(WAITMAX) : "memory"); }
__device__ __forceinline__ bool mbar_test2(uint32_t bar0, uint32_t par0, uint32_t bar1, uint32_t par1) { uint32_t r;
  asm volatile("{\n.reg .pred p, q;\nmbarrier.test_wait.parity.shared::cta.b64 p, [%1], %2;\nmbarrier.test_wait.parity.shared::cta.b64 q, [%3], %4;\nand.pred p, p, q;\nselp.u32 %0, 1, 0, p;\n}\n"
               : "=r"(r) : "r"(bar0), "r"(par0), "r"(bar1), "r"(par1) : "memory"); return r; }
__device__ __forceinline__ void mbar_pace(uint32_t bar, uint32_t parity) {
  asm volatile("{\n.reg .pred p;\n.reg .u32 c;\nmov.u32 c, 0;\nLAB_WAIT:\nmbarrier.try_wait.parity.shared::cta.b64 p, [%0], %1;\n@p bra LAB_DONE;\n"
               "add.u32 c, c, 1;\nsetp.lt.u32 p, c, 64;\n@p bra LAB_WAIT;\nLAB_DONE:\n}\n" :: "r"(bar), "r"(parity) : "memory"); }
__device__ __forceinline__ void flag_wait(const unsigned* p, unsigned target, unsigned ns = 500) {
  asm volatile("{\n.reg .pred p;\n.reg .u32 c, v;\nmov.u32 c, 0;\nLAB_WAIT:\nld.relaxed.gpu.global.u32 v, [%0];\nsub.u32 v, v, %1;\nsetp.ge.s32 p, v, 0;\n@p bra LAB_DONE;\n"
               "nanosleep.u32 %2;\nadd.u32 c, c, 1;\nsetp.lt.u32 p, c, 8388608;\n@p bra LAB_WAIT;\ntrap;\nLAB_DONE:\nld.acquire.gpu.global.u32 v, [%0];\n}\n" :: "l"(p), "r"(target), "r"(ns) : "memory"); }
__device__ __forceinline__ void flag_add_release(unsigned* p) { asm volatile("fence.acq_rel.gpu;\nred.relaxed.gpu.global.add.u32 [%0], 1;" :: "l"(p) : "memory"); }
__device__ __forceinline__ void tma_load_2d(uint32_t dst, const CUtensorMap* tm, uint32_t bar, int c0, int c1) {
  asm volatile("cp.async.bulk.tensor.2d.shared::cluster.global.mbarrier::complete_tx::bytes [%0], [%1, {%3, %4}], [%2];"
    :: "r"(dst), "l"(tm), "r"(bar), "r"(c0), "r"(c1) : "memory"); }
__device__ __forceinline__ void tma_load_2d_mc(uint32_t dst, const CUtensorMap* tm, uint32_t bar, int c0, int c1) {
  asm volatile("cp.async.bulk.tensor.2d.shared::cluster.global.mbarrier::complete_tx::bytes.multicast::cluster [%0], [%1, {%3, %4}], [%2], %5;"
    :: "r"(dst), "l"(tm), "r"(bar), "r"(c0), "r"(c1), "h"((uint16_t)3) : "memory"); }
__device__ __forceinline__ void tma_load_3d(uint32_t dst, const CUtensorMap* tm, uint32_t bar, int c0, int c1, int c2) {
  asm volatile("cp.async.bulk.tensor.3d.shared::cluster.global.mbarrier::complete_tx::bytes [%0], [%1, {%3, %4, %5}], [%2];"
    :: "r"(dst), "l"(tm), "r"(bar), "r"(c0), "r"(c1), "r"(c2) : "memory"); }
__device__ __forceinline__ void tma_load_3d_mc(uint32_t dst, const CUtensorMap* tm, uint32_t bar, int c0, int c1, int c2) {
  asm volatile("cp.async.bulk.tensor.3d.shared::cluster.global.mbarrier::complete_tx::bytes.multicast::cluster [%0], [%1, {%3, %4, %5}], [%2], %6;"
    :: "r"(dst), "l"(tm), "r"(bar), "r"(c0), "r"(c1), "r"(c2), "h"((uint16_t)3) : "memory"); }
__device__ __forceinline__ void bulk_load(uint32_t dst, const void* src, uint32_t bytes, uint32_t bar) {
  asm volatile("cp.async.bulk.shared::cluster.global.mbarrier::complete_tx::bytes [%0], [%1], %2, [%3];" :: "r"(dst), "l"(src), "r"(bytes), "r"(bar) : "memory"); }
__device__ __forceinline__ void l2_prefetch(const void* p, uint32_t bytes) { asm volatile("cp.async.bulk.prefetch.L2.global [%0], %1;" :: "l"(p), "r"(bytes) : "memory"); }
__device__ __forceinline__ void wg_fence() { asm volatile("wgmma.fence.sync.aligned;" ::: "memory"); }
__device__ __forceinline__ void wg_commit() { asm volatile("wgmma.commit_group.sync.aligned;" ::: "memory"); }
template <int N> __device__ __forceinline__ void wg_wait() { asm volatile("wgmma.wait_group.sync.aligned %0;" :: "n"(N) : "memory"); }
__device__ __forceinline__ void bar_sync(int id, int n) { asm volatile("bar.sync %0, %1;" :: "r"(id), "r"(n) : "memory"); }
__device__ __forceinline__ void bar_arrive(int id, int n) { asm volatile("bar.arrive %0, %1;" :: "r"(id), "r"(n) : "memory"); }
__device__ __forceinline__ bool bar_any(int id, int n, uint32_t v) { uint32_t r;
  asm volatile("{\n.reg .pred p;\nsetp.ne.u32 p, %3, 0;\nbar.red.or.pred p, %1, %2, p;\nselp.u32 %0, 1, 0, p;\n}\n" : "=r"(r) : "r"(id), "r"(n), "r"(v) : "memory"); return r; }
__device__ __forceinline__ int sel_lt(int a, int b, int x, int y) { int r; asm("{\n.reg .pred p;\nsetp.lt.s32 p, %1, %2;\nselp.s32 %0, %3, %4, p;\n}\n" : "=r"(r) : "r"(a), "r"(b), "r"(x), "r"(y)); return r; }
__device__ __forceinline__ bool elect_one() { uint32_t r; asm volatile("{\n.reg .pred p;\nelect.sync _|p, 0xffffffff;\nselp.u32 %0, 1, 0, p;\n}\n" : "=r"(r)); return r; }
__device__ __forceinline__ void cluster_arrive() { asm volatile("barrier.cluster.arrive.relaxed.aligned;" ::: "memory"); }
__device__ __forceinline__ void cluster_wait() { asm volatile("barrier.cluster.wait.aligned;" ::: "memory"); }
__device__ __forceinline__ void proxy_fence() { asm volatile("fence.proxy.async.shared::cta;" ::: "memory"); }
__device__ __forceinline__ uint32_t pack_bf16(float lo, float hi) { uint32_t r; asm("cvt.rn.bf16x2.f32 %0, %1, %2;" : "=r"(r) : "f"(hi), "f"(lo)); return r; }
__device__ __forceinline__ float bf_lo(uint32_t v) { return __uint_as_float(v << 16); }
__device__ __forceinline__ float bf_hi(uint32_t v) { return __uint_as_float(v & 0xffff0000u); }
__device__ __forceinline__ void add8(float* a, const uint4& w) {
  a[0] += bf_lo(w.x); a[1] += bf_hi(w.x); a[2] += bf_lo(w.y); a[3] += bf_hi(w.y); a[4] += bf_lo(w.z); a[5] += bf_hi(w.z); a[6] += bf_lo(w.w); a[7] += bf_hi(w.w); }
__device__ __forceinline__ float rbf(float x) { return __bfloat162float(__float2bfloat16_rn(x)); }
__device__ __forceinline__ float ex2(float x) { float y; asm("ex2.approx.ftz.f32 %0, %1;" : "=f"(y) : "f"(x)); return y; }
__device__ __forceinline__ uint32_t lds32(uint32_t a) { uint32_t v; asm volatile("ld.shared.u32 %0, [%1];" : "=r"(v) : "r"(a) : "memory"); return v; }
__device__ __forceinline__ void sts32(uint32_t a, uint32_t v) { asm volatile("st.shared.u32 [%0], %1;" :: "r"(a), "r"(v) : "memory"); }
__device__ __forceinline__ uint4 lds128(uint32_t a) { uint4 v; asm volatile("ld.shared.v4.u32 {%0,%1,%2,%3}, [%4];" : "=r"(v.x), "=r"(v.y), "=r"(v.z), "=r"(v.w) : "r"(a) : "memory"); return v; }
__device__ __forceinline__ void sts128(uint32_t a, uint32_t x, uint32_t y, uint32_t z, uint32_t w) { asm volatile("st.shared.v4.u32 [%0], {%1,%2,%3,%4};" :: "r"(a), "r"(x), "r"(y), "r"(z), "r"(w) : "memory"); }
__device__ __forceinline__ void st_tagged(uint4* p, uint32_t x, uint32_t y, uint32_t z, uint32_t w) {
  asm volatile("st.relaxed.gpu.global.v4.u32 [%0], {%1,%2,%3,%4};" :: "l"(p), "r"(x), "r"(y), "r"(z), "r"(w) : "memory"); }
__device__ __forceinline__ uint4 ld_tagged(const uint4* p) { uint4 v;
  asm volatile("{\n.reg .b128 v;\nld.relaxed.gpu.global.b128 v, [%4];\nmov.b128 {%0,%1,%2,%3}, v;\n}\n" : "=r"(v.x), "=r"(v.y), "=r"(v.z), "=r"(v.w) : "l"(p) : "memory"); return v; }
__device__ __forceinline__ uint4 ld_relaxed4(const void* p) { uint4 v;
  asm volatile("ld.relaxed.gpu.global.v4.u32 {%0,%1,%2,%3}, [%4];" : "=r"(v.x), "=r"(v.y), "=r"(v.z), "=r"(v.w) : "l"(p) : "memory"); return v; }
__device__ __forceinline__ uint4 ldg_nc(const void* p) { uint4 v;
  asm volatile("ld.global.nc.L1::no_allocate.v4.u32 {%0,%1,%2,%3}, [%4];" : "=r"(v.x), "=r"(v.y), "=r"(v.z), "=r"(v.w) : "l"(p) : "memory"); return v; }
__device__ __forceinline__ uint32_t ldg32(const void* p) { uint32_t v; asm volatile("ld.relaxed.gpu.global.u32 %0, [%1];" : "=r"(v) : "l"(p) : "memory"); return v; }
__device__ __forceinline__ void stg128(void* p, const uint4& v) { asm volatile("st.global.v4.u32 [%0], {%1,%2,%3,%4};" :: "l"(p), "r"(v.x), "r"(v.y), "r"(v.z), "r"(v.w) : "memory"); }
__device__ __forceinline__ void st_relaxed(uint32_t* p, uint32_t v) { asm volatile("st.relaxed.gpu.global.u32 [%0], %1;" :: "l"(p), "r"(v) : "memory"); }
__device__ __forceinline__ uint32_t mul_bf2(uint32_t a, uint32_t b) { uint32_t r; asm("mul.rn.bf16x2 %0, %1, %2;" : "=r"(r) : "r"(a), "r"(b)); return r; }
__device__ __forceinline__ uint32_t add_bf2(uint32_t a, uint32_t b) { uint32_t r; asm("add.rn.bf16x2 %0, %1, %2;" : "=r"(r) : "r"(a), "r"(b)); return r; }
__device__ __forceinline__ uint32_t sub_bf2(uint32_t a, uint32_t b) { uint32_t r; asm("sub.rn.bf16x2 %0, %1, %2;" : "=r"(r) : "r"(a), "r"(b)); return r; }
__device__ __forceinline__ void stsm4(uint32_t a, uint32_t r0, uint32_t r1, uint32_t r2, uint32_t r3) {
  asm volatile("stmatrix.sync.aligned.m8n8.x4.shared.b16 [%0], {%1,%2,%3,%4};" :: "r"(a), "r"(r0), "r"(r1), "r"(r2), "r"(r3) : "memory"); }
__device__ __forceinline__ void stsm4t(uint32_t a, uint32_t r0, uint32_t r1, uint32_t r2, uint32_t r3) {
  asm volatile("stmatrix.sync.aligned.m8n8.x4.trans.shared.b16 [%0], {%1,%2,%3,%4};" :: "r"(a), "r"(r0), "r"(r1), "r"(r2), "r"(r3) : "memory"); }
__device__ __forceinline__ uint4 gated(const uint4& x, const uint4& s, const uint4& g) {
  return make_uint4(add_bf2(x.x, mul_bf2(s.x, g.x)), add_bf2(x.y, mul_bf2(s.y, g.y)), add_bf2(x.z, mul_bf2(s.z, g.z)), add_bf2(x.w, mul_bf2(s.w, g.w))); }
__device__ __forceinline__ uint32_t or_bit0(uint32_t a, uint32_t b) { uint32_t d; asm("lop3.b32 %0, %1, %2, 1, 0xA8;" : "=r"(d) : "r"(a), "r"(b)); return d; }
__device__ __forceinline__ uint32_t tag_miss(uint32_t a, uint32_t b, uint32_t tm) { uint32_t d; asm("lop3.b32 %0, %1, %2, %3, 0x7E;" : "=r"(d) : "r"(a), "r"(b), "r"(tm)); return d; }
template <int R> __device__ __forceinline__ void fence_regs(float (&d)[R]) {
  #pragma unroll
  for (int i = 0; i < R; i++) asm volatile("" : "+f"(d[i]) :: "memory"); }
template <int R> __device__ __forceinline__ void fence_regs(uint32_t (&d)[R]) {
  #pragma unroll
  for (int i = 0; i < R; i++) asm volatile("" : "+r"(d[i]) :: "memory"); }
__device__ __forceinline__ uint32_t desc_lo(uint32_t addr, uint32_t lbo_bytes) { return ((addr & 0x3FFFF) >> 4) | ((lbo_bytes >> 4) << 16); }
__device__ __forceinline__ uint64_t desc(uint32_t sb, uint32_t var = 0) {
  uint64_t d; asm("mov.b64 %0, {%1, %2};" : "=l"(d) : "r"(desc_lo(sb, 0) + var), "r"(0x40000040u)); return d; }
__host__ __device__ constexpr int doff(uint32_t off, uint32_t lbo_bytes) { return (off >> 4) | ((lbo_bytes >> 4) << 16); }
__device__ __forceinline__ float rcp_approx(float x) { float y; asm("rcp.approx.f32 %0, %1;" : "=f"(y) : "f"(x)); return y; }
__device__ __forceinline__ float rcp_fast(float x) { float y; asm("rcp.approx.ftz.f32 %0, %1;" : "=f"(y) : "f"(x)); return y; }
__device__ __forceinline__ float sqrt_approx(float x) { float y; asm("sqrt.approx.f32 %0, %1;" : "=f"(y) : "f"(x)); return y; }
__device__ __forceinline__ float sigmoid_f(float z) { return rcp_fast(1.f + ex2(z * -1.4426950408889634f)); }
__device__ __forceinline__ uint32_t norm2(uint32_t x, uint32_t mean2, float rsd) { const uint32_t d = sub_bf2(x, mean2); return pack_bf16(bf_lo(d) * rsd, bf_hi(d) * rsd); }
#define TRACE(w, i)
#define TRACE1(w, i)
#define TRACEF(m, w, i)
#define TRACEO(i)

template <int OA, int OB> __device__ __forceinline__ void wgmma_ss_tb(float (&d)[128], uint64_t da, uint64_t db, int sd) {
  asm volatile("{\n.reg .pred p;\n.reg .b64 a, b;\nadd.s64 a, %128, %131;\nadd.s64 b, %129, %132;\nsetp.ne.b32 p, %130, 0;\n"
    "wgmma.mma_async.sync.aligned.m64n256k16.f32.bf16.bf16 {%0, %1, %2, %3, %4, %5, %6, %7, %8, %9, %10, %11, %12, %13, %14, %15, %16, %17, %18, %19, %20, %21, %22, %23, %24, %25, %26, %27, %28, %29, %30, %31, %32, %33, %34, %35, %36, %37, %38, %39, %40, %41, %42, %43, %44, %45, %46, %47, %48, %49, %50, %51, %52, %53, %54, %55, %56, %57, %58, %59, %60, %61, %62, %63, %64, %65, %66, %67, %68, %69, %70, %71, %72, %73, %74, %75, %76, %77, %78, %79, %80, %81, %82, %83, %84, %85, %86, %87, %88, %89, %90, %91, %92, %93, %94, %95, %96, %97, %98, %99, %100, %101, %102, %103, %104, %105, %106, %107, %108, %109, %110, %111, %112, %113, %114, %115, %116, %117, %118, %119, %120, %121, %122, %123, %124, %125, %126, %127}, a, b, p, 1, 1, 0, 1;\n}\n"
    : "+f"(d[0]), "+f"(d[1]), "+f"(d[2]), "+f"(d[3]), "+f"(d[4]), "+f"(d[5]), "+f"(d[6]), "+f"(d[7]), "+f"(d[8]), "+f"(d[9]), "+f"(d[10]), "+f"(d[11]), "+f"(d[12]), "+f"(d[13]), "+f"(d[14]), "+f"(d[15]), "+f"(d[16]), "+f"(d[17]), "+f"(d[18]), "+f"(d[19]), "+f"(d[20]), "+f"(d[21]), "+f"(d[22]), "+f"(d[23]), "+f"(d[24]), "+f"(d[25]), "+f"(d[26]), "+f"(d[27]), "+f"(d[28]), "+f"(d[29]), "+f"(d[30]), "+f"(d[31]), "+f"(d[32]), "+f"(d[33]), "+f"(d[34]), "+f"(d[35]), "+f"(d[36]), "+f"(d[37]), "+f"(d[38]), "+f"(d[39]), "+f"(d[40]), "+f"(d[41]), "+f"(d[42]), "+f"(d[43]), "+f"(d[44]), "+f"(d[45]), "+f"(d[46]), "+f"(d[47]), "+f"(d[48]), "+f"(d[49]), "+f"(d[50]), "+f"(d[51]), "+f"(d[52]), "+f"(d[53]), "+f"(d[54]), "+f"(d[55]), "+f"(d[56]), "+f"(d[57]), "+f"(d[58]), "+f"(d[59]), "+f"(d[60]), "+f"(d[61]), "+f"(d[62]), "+f"(d[63]), "+f"(d[64]), "+f"(d[65]), "+f"(d[66]), "+f"(d[67]), "+f"(d[68]), "+f"(d[69]), "+f"(d[70]), "+f"(d[71]), "+f"(d[72]), "+f"(d[73]), "+f"(d[74]), "+f"(d[75]), "+f"(d[76]), "+f"(d[77]), "+f"(d[78]), "+f"(d[79]), "+f"(d[80]), "+f"(d[81]), "+f"(d[82]), "+f"(d[83]), "+f"(d[84]), "+f"(d[85]), "+f"(d[86]), "+f"(d[87]), "+f"(d[88]), "+f"(d[89]), "+f"(d[90]), "+f"(d[91]), "+f"(d[92]), "+f"(d[93]), "+f"(d[94]), "+f"(d[95]), "+f"(d[96]), "+f"(d[97]), "+f"(d[98]), "+f"(d[99]), "+f"(d[100]), "+f"(d[101]), "+f"(d[102]), "+f"(d[103]), "+f"(d[104]), "+f"(d[105]), "+f"(d[106]), "+f"(d[107]), "+f"(d[108]), "+f"(d[109]), "+f"(d[110]), "+f"(d[111]), "+f"(d[112]), "+f"(d[113]), "+f"(d[114]), "+f"(d[115]), "+f"(d[116]), "+f"(d[117]), "+f"(d[118]), "+f"(d[119]), "+f"(d[120]), "+f"(d[121]), "+f"(d[122]), "+f"(d[123]), "+f"(d[124]), "+f"(d[125]), "+f"(d[126]), "+f"(d[127])
    : "l"(da), "l"(db), "r"(sd), "n"(OA), "n"(OB));
}
template <int OB> __device__ __forceinline__ void wgmma_rs_tb(float (&d)[128], uint32_t a0, uint32_t a1, uint32_t a2, uint32_t a3, uint64_t db, int sd) {
  asm volatile("{\n.reg .pred p;\n.reg .b64 b;\nadd.s64 b, %132, %134;\nsetp.ne.b32 p, %133, 0;\n"
    "wgmma.mma_async.sync.aligned.m64n256k16.f32.bf16.bf16 {%0, %1, %2, %3, %4, %5, %6, %7, %8, %9, %10, %11, %12, %13, %14, %15, %16, %17, %18, %19, %20, %21, %22, %23, %24, %25, %26, %27, %28, %29, %30, %31, %32, %33, %34, %35, %36, %37, %38, %39, %40, %41, %42, %43, %44, %45, %46, %47, %48, %49, %50, %51, %52, %53, %54, %55, %56, %57, %58, %59, %60, %61, %62, %63, %64, %65, %66, %67, %68, %69, %70, %71, %72, %73, %74, %75, %76, %77, %78, %79, %80, %81, %82, %83, %84, %85, %86, %87, %88, %89, %90, %91, %92, %93, %94, %95, %96, %97, %98, %99, %100, %101, %102, %103, %104, %105, %106, %107, %108, %109, %110, %111, %112, %113, %114, %115, %116, %117, %118, %119, %120, %121, %122, %123, %124, %125, %126, %127}, {%128, %129, %130, %131}, b, p, 1, 1, 1;\n}\n"
    : "+f"(d[0]), "+f"(d[1]), "+f"(d[2]), "+f"(d[3]), "+f"(d[4]), "+f"(d[5]), "+f"(d[6]), "+f"(d[7]), "+f"(d[8]), "+f"(d[9]), "+f"(d[10]), "+f"(d[11]), "+f"(d[12]), "+f"(d[13]), "+f"(d[14]), "+f"(d[15]), "+f"(d[16]), "+f"(d[17]), "+f"(d[18]), "+f"(d[19]), "+f"(d[20]), "+f"(d[21]), "+f"(d[22]), "+f"(d[23]), "+f"(d[24]), "+f"(d[25]), "+f"(d[26]), "+f"(d[27]), "+f"(d[28]), "+f"(d[29]), "+f"(d[30]), "+f"(d[31]), "+f"(d[32]), "+f"(d[33]), "+f"(d[34]), "+f"(d[35]), "+f"(d[36]), "+f"(d[37]), "+f"(d[38]), "+f"(d[39]), "+f"(d[40]), "+f"(d[41]), "+f"(d[42]), "+f"(d[43]), "+f"(d[44]), "+f"(d[45]), "+f"(d[46]), "+f"(d[47]), "+f"(d[48]), "+f"(d[49]), "+f"(d[50]), "+f"(d[51]), "+f"(d[52]), "+f"(d[53]), "+f"(d[54]), "+f"(d[55]), "+f"(d[56]), "+f"(d[57]), "+f"(d[58]), "+f"(d[59]), "+f"(d[60]), "+f"(d[61]), "+f"(d[62]), "+f"(d[63]), "+f"(d[64]), "+f"(d[65]), "+f"(d[66]), "+f"(d[67]), "+f"(d[68]), "+f"(d[69]), "+f"(d[70]), "+f"(d[71]), "+f"(d[72]), "+f"(d[73]), "+f"(d[74]), "+f"(d[75]), "+f"(d[76]), "+f"(d[77]), "+f"(d[78]), "+f"(d[79]), "+f"(d[80]), "+f"(d[81]), "+f"(d[82]), "+f"(d[83]), "+f"(d[84]), "+f"(d[85]), "+f"(d[86]), "+f"(d[87]), "+f"(d[88]), "+f"(d[89]), "+f"(d[90]), "+f"(d[91]), "+f"(d[92]), "+f"(d[93]), "+f"(d[94]), "+f"(d[95]), "+f"(d[96]), "+f"(d[97]), "+f"(d[98]), "+f"(d[99]), "+f"(d[100]), "+f"(d[101]), "+f"(d[102]), "+f"(d[103]), "+f"(d[104]), "+f"(d[105]), "+f"(d[106]), "+f"(d[107]), "+f"(d[108]), "+f"(d[109]), "+f"(d[110]), "+f"(d[111]), "+f"(d[112]), "+f"(d[113]), "+f"(d[114]), "+f"(d[115]), "+f"(d[116]), "+f"(d[117]), "+f"(d[118]), "+f"(d[119]), "+f"(d[120]), "+f"(d[121]), "+f"(d[122]), "+f"(d[123]), "+f"(d[124]), "+f"(d[125]), "+f"(d[126]), "+f"(d[127])
    : "r"(a0), "r"(a1), "r"(a2), "r"(a3), "l"(db), "r"(sd), "n"(OB));
}
template <int OA, int OB> __device__ __forceinline__ void wgmma_ss_tb(float (&d)[96], uint64_t da, uint64_t db, int sd) {
  asm volatile("{\n.reg .pred p;\n.reg .b64 a, b;\nadd.s64 a, %96, %99;\nadd.s64 b, %97, %100;\nsetp.ne.b32 p, %98, 0;\n"
    "wgmma.mma_async.sync.aligned.m64n192k16.f32.bf16.bf16 {%0, %1, %2, %3, %4, %5, %6, %7, %8, %9, %10, %11, %12, %13, %14, %15, %16, %17, %18, %19, %20, %21, %22, %23, %24, %25, %26, %27, %28, %29, %30, %31, %32, %33, %34, %35, %36, %37, %38, %39, %40, %41, %42, %43, %44, %45, %46, %47, %48, %49, %50, %51, %52, %53, %54, %55, %56, %57, %58, %59, %60, %61, %62, %63, %64, %65, %66, %67, %68, %69, %70, %71, %72, %73, %74, %75, %76, %77, %78, %79, %80, %81, %82, %83, %84, %85, %86, %87, %88, %89, %90, %91, %92, %93, %94, %95}, a, b, p, 1, 1, 0, 1;\n}\n"
    : "+f"(d[0]), "+f"(d[1]), "+f"(d[2]), "+f"(d[3]), "+f"(d[4]), "+f"(d[5]), "+f"(d[6]), "+f"(d[7]), "+f"(d[8]), "+f"(d[9]), "+f"(d[10]), "+f"(d[11]), "+f"(d[12]), "+f"(d[13]), "+f"(d[14]), "+f"(d[15]), "+f"(d[16]), "+f"(d[17]), "+f"(d[18]), "+f"(d[19]), "+f"(d[20]), "+f"(d[21]), "+f"(d[22]), "+f"(d[23]), "+f"(d[24]), "+f"(d[25]), "+f"(d[26]), "+f"(d[27]), "+f"(d[28]), "+f"(d[29]), "+f"(d[30]), "+f"(d[31]), "+f"(d[32]), "+f"(d[33]), "+f"(d[34]), "+f"(d[35]), "+f"(d[36]), "+f"(d[37]), "+f"(d[38]), "+f"(d[39]), "+f"(d[40]), "+f"(d[41]), "+f"(d[42]), "+f"(d[43]), "+f"(d[44]), "+f"(d[45]), "+f"(d[46]), "+f"(d[47]), "+f"(d[48]), "+f"(d[49]), "+f"(d[50]), "+f"(d[51]), "+f"(d[52]), "+f"(d[53]), "+f"(d[54]), "+f"(d[55]), "+f"(d[56]), "+f"(d[57]), "+f"(d[58]), "+f"(d[59]), "+f"(d[60]), "+f"(d[61]), "+f"(d[62]), "+f"(d[63]), "+f"(d[64]), "+f"(d[65]), "+f"(d[66]), "+f"(d[67]), "+f"(d[68]), "+f"(d[69]), "+f"(d[70]), "+f"(d[71]), "+f"(d[72]), "+f"(d[73]), "+f"(d[74]), "+f"(d[75]), "+f"(d[76]), "+f"(d[77]), "+f"(d[78]), "+f"(d[79]), "+f"(d[80]), "+f"(d[81]), "+f"(d[82]), "+f"(d[83]), "+f"(d[84]), "+f"(d[85]), "+f"(d[86]), "+f"(d[87]), "+f"(d[88]), "+f"(d[89]), "+f"(d[90]), "+f"(d[91]), "+f"(d[92]), "+f"(d[93]), "+f"(d[94]), "+f"(d[95])
    : "l"(da), "l"(db), "r"(sd), "n"(OA), "n"(OB));
}
template <int OB> __device__ __forceinline__ void wgmma_rs_tb(float (&d)[96], uint32_t a0, uint32_t a1, uint32_t a2, uint32_t a3, uint64_t db, int sd) {
  asm volatile("{\n.reg .pred p;\n.reg .b64 b;\nadd.s64 b, %100, %102;\nsetp.ne.b32 p, %101, 0;\n"
    "wgmma.mma_async.sync.aligned.m64n192k16.f32.bf16.bf16 {%0, %1, %2, %3, %4, %5, %6, %7, %8, %9, %10, %11, %12, %13, %14, %15, %16, %17, %18, %19, %20, %21, %22, %23, %24, %25, %26, %27, %28, %29, %30, %31, %32, %33, %34, %35, %36, %37, %38, %39, %40, %41, %42, %43, %44, %45, %46, %47, %48, %49, %50, %51, %52, %53, %54, %55, %56, %57, %58, %59, %60, %61, %62, %63, %64, %65, %66, %67, %68, %69, %70, %71, %72, %73, %74, %75, %76, %77, %78, %79, %80, %81, %82, %83, %84, %85, %86, %87, %88, %89, %90, %91, %92, %93, %94, %95}, {%96, %97, %98, %99}, b, p, 1, 1, 1;\n}\n"
    : "+f"(d[0]), "+f"(d[1]), "+f"(d[2]), "+f"(d[3]), "+f"(d[4]), "+f"(d[5]), "+f"(d[6]), "+f"(d[7]), "+f"(d[8]), "+f"(d[9]), "+f"(d[10]), "+f"(d[11]), "+f"(d[12]), "+f"(d[13]), "+f"(d[14]), "+f"(d[15]), "+f"(d[16]), "+f"(d[17]), "+f"(d[18]), "+f"(d[19]), "+f"(d[20]), "+f"(d[21]), "+f"(d[22]), "+f"(d[23]), "+f"(d[24]), "+f"(d[25]), "+f"(d[26]), "+f"(d[27]), "+f"(d[28]), "+f"(d[29]), "+f"(d[30]), "+f"(d[31]), "+f"(d[32]), "+f"(d[33]), "+f"(d[34]), "+f"(d[35]), "+f"(d[36]), "+f"(d[37]), "+f"(d[38]), "+f"(d[39]), "+f"(d[40]), "+f"(d[41]), "+f"(d[42]), "+f"(d[43]), "+f"(d[44]), "+f"(d[45]), "+f"(d[46]), "+f"(d[47]), "+f"(d[48]), "+f"(d[49]), "+f"(d[50]), "+f"(d[51]), "+f"(d[52]), "+f"(d[53]), "+f"(d[54]), "+f"(d[55]), "+f"(d[56]), "+f"(d[57]), "+f"(d[58]), "+f"(d[59]), "+f"(d[60]), "+f"(d[61]), "+f"(d[62]), "+f"(d[63]), "+f"(d[64]), "+f"(d[65]), "+f"(d[66]), "+f"(d[67]), "+f"(d[68]), "+f"(d[69]), "+f"(d[70]), "+f"(d[71]), "+f"(d[72]), "+f"(d[73]), "+f"(d[74]), "+f"(d[75]), "+f"(d[76]), "+f"(d[77]), "+f"(d[78]), "+f"(d[79]), "+f"(d[80]), "+f"(d[81]), "+f"(d[82]), "+f"(d[83]), "+f"(d[84]), "+f"(d[85]), "+f"(d[86]), "+f"(d[87]), "+f"(d[88]), "+f"(d[89]), "+f"(d[90]), "+f"(d[91]), "+f"(d[92]), "+f"(d[93]), "+f"(d[94]), "+f"(d[95])
    : "r"(a0), "r"(a1), "r"(a2), "r"(a3), "l"(db), "r"(sd), "n"(OB));
}
template <int OA, int OB> __device__ __forceinline__ void wgmma_ss_tb(float (&d)[64], uint64_t da, uint64_t db, int sd) {
  asm volatile("{\n.reg .pred p;\n.reg .b64 a, b;\nadd.s64 a, %64, %67;\nadd.s64 b, %65, %68;\nsetp.ne.b32 p, %66, 0;\n"
    "wgmma.mma_async.sync.aligned.m64n128k16.f32.bf16.bf16 {%0, %1, %2, %3, %4, %5, %6, %7, %8, %9, %10, %11, %12, %13, %14, %15, %16, %17, %18, %19, %20, %21, %22, %23, %24, %25, %26, %27, %28, %29, %30, %31, %32, %33, %34, %35, %36, %37, %38, %39, %40, %41, %42, %43, %44, %45, %46, %47, %48, %49, %50, %51, %52, %53, %54, %55, %56, %57, %58, %59, %60, %61, %62, %63}, a, b, p, 1, 1, 0, 1;\n}\n"
    : "+f"(d[0]), "+f"(d[1]), "+f"(d[2]), "+f"(d[3]), "+f"(d[4]), "+f"(d[5]), "+f"(d[6]), "+f"(d[7]), "+f"(d[8]), "+f"(d[9]), "+f"(d[10]), "+f"(d[11]), "+f"(d[12]), "+f"(d[13]), "+f"(d[14]), "+f"(d[15]), "+f"(d[16]), "+f"(d[17]), "+f"(d[18]), "+f"(d[19]), "+f"(d[20]), "+f"(d[21]), "+f"(d[22]), "+f"(d[23]), "+f"(d[24]), "+f"(d[25]), "+f"(d[26]), "+f"(d[27]), "+f"(d[28]), "+f"(d[29]), "+f"(d[30]), "+f"(d[31]), "+f"(d[32]), "+f"(d[33]), "+f"(d[34]), "+f"(d[35]), "+f"(d[36]), "+f"(d[37]), "+f"(d[38]), "+f"(d[39]), "+f"(d[40]), "+f"(d[41]), "+f"(d[42]), "+f"(d[43]), "+f"(d[44]), "+f"(d[45]), "+f"(d[46]), "+f"(d[47]), "+f"(d[48]), "+f"(d[49]), "+f"(d[50]), "+f"(d[51]), "+f"(d[52]), "+f"(d[53]), "+f"(d[54]), "+f"(d[55]), "+f"(d[56]), "+f"(d[57]), "+f"(d[58]), "+f"(d[59]), "+f"(d[60]), "+f"(d[61]), "+f"(d[62]), "+f"(d[63])
    : "l"(da), "l"(db), "r"(sd), "n"(OA), "n"(OB));
}
template <int OB> __device__ __forceinline__ void wgmma_rs_tb(float (&d)[64], uint32_t a0, uint32_t a1, uint32_t a2, uint32_t a3, uint64_t db, int sd) {
  asm volatile("{\n.reg .pred p;\n.reg .b64 b;\nadd.s64 b, %68, %70;\nsetp.ne.b32 p, %69, 0;\n"
    "wgmma.mma_async.sync.aligned.m64n128k16.f32.bf16.bf16 {%0, %1, %2, %3, %4, %5, %6, %7, %8, %9, %10, %11, %12, %13, %14, %15, %16, %17, %18, %19, %20, %21, %22, %23, %24, %25, %26, %27, %28, %29, %30, %31, %32, %33, %34, %35, %36, %37, %38, %39, %40, %41, %42, %43, %44, %45, %46, %47, %48, %49, %50, %51, %52, %53, %54, %55, %56, %57, %58, %59, %60, %61, %62, %63}, {%64, %65, %66, %67}, b, p, 1, 1, 1;\n}\n"
    : "+f"(d[0]), "+f"(d[1]), "+f"(d[2]), "+f"(d[3]), "+f"(d[4]), "+f"(d[5]), "+f"(d[6]), "+f"(d[7]), "+f"(d[8]), "+f"(d[9]), "+f"(d[10]), "+f"(d[11]), "+f"(d[12]), "+f"(d[13]), "+f"(d[14]), "+f"(d[15]), "+f"(d[16]), "+f"(d[17]), "+f"(d[18]), "+f"(d[19]), "+f"(d[20]), "+f"(d[21]), "+f"(d[22]), "+f"(d[23]), "+f"(d[24]), "+f"(d[25]), "+f"(d[26]), "+f"(d[27]), "+f"(d[28]), "+f"(d[29]), "+f"(d[30]), "+f"(d[31]), "+f"(d[32]), "+f"(d[33]), "+f"(d[34]), "+f"(d[35]), "+f"(d[36]), "+f"(d[37]), "+f"(d[38]), "+f"(d[39]), "+f"(d[40]), "+f"(d[41]), "+f"(d[42]), "+f"(d[43]), "+f"(d[44]), "+f"(d[45]), "+f"(d[46]), "+f"(d[47]), "+f"(d[48]), "+f"(d[49]), "+f"(d[50]), "+f"(d[51]), "+f"(d[52]), "+f"(d[53]), "+f"(d[54]), "+f"(d[55]), "+f"(d[56]), "+f"(d[57]), "+f"(d[58]), "+f"(d[59]), "+f"(d[60]), "+f"(d[61]), "+f"(d[62]), "+f"(d[63])
    : "r"(a0), "r"(a1), "r"(a2), "r"(a3), "l"(db), "r"(sd), "n"(OB));
}
template <int OA, int OB> __device__ __forceinline__ void wgmma_ss_ta(float (&d)[64], uint64_t da, uint64_t db, int sd) {
  asm volatile("{\n.reg .pred p;\n.reg .b64 a, b;\nadd.s64 a, %64, %67;\nadd.s64 b, %65, %68;\nsetp.ne.b32 p, %66, 0;\n"
    "wgmma.mma_async.sync.aligned.m64n128k16.f32.bf16.bf16 {%0, %1, %2, %3, %4, %5, %6, %7, %8, %9, %10, %11, %12, %13, %14, %15, %16, %17, %18, %19, %20, %21, %22, %23, %24, %25, %26, %27, %28, %29, %30, %31, %32, %33, %34, %35, %36, %37, %38, %39, %40, %41, %42, %43, %44, %45, %46, %47, %48, %49, %50, %51, %52, %53, %54, %55, %56, %57, %58, %59, %60, %61, %62, %63}, a, b, p, 1, 1, 1, 0;\n}\n"
    : "+f"(d[0]), "+f"(d[1]), "+f"(d[2]), "+f"(d[3]), "+f"(d[4]), "+f"(d[5]), "+f"(d[6]), "+f"(d[7]), "+f"(d[8]), "+f"(d[9]), "+f"(d[10]), "+f"(d[11]), "+f"(d[12]), "+f"(d[13]), "+f"(d[14]), "+f"(d[15]), "+f"(d[16]), "+f"(d[17]), "+f"(d[18]), "+f"(d[19]), "+f"(d[20]), "+f"(d[21]), "+f"(d[22]), "+f"(d[23]), "+f"(d[24]), "+f"(d[25]), "+f"(d[26]), "+f"(d[27]), "+f"(d[28]), "+f"(d[29]), "+f"(d[30]), "+f"(d[31]), "+f"(d[32]), "+f"(d[33]), "+f"(d[34]), "+f"(d[35]), "+f"(d[36]), "+f"(d[37]), "+f"(d[38]), "+f"(d[39]), "+f"(d[40]), "+f"(d[41]), "+f"(d[42]), "+f"(d[43]), "+f"(d[44]), "+f"(d[45]), "+f"(d[46]), "+f"(d[47]), "+f"(d[48]), "+f"(d[49]), "+f"(d[50]), "+f"(d[51]), "+f"(d[52]), "+f"(d[53]), "+f"(d[54]), "+f"(d[55]), "+f"(d[56]), "+f"(d[57]), "+f"(d[58]), "+f"(d[59]), "+f"(d[60]), "+f"(d[61]), "+f"(d[62]), "+f"(d[63])
    : "l"(da), "l"(db), "r"(sd), "n"(OA), "n"(OB));
}
template <int OB> __device__ __forceinline__ void wgmma_rs(float (&d)[64], uint32_t a0, uint32_t a1, uint32_t a2, uint32_t a3, uint64_t db, int sd) {
  asm volatile("{\n.reg .pred p;\n.reg .b64 b;\nadd.s64 b, %68, %70;\nsetp.ne.b32 p, %69, 0;\n"
    "wgmma.mma_async.sync.aligned.m64n128k16.f32.bf16.bf16 {%0, %1, %2, %3, %4, %5, %6, %7, %8, %9, %10, %11, %12, %13, %14, %15, %16, %17, %18, %19, %20, %21, %22, %23, %24, %25, %26, %27, %28, %29, %30, %31, %32, %33, %34, %35, %36, %37, %38, %39, %40, %41, %42, %43, %44, %45, %46, %47, %48, %49, %50, %51, %52, %53, %54, %55, %56, %57, %58, %59, %60, %61, %62, %63}, {%64, %65, %66, %67}, b, p, 1, 1, 0;\n}\n"
    : "+f"(d[0]), "+f"(d[1]), "+f"(d[2]), "+f"(d[3]), "+f"(d[4]), "+f"(d[5]), "+f"(d[6]), "+f"(d[7]), "+f"(d[8]), "+f"(d[9]), "+f"(d[10]), "+f"(d[11]), "+f"(d[12]), "+f"(d[13]), "+f"(d[14]), "+f"(d[15]), "+f"(d[16]), "+f"(d[17]), "+f"(d[18]), "+f"(d[19]), "+f"(d[20]), "+f"(d[21]), "+f"(d[22]), "+f"(d[23]), "+f"(d[24]), "+f"(d[25]), "+f"(d[26]), "+f"(d[27]), "+f"(d[28]), "+f"(d[29]), "+f"(d[30]), "+f"(d[31]), "+f"(d[32]), "+f"(d[33]), "+f"(d[34]), "+f"(d[35]), "+f"(d[36]), "+f"(d[37]), "+f"(d[38]), "+f"(d[39]), "+f"(d[40]), "+f"(d[41]), "+f"(d[42]), "+f"(d[43]), "+f"(d[44]), "+f"(d[45]), "+f"(d[46]), "+f"(d[47]), "+f"(d[48]), "+f"(d[49]), "+f"(d[50]), "+f"(d[51]), "+f"(d[52]), "+f"(d[53]), "+f"(d[54]), "+f"(d[55]), "+f"(d[56]), "+f"(d[57]), "+f"(d[58]), "+f"(d[59]), "+f"(d[60]), "+f"(d[61]), "+f"(d[62]), "+f"(d[63])
    : "r"(a0), "r"(a1), "r"(a2), "r"(a3), "l"(db), "r"(sd), "n"(OB));
}
template <int OA, int OB> __device__ __forceinline__ void wgmma_ss_ta(float (&d)[4], uint64_t da, uint64_t db, int sd) {
  asm volatile("{\n.reg .pred p;\n.reg .b64 a, b;\nadd.s64 a, %4, %7;\nadd.s64 b, %5, %8;\nsetp.ne.b32 p, %6, 0;\n"
    "wgmma.mma_async.sync.aligned.m64n8k16.f32.bf16.bf16 {%0, %1, %2, %3}, a, b, p, 1, 1, 1, 0;\n}\n"
    : "+f"(d[0]), "+f"(d[1]), "+f"(d[2]), "+f"(d[3])
    : "l"(da), "l"(db), "r"(sd), "n"(OA), "n"(OB));
}

constexpr uint32_t U = 16384;
constexpr uint32_t SM_QO = 2 * U, SM_W = 8 * U, SM_V = 8 * U, SM_K1 = 12 * U, SM_BAR = 14 * U;
constexpr uint32_t B_WF = SM_BAR, B_KF = SM_BAR + 48, B_CF = SM_BAR + 80, B_GATE = SM_BAR + 128, B_OF = SM_BAR + 136, B_EP = SM_BAR + 144, B_EXT = SM_BAR + 152, B_Q3 = SM_BAR + 168,
                   B_WE = SM_BAR + 192, B_KE = SM_BAR + 240, B_CE = SM_BAR + 288, B_OS = SM_BAR + 344;
constexpr uint32_t SM_EP = SM_BAR + 384;
constexpr uint32_t SM_ONE = SM_BAR + 388;
constexpr uint32_t SM_STAT = SM_BAR + 400, SM_EXT = SM_STAT + 512;
constexpr uint32_t SM_BAD = SM_EXT + 2048;
constexpr int SMEM_BYTES = SM_BAR + 3072;
__device__ __forceinline__ uint32_t c_slot(int s) { return (0xBADC10u >> (4 * s)) & 15; }

struct Params {
  const __nv_bfloat16 *x, *k, *v, *wq, *wo, *wr;
  __nv_bfloat16* out;
  Scratch* g;
};

__device__ __forceinline__ void release2(uint32_t rbar, int lane) { if (lane < 2) mbar_arrive_cluster(rbar); }
__device__ __forceinline__ void pin_after(uint32_t a, float e0, float e1) {
  asm volatile("{\n.reg .pred p;\nsetp.lt.f32 p, %1, %2;\n@p st.shared.u32 [%0], %0;\n}\n" :: "r"(a), "f"(e0), "f"(-e1) : "memory"); }
__device__ __forceinline__ void lds128_after(uint32_t& x, uint32_t& y, uint32_t& z, uint32_t& w, uint32_t a, float e0, float e1) {
  asm volatile("{\n.reg .pred p;\nsetp.geu.f32 p, %5, %6;\n@p ld.shared.v4.u32 {%0,%1,%2,%3}, [%4];\n}\n" : "+r"(x), "+r"(y), "+r"(z), "+r"(w) : "r"(a), "f"(e0), "f"(-e1) : "memory"); }
__device__ __forceinline__ uint32_t launch_of(unsigned long long ticket) { return (uint32_t)(ticket / 132) + 1; }

__device__ __forceinline__ void attn_slow(float (&o)[64], float& i0, float& i1, const __nv_bfloat16* __restrict__ X, const __nv_bfloat16* __restrict__ WQ, uint32_t st0, uint32_t st1,
                                          const __nv_bfloat16* __restrict__ K, const __nv_bfloat16* __restrict__ V, int lane) {
  uint32_t q[32];
  #pragma unroll
  for (int i = 0; i < 64; i++) o[i] = 0.f;
  const int g = lane >> 2, qd = lane & 3;
  #pragma unroll 1
  for (int k0 = 0; k0 < DM; k0 += 16) {
    uint32_t a[4];
    #pragma unroll
    for (int e = 0; e < 4; e++) {
      const uint32_t xv = *(const uint32_t*)(X + (size_t)(g + (e & 1) * 8) * DM + k0 + (e >> 1) * 8 + 2 * qd);
      const float mb = bf_lo((e & 1) ? st1 : st0);
      a[e] = pack_bf16(bf_lo(xv) - mb, bf_hi(xv) - mb);
    }
    const unsigned short* wr = (const unsigned short*)(WQ + (size_t)(k0 + 2 * qd) * (NH * DH) + g);
    #pragma unroll
    for (int nb = 0; nb < 16; nb++) {
      uint32_t b0 = (uint32_t)wr[nb * 8] | ((uint32_t)wr[nb * 8 + NH * DH] << 16);
      uint32_t b1 = (uint32_t)wr[nb * 8 + 8 * NH * DH] | ((uint32_t)wr[nb * 8 + 9 * NH * DH] << 16);
      asm volatile("mma.sync.aligned.m16n8k16.row.col.f32.bf16.bf16.f32 {%0,%1,%2,%3}, {%4,%5,%6,%7}, {%8,%9}, {%0,%1,%2,%3};"
        : "+f"(o[nb*4]), "+f"(o[nb*4+1]), "+f"(o[nb*4+2]), "+f"(o[nb*4+3]) : "r"(a[0]), "r"(a[1]), "r"(a[2]), "r"(a[3]), "r"(b0), "r"(b1));
    }
  }
  {
    const float r0 = rcp_approx(bf_hi(st0)) * SCALE_LOG2E, r1 = rcp_approx(bf_hi(st1)) * SCALE_LOG2E;
    #pragma unroll
    for (int i = 0; i < 16; i++) { q[2*i] = pack_bf16(o[4*i] * r0, o[4*i+1] * r0); q[2*i+1] = pack_bf16(o[4*i+2] * r1, o[4*i+3] * r1); }
    #pragma unroll
    for (int i = 0; i < 64; i++) o[i] = 0.f;
  }
  float m0 = -INFINITY, m1 = -INFINITY, l0 = 0.f, l1 = 0.f;
  #pragma unroll 1
  for (int n0 = 0; n0 < S_LEN; n0 += 16) {
    float s[8];
    #pragma unroll
    for (int i = 0; i < 8; i++) s[i] = 0.f;
    #pragma unroll
    for (int nb = 0; nb < 2; nb++) {
      const uint32_t* kr = (const uint32_t*)(K + (size_t)(n0 + nb * 8 + g) * DH) + qd;
      #pragma unroll
      for (int kk = 0; kk < 8; kk++) {
        uint32_t b0 = kr[kk * 8], b1 = kr[kk * 8 + 4];
        asm volatile("mma.sync.aligned.m16n8k16.row.col.f32.bf16.bf16.f32 {%0,%1,%2,%3}, {%4,%5,%6,%7}, {%8,%9}, {%0,%1,%2,%3};"
          : "+f"(s[nb*4]), "+f"(s[nb*4+1]), "+f"(s[nb*4+2]), "+f"(s[nb*4+3]) : "r"(q[kk*4]), "r"(q[kk*4+1]), "r"(q[kk*4+2]), "r"(q[kk*4+3]), "r"(b0), "r"(b1));
      }
    }
    float x0 = fmaxf(fmaxf(s[0], s[1]), fmaxf(s[4], s[5])), x1 = fmaxf(fmaxf(s[2], s[3]), fmaxf(s[6], s[7]));
    x0 = fmaxf(x0, __shfl_xor_sync(0xffffffff, x0, 1)); x1 = fmaxf(x1, __shfl_xor_sync(0xffffffff, x1, 1));
    x0 = fmaxf(x0, __shfl_xor_sync(0xffffffff, x0, 2)); x1 = fmaxf(x1, __shfl_xor_sync(0xffffffff, x1, 2));
    const float n0m = fmaxf(m0, x0), n1m = fmaxf(m1, x1);
    const float sh0 = (n0m == -INFINITY) ? 0.f : n0m, sh1 = (n1m == -INFINITY) ? 0.f : n1m;
    const float c0 = ex2(m0 - sh0), c1 = ex2(m1 - sh1);
    m0 = n0m; m1 = n1m;
    s[0] = ex2(s[0] - sh0); s[1] = ex2(s[1] - sh0); s[4] = ex2(s[4] - sh0); s[5] = ex2(s[5] - sh0);
    s[2] = ex2(s[2] - sh1); s[3] = ex2(s[3] - sh1); s[6] = ex2(s[6] - sh1); s[7] = ex2(s[7] - sh1);
    l0 = l0 * c0 + (s[0] + s[1]) + (s[4] + s[5]); l1 = l1 * c1 + (s[2] + s[3]) + (s[6] + s[7]);
    const uint32_t a0 = pack_bf16(s[0], s[1]), a1 = pack_bf16(s[2], s[3]), a2 = pack_bf16(s[4], s[5]), a3 = pack_bf16(s[6], s[7]);
    const unsigned short* vr = (const unsigned short*)(V + (size_t)(n0 + 2 * qd) * DH + g);
    #pragma unroll
    for (int nb = 0; nb < 16; nb++) {
      uint32_t b0 = (uint32_t)vr[nb * 8] | ((uint32_t)vr[nb * 8 + DH] << 16);
      uint32_t b1 = (uint32_t)vr[nb * 8 + 8 * DH] | ((uint32_t)vr[nb * 8 + 9 * DH] << 16);
      o[nb*4] *= c0; o[nb*4+1] *= c0; o[nb*4+2] *= c1; o[nb*4+3] *= c1;
      asm volatile("mma.sync.aligned.m16n8k16.row.col.f32.bf16.bf16.f32 {%0,%1,%2,%3}, {%4,%5,%6,%7}, {%8,%9}, {%0,%1,%2,%3};"
        : "+f"(o[nb*4]), "+f"(o[nb*4+1]), "+f"(o[nb*4+2]), "+f"(o[nb*4+3]) : "r"(a0), "r"(a1), "r"(a2), "r"(a3), "r"(b0), "r"(b1));
    }
  }
  l0 += __shfl_xor_sync(0xffffffff, l0, 1); l1 += __shfl_xor_sync(0xffffffff, l1, 1);
  l0 += __shfl_xor_sync(0xffffffff, l0, 2); l1 += __shfl_xor_sync(0xffffffff, l1, 2);
  i0 = rcp_approx(l0); i1 = rcp_approx(l1);
}

__device__ __forceinline__ void flag_if(uint32_t a, bool c) { asm volatile("{\n.reg .pred p;\nsetp.ne.u32 p, %1, 0;\n@p st.shared.u8 [%0], 1;\n}\n" :: "r"(a), "r"((uint32_t)c) : "memory"); }
__device__ __forceinline__ void row_scale(float& l0, float& l1, int one, uint32_t flag) {
  l0 += __shfl_xor_sync(0xffffffff, l0, one); l1 += __shfl_xor_sync(0xffffffff, l1, one);
  l0 += __shfl_xor_sync(0xffffffff, l0, 2); l1 += __shfl_xor_sync(0xffffffff, l1, 2);
  flag_if(flag, !((l0 >= 0.00390625f) && (l0 <= 1.8446744e19f) && (l1 >= 0.00390625f) && (l1 <= 1.8446744e19f)));
  l0 = rcp_fast(l0); l1 = rcp_fast(l1);
}
__device__ __forceinline__ uint32_t taint(uint32_t z, uint32_t a, uint32_t b) { asm("fma.rn.bf16x2 %0, %1, %2, %0;" : "+r"(z) : "r"(a), "r"(b)); return z; }
__device__ __forceinline__ bool tainted(uint32_t z) { return (taint(0u, z, 0u) & 0x7fff7fffu) != 0; }

__device__ __forceinline__ uint32_t qo_slot(int h) { return SM_QO + ((0x3102 >> (4 * h)) & 3) * 2 * U; }
__device__ __forceinline__ uint32_t o_addr(uint32_t wr, int lane) { return wr + (lane & 15) * 128 + (((lane >> 4) ^ (lane & 7)) << 4); }
template <bool CHECK> __device__ __forceinline__ uint32_t store_o(uint32_t a, const float (&o)[64], float i0, float i1) {
  uint32_t z = 0;
  #pragma unroll
  for (int i = 0; i < 8; i++) {
    const uint32_t w0 = pack_bf16(o[8*i] * i0, o[8*i+1] * i0), w1 = pack_bf16(o[8*i+2] * i1, o[8*i+3] * i1), w2 = pack_bf16(o[8*i+4] * i0, o[8*i+5] * i0), w3 = pack_bf16(o[8*i+6] * i1, o[8*i+7] * i1);
    stsm4((a ^ ((i & 3) << 5)) + (i >> 2) * U, w0, w1, w2, w3);
    if (CHECK) z = taint(taint(z, w0, w1), w2, w3);
  }
  return z;
}

__device__ __noinline__ void redo_heads(const Params& P, uint32_t sb, uint32_t bad, int row0, int head0) {
  const int lane = threadIdx.x & 31;
  const uint32_t st0 = lds32(sb + SM_STAT + ((row0 & 127) + (lane >> 2)) * 4), st1 = lds32(sb + SM_STAT + ((row0 & 127) + 8 + (lane >> 2)) * 4);
  #pragma unroll 1
  for (int h = 0; h < 4; h++) {
    if (!((bad >> (8 * h)) & 1)) continue;
    float o[64], i0, i1;
    attn_slow(o, i0, i1, P.x + (size_t)row0 * DM, P.wq + (head0 + h) * DH, st0, st1, P.k + (size_t)(head0 + h) * S_LEN * DH, P.v + (size_t)(head0 + h) * S_LEN * DH, lane);
    store_o<false>(o_addr(sb + (row0 & 127) * 128, lane) + qo_slot(h), o, i0, i1);
  }
}

template <int K> struct IC { static constexpr int v = K; };
template <int K, int N, class F> __device__ __forceinline__ void static_for(F&& f) { if constexpr (K < N) { f(IC<K>{}); static_for<K + 1, N>(f); } }
template <uint32_t OFF, int SITE> __device__ __forceinline__ void mma_qk(float (&s)[64], const uint32_t (&q)[32], uint64_t d0) {
  wg_fence();
  static_for<0, 8>([&](auto kc) { constexpr int k = decltype(kc)::v; wgmma_rs<doff(OFF, 16) - SITE + (k / 4) * 1024 + (k % 4) * 2>(s, q[k*4], q[k*4+1], q[k*4+2], q[k*4+3], d0, k > 0); });
  wg_commit();
}
template <uint32_t OFF, int SITE> __device__ __forceinline__ void mma_pv(float (&o)[64], const uint32_t (&p)[32], uint64_t d0, bool keep) {
  wg_fence();
  static_for<0, 8>([&](auto kc) { constexpr int k = decltype(kc)::v; wgmma_rs_tb<doff(OFF, U) - SITE + k * 128>(o, p[k*4], p[k*4+1], p[k*4+2], p[k*4+3], d0, (k > 0) || keep); });
  wg_commit();
}
template <int I0, int I1>
__device__ __forceinline__ void exp_rows(float (&s)[64], float (&l)[2]) {
  #pragma unroll
  for (int i = I0; i < I1; i += 2) {
    s[i] = ex2(s[i]); s[i+1] = ex2(s[i+1]);
    if (SMV) l[(i >> 1) & 1] += s[i] + s[i+1]; else { l[(i >> 1) & 1] += s[i]; l[(i >> 1) & 1] += s[i+1]; }
  }
}

template <int KS, bool EDGE>
__device__ __forceinline__ void attn_step(uint32_t sb, uint32_t rb, uint32_t wr, uint32_t qa, int wg, int lane, int j, int ph, float (&s)[64], float (&o)[64], uint32_t (&p)[32], uint32_t (&q)[32],
                                          float (&l)[2], bool& ready, Scratch* g, unsigned (&tz)[3]) {
  constexpr bool FIRST = EDGE && !KS, LAST = EDGE && KS;
  TRACEF(2, wg, 32 + j);
  if (!ETEST || !ready) {
    mbar_wait(sb + B_KF + 24 - KS * 8, KS ? ph : ph ^ 1);
    mbar_wait(sb + B_KF + KS * 8, ph);
  }
  bar_sync(1 + wg, 256);
  mma_qk<KS * SM_K1, EDGE>(s, q, desc(sb, EDGE));
  mma_pv<SM_V + (1 - KS) * 2 * U, EDGE>(o, p, desc(sb, EDGE), !KS || LAST || ((j & 15) != 1));
  bar_arrive(1 + (wg ^ 1), 256);
  const int one = FIRST ? lds32(sb + SM_ONE) : 1;
  wg_wait<1>();
  fence_regs(s);
  release2(rb + B_KE + KS * 8, lane);
  float i0 = l[0], i1 = l[1];
  if (FIRST) { row_scale(i0, i1, one, sb + SM_BAD - 1 + ((wr - sb) >> 9) + (j >> 4)); l[0] = fminf(i0, 0.f); l[1] = fminf(i1, 0.f); }
  constexpr int DP = FIRST ? DPOSF : (LAST && DPOS < 7 * QSP ? 7 * QSP : DPOS);
  if (LAST) {
    fence_regs(q);
    const uint32_t a = qa + qo_slot(j >> 4);
    static_for<0, 8>([&](auto ic) { constexpr int i = decltype(ic)::v;
      lds128_after(q[4*i], q[4*i+1], q[4*i+2], q[4*i+3], a + (i >> 2) * U + (i & 3) * 512, l[0], l[1]);
      exp_rows<i * QSP, i < 7 ? (i + 1) * QSP : DP>(s, l);
    });
  } else exp_rows<0, DP>(s, l);
  pin_after(sb + SM_BAD, l[0], l[1]);
  exp_rows<DP, 64>(s, l);
  wg_wait<0>();
  fence_regs(o); fence_regs(p);
  release2(rb + B_KE + 24 - KS * 8, lane);
  if (ETEST) ready = mbar_test2(sb + B_KF + 16 + KS * 8, ph, sb + B_KF + 8 - KS * 8, KS ? ph ^ 1 : ph);
  if (FIRST) {
    const int h = (j >> 4) - 1;
    store_o<false>(o_addr(wr, lane) + qo_slot(h), o, i0, i1);
    if (lane == 0) mbar_arrive(sb + B_OS + h * 8);
  }
  #pragma unroll
  for (int i = 0; i < 32; i++) p[i] = pack_bf16(s[2*i], s[2*i+1]);
}

template <int SITE> __device__ __forceinline__ void mma_c(float (&acc)[64], uint32_t sb, int slot, int h, int arrive_bar) {
  const uint64_t a = desc(sb, c_slot(slot) * 1024 + SITE), b = desc(sb, h * 2048 + SITE);
  wg_fence();
  static_for<0, 8>([&](auto kc) { constexpr int k = decltype(kc)::v;
    if (k == C_EARLY && arrive_bar) bar_arrive(arrive_bar, 256);
    wgmma_ss_ta<doff(0, 16) - SITE + k * 128, doff(SM_QO, 16) - SITE + (k >> 2) * 1024 + (k & 3) * 2>(acc, a, b, k > 0 || h > 0);
  });
  wg_commit();
}

__device__ __forceinline__ void side_cta(const Params& P, const CUtensorMap* tmX, const CUtensorMap* tmW, const CUtensorMap* tmG, const CUtensorMap* tmU,
                                         const CUtensorMap* tmD, uint32_t sb, int m) {
  const int tid = threadIdx.x, warp = __shfl_sync(0xffffffff, tid >> 5, 0), lane = tid & 31;
  const uint32_t XS = sb + 12 * U, HS = XS + 10240, BF = sb + SM_BAR, BE = BF + 96, XF = BE + 96, XE = XF + 32, BW = XE + 32, SEL = BW + 16, KEY = SEL + 64;
  Scratch* const g = P.g;
  const int nj = m < 3 ? 14 : 12, nd = m < 3 ? 4 : 3, f0 = m * 448;
  if (elect_one()) { mbar_init(BF + warp * 8, 1); mbar_init(BE + warp * 8, 4); if (warp < 9) mbar_init(XF + warp * 8, (warp & 4) ? 8 : 1); }
  if (tid == 32) sts32(SEL + 32, launch_of(atomicAdd(&g->ticket, 1ull)));
  __syncthreads();
  const uint32_t launch = lds32(SEL + 32);
  if (warp == 0) {
    if (elect_one()) {
      mbar_expect_tx(BW, 10 * U);
      #pragma unroll 1
      for (int i = 0; i < 10; i++) tma_load_2d(sb + i * U, tmW, BW, m * 1024 + (i < 5 ? 448 : 960), (i < 5 ? i : i - 5) * 128);
    }
    #pragma unroll 1
    for (int n = 0, qt = 0, c = 0; n < 160; n++) {
      const uint32_t bar = XF + (n & 3) * 8;
      mbar_wait(bar + 32, ((n >> 2) & 1) ^ 1);
      if (elect_one()) {
        mbar_expect_tx(bar, U);
        tma_load_2d(sb + (10 + (n & 3)) * U, tmX, bar, c * 64, qt * 128);
        if (c == 0 && qt < 15) l2_prefetch(P.x + (size_t)(qt * 128 + 128 + m * 32) * DM, 32 * DM * 2);
      }
      if (++c == 10) { c = 0; qt++; }
    }
  } else if (warp == 1) {
    #pragma unroll 1
    for (int qt = 0; qt < 16; qt++) {
      bar_sync(2 + (qt & 1), 288);
      if (lane == 0) asm volatile("fence.acq_rel.gpu;\nst.relaxed.gpu.global.u32 [%0], %1;" :: "l"(&g->q3_done[m].v), "r"(launch * 16 + qt + 1) : "memory");
    }
  } else if (warp >= 4) {
    float acc[64], cs[32];
    mbar_wait(BW, 0);
    #pragma unroll 1
    for (int c = 0; c < 10; c++) {
      wg_fence();
      static_for<0, 4>([&](auto kc) { constexpr int k = decltype(kc)::v;
        wgmma_rs_tb<doff(0, 5 * U) + k * 128>(acc, 0x3f803f80u, 0x3f803f80u, 0x3f803f80u, 0x3f803f80u, desc(sb, c * 512), k || c); });
      wg_commit();
      wg_wait<0>();
    }
    fence_regs(acc);
    #pragma unroll
    for (int i = 0; i < 32; i++) cs[i] = -acc[(i >> 1) * 4 + (i & 1)];
    fence_regs(cs);
    #pragma unroll 1
    for (int qt = 0, n = 0; qt < 16; qt++) {
      const uint32_t* const sp = g->stat + qt * 128 + (warp - 4) * 16 + (lane >> 2);
      uint32_t st0, st1;
      #pragma unroll 1
      for (int c = 0; c < 10; c++, n++) {
        const uint64_t a = desc(sb, (n & 3) * 1024 + (warp >> 3) * 512), b = desc(sb, c * 512);
        mbar_wait(XF + (n & 3) * 8, (n >> 2) & 1);
        wg_fence();
        static_for<0, 4>([&](auto kc) { constexpr int k = decltype(kc)::v; wgmma_ss_tb<doff(10 * U, 16) + k * 2, doff(0, 5 * U) + k * 128>(acc, a, b, k || c); });
        wg_commit();
        if (c == 9) { st0 = ldg32(sp); st1 = ldg32(sp + 8); }
        wg_wait<1>();
        if (c && lane == 0) mbar_arrive(XE + ((n - 1) & 3) * 8);
      }
      #pragma unroll 1
      for (int it = 0; __any_sync(0xffffffff, tag_miss(st0, st1, launch << 31) >> 31) && it < MAXPOLL; it++) { st0 = ldg32(sp); st1 = ldg32(sp + 8); }
      st0 &= 0x7fffffffu; st1 &= 0x7fffffffu;
      const float rs[2] = {rcp_approx(bf_hi(st0)) * SCALE_LOG2E, rcp_approx(bf_hi(st1)) * SCALE_LOG2E}, nm[2] = {bf_lo(st0), bf_lo(st1)};
      wg_wait<0>();
      fence_regs(acc);
      if (lane == 0) mbar_arrive(XE + ((n - 1) & 3) * 8);
      uint4* const dst = g->q3 + (qt * 8 + m * 2) * 1024 + (warp - 4) * 128 + lane;
      #pragma unroll
      for (int e = 0; e < 8; e++) {
        uint32_t w[4];
        #pragma unroll
        for (int i = 0; i < 4; i++)
          w[i] = pack_bf16(fmaf(nm[i & 1], cs[4*e + (i & 2)], acc[8*e + 2*i]) * rs[i & 1], fmaf(nm[i & 1], cs[4*e + (i & 2) + 1], acc[8*e + 2*i + 1]) * rs[i & 1]);
        dst[(e >> 2) * 1024 + (e & 3) * 32] = make_uint4(w[0], w[1], w[2], w[3]);
      }
      bar_arrive(2 + (qt & 1), 288);
    }
  }
  if (tid == 64) flag_wait(&g->cnt_gate.v, launch * 256);
  __syncthreads();
  TRACE(0, 1);
  if (tid >= 256 && tid < 320) sts128(HS + 3072 + tid * 16, 0, 0, 0, 0);
  if (warp < 4) {
    uint4 k4[4];
    #pragma unroll
    for (int i = 0; i < 4; i++) k4[i] = ld_relaxed4(g->key + warp * 512 + i * 128 + lane * 4);
    uint32_t bound = 0;
    #pragma unroll 1
    for (int c = 0; c < TOPC; c++) {
      uint32_t b = 0;
      #pragma unroll
      for (int i = 0; i < 4; i++) b = max(max(max(b, k4[i].x - bound), k4[i].y - bound), max(k4[i].z - bound, k4[i].w - bound));
      bound += __reduce_max_sync(0xffffffff, b);
      if (lane == 0) sts32(KEY + (warp * TOPC + c) * 4, bound);
    }
    bar_sync(1, 128);
    const uint32_t v = lds32(KEY + lane * 4);
    int n = 0;
    #pragma unroll 1
    for (int j = 0; j < 32; j++) n += __shfl_sync(0xffffffff, v, j) > v;
    if (n < TOPC) sts32(SEL + n * 4, v);
  }
  __syncthreads();
  #pragma unroll 1
  for (int i = tid; i < TOPC * 80; i += 384) {
    const int row = 0xffff - (lds32(SEL + (i & 7) * 4) & 0xffff);
    const uint32_t st = ldg32(g->stat + row), m2 = __byte_perm(st, 0, 0x1010);
    const float rsd = rcp_approx(bf_hi(st & 0x7fffffffu));
    const uint4 v = ldg_nc((const uint4*)(P.x + (size_t)row * DM) + (i >> 3));
    sts128(XS + i * 16, norm2(v.x, m2, rsd), norm2(v.y, m2, rsd), norm2(v.z, m2, rsd), norm2(v.w, m2, rsd));
  }
  proxy_fence();
  __syncthreads();
  TRACE(0, 2);
  uint32_t sl = 0, ph = 0;
  if (warp == 0) {
    #pragma unroll 1
    for (int job = 0; job < nj + 10; job++) {
      const bool up = job < nj;
      #pragma unroll 1
      for (int i = 0; i < (up ? 5 : nd); i++) {
        mbar_wait(BE + sl * 8, ph ^ 1);
        if (elect_one()) {
          mbar_expect_tx(BF + sl * 8, U);
          tma_load_2d(sb + sl * U, up ? ((job & 1) ? tmU : tmG) : tmD, BF + sl * 8, up ? f0 + (job >> 1) * 64 : (job - nj) * 64, (up ? 0 : f0) + i * 128);
        }
        if (++sl == 12) { sl = 0; ph ^= 1; }
      }
    }
  } else if ((warp >> 2) == 1) {
    float gs[4];
    #pragma unroll 1
    for (int job = 0; job < nj + 10; job++) {
      const bool up = job < nj;
      if (job == nj) { proxy_fence(); bar_sync(1, 128); }
      float ac[4][4], acc[4];
      uint32_t prev = 0;
      #pragma unroll 1
      for (int i = 0; i < (up ? 5 : nd); i++) {
        const uint64_t a = desc(sb, sl * 1024 + 0x10000), b = (uint64_t)(desc_lo(up ? XS : HS, 128) + i * 128) | (8ull << 32);
        mbar_wait(BF + sl * 8, ph);
        wg_fence();
        static_for<0, 8>([&](auto kc) { constexpr int k = decltype(kc)::v; wgmma_ss_ta<k * 128, k * 16>(ac[k & 3], a, b, k > 3 || i > 0); });
        wg_commit();
        wg_wait<1>();
        if (i && lane == 0) mbar_arrive(prev);
        prev = BE + sl * 8;
        if (++sl == 12) { sl = 0; ph ^= 1; }
      }
      wg_wait<0>();
      if (lane == 0) mbar_arrive(prev);
      #pragma unroll
      for (int e = 0; e < 4; e++) fence_regs(ac[e]);
      #pragma unroll
      for (int e = 0; e < 4; e++) acc[e] = (ac[0][e] + ac[1][e]) + (ac[2][e] + ac[3][e]);
      const int f = (warp & 3) * 16 + (lane >> 2), tk = (lane & 3) * 2;
      if (!up) {
        float* y = g->ypart + (m * DM + (job - nj) * 64 + f) * TOPC + tk;
        *(float2*)y = make_float2(acc[0], acc[1]); *(float2*)(y + 8 * TOPC) = make_float2(acc[2], acc[3]);
      } else {
        #pragma unroll
        for (int e = 0; e < 4; e++) {
          const float z = rbf(acc[e]);
          if (job & 1) asm volatile("st.shared.u16 [%0], %1;" :: "r"(HS + (job >> 1) * 1024 + ((f >> 3) + (e >> 1)) * 128 + (tk + (e & 1)) * 16 + (f & 7) * 2), "h"((uint16_t)pack_bf16(gs[e] * z, 0.f)) : "memory");
          gs[e] = rbf(z * sigmoid_f(z));
        }
      }
    }
  }
  __syncthreads();
  TRACE(0, 3);
  if (tid == 0) { flag_add_release(&g->cnt_mod.v); flag_wait(&g->cnt_mod.v, launch * 4, 50); }
  __syncthreads();
  #pragma unroll 1
  for (int i = tid; i < 2 * DM; i += 384) {
    const int t = 2 * m + (i & 1), col = i >> 1;
    const uint32_t key = lds32(SEL + t * 4);
    const float* yp = g->ypart + col * TOPC + t;
    const float y = rbf((__ldcg(yp) + __ldcg(yp + TOPC * DM)) + (__ldcg(yp + 2 * TOPC * DM) + __ldcg(yp + 3 * TOPC * DM)));
    const float rs = rbf(sigmoid_f(bf_hi((key >> 31) ? key & 0x7fffffffu : ~key)));
    const uint32_t xn = lds32(XS + (col >> 3) * 128 + t * 16 + (col & 6) * 2);
    const float z = rbf(((col & 1) ? bf_hi(xn) : bf_lo(xn)) + rbf(y * rs));
    g->gate[(size_t)(0xffff - (key & 0xffff)) * DM + col] = __float2bfloat16_rn(z * sigmoid_f(z));
  }
  __syncthreads();
  if (tid == 0) flag_add_release(&g->mod_done.v);
  TRACE(0, 4);
}

__global__ void __cluster_dims__(2, 1, 1) __launch_bounds__(384, 1) fused_kernel(const __grid_constant__ CUtensorMap tmX, const __grid_constant__ CUtensorMap tmW4,
    const __grid_constant__ CUtensorMap tmW3, const __grid_constant__ CUtensorMap tmW1,
    const __grid_constant__ CUtensorMap tmK, const __grid_constant__ CUtensorMap tmV, const __grid_constant__ CUtensorMap tmWO,
    const __grid_constant__ CUtensorMap tmG, const __grid_constant__ CUtensorMap tmU, const __grid_constant__ CUtensorMap tmD,
    const __grid_constant__ CUtensorMap tmGate, const __grid_constant__ Params P) {
  extern __shared__ __align__(1024) uint8_t smem_raw[];
  const uint32_t sb = smem_u32(smem_raw);
  const int tid = threadIdx.x, lane = tid & 31;
  const int rank = blockIdx.x & 1, cl = blockIdx.x >> 1;
  if (cl >= 64) {
    side_cta(P, &tmX, &tmW1, &tmG, &tmU, &tmD, sb, blockIdx.x & 3);
    return;
  }
  const int rr = ((cl - 36) * 37) >> 8, qp = sel_lt(cl, 4, 0, sel_lt(cl, 36, (cl - 4) & 7, cl - 35 - rr * 7));
  const int hg = sel_lt(cl, 4, cl, sel_lt(cl, 36, ((cl - 4) >> 3) + sel_lt(qp, 1, 4, 0), 4 + rr)), qt = qp * 2 + rank;
  const int warp = __shfl_sync(0xffffffff, tid >> 5, 0), wgi = warp >> 2;
  Scratch* const g = P.g;
  if (elect_one()) {
    #pragma unroll
    for (int i = 0; i < 4; i++) mbar_init(sb + SM_BAR + warp * 32 + i * 8, 1 << ((0x333444000000ull >> (4 * warp)) & 7));
    if (warp == 0) {
      mbar_expect_tx(sb + B_WF, 2 * U);
      tma_load_2d(sb + 2 * U, &tmX, sb + B_WF, 0, qt * 128);
      if (W0E) { tma_load_3d(sb + SM_W, &tmW4, sb + B_WF, 0, 0, hg * 8); tma_load_3d(sb + SM_W + 8192, &tmW4, sb + B_WF, 0, 16, hg * 8); }
    }
    if (warp == 1 && !W0E) asm volatile("prefetch.tensormap [%0];" :: "l"(&tmW4) : "memory");
    asm volatile("fence.mbarrier_init.release.cluster;" ::: "memory");
  }
  __syncwarp();
  cluster_arrive();
  unsigned long long ticket = 0;
  if (tid == 64) asm volatile("atom.relaxed.gpu.global.add.u64 %0, [%1], 1;" : "=l"(ticket) : "l"(&g->ticket) : "memory");
  cluster_wait();
  if (warp == 0 && elect_one()) {
    #pragma unroll
    for (int i = W0E; i < 6; i++) {
      if (i) mbar_expect_tx(sb + B_WF + i * 8, (i & 1) ? U : 2 * U);
      tma_load_3d_mc(sb + SM_W + i * U + rank * 8192, &tmW4, sb + B_WF + i * 8, 0, i * 32 + rank * 16, hg * 8);
      if (i && !(i & 1)) tma_load_2d(sb + (2 + i / 2) * U, &tmX, sb + B_WF + i * 8, i * 32, qt * 128);
    }
  }
  if (wgi == 0) {
    asm volatile("setmaxnreg.dec.sync.aligned.u32 56;");
    uint32_t w0 = 0;
    if (warp == 1 || warp == 2) {
      if (warp == 2 && lane < 12) sts128(sb + SM_EXT + 1024 + (lane >= 6 ? 1024 - 96 : 0) + lane * 16, 0, 0, 0, 0);
      __syncwarp();
      if (tid == 64) { sts32(sb + SM_ONE, 1); sts32(sb + SM_EP, launch_of(ticket)); mbar_arrive(sb + B_EP); }
      __syncwarp();
      mbar_wait(sb + B_WF, 0);
      TRACEO(1);
      auto warm = [&](int ps, int i0, int i1) {
        const uint32_t o = (((qt >> 2) * 4 + (lane & 3) + (lane >> 2) * 16) * (NH * DH) + hg * 512 + ps * 256 + (qt & 3) * 64) * 2;
        #pragma unroll 1
        for (int i = i0; i < i1; i++) {
          asm volatile("prefetch.global.L2 [%0];" :: "l"(at<char>(P.wq, o + i * 256 * (NH * DH))) : "memory");
          if (ps) __nanosleep(W1SL);
        }
      };
      if (XPF && elect_one()) l2_prefetch(P.x + (size_t)(qt * 128 + hg * 16 + warp * 8 - 6) * DM, 6 * DM * 2);
      if (warp == 1) warm(0, 1, 5);
      auto publish = [&](uint32_t w) { if (!(lane & 12)) st_relaxed(at<uint32_t>(g->stat, (qt * 128 + hg * 16 + (warp - 1) * 8 + (lane & 3) * 2 + (lane >> 4)) * 4), w ^ (lds32(sb + SM_EP) << 31)); };
      mbar_wait(sb + B_EP, 0);
      publish(0x80000000u);
      const int r0 = qt * 128 + hg * 16 + (warp - 1) * 8 + (lane >> 4);
      const uint32_t e = r0 * DM * 2 + (lane & 15) * 16;
      uint4 vn[5];
      #pragma unroll
      for (int i = 0; i < 5; i++) vn[i] = ldg_nc(at<uint4>(P.x, e) + i * 16);
      #pragma unroll 1
      for (int it = 0; it < 4; it++) {
        uint4 v[5];
        #pragma unroll
        for (int i = 0; i < 5; i++) { v[i] = vn[i]; if (it < 3) vn[i] = ldg_nc(at<uint4>(P.x, e + (it + 1) * 2560) + i * 16); }
        const float x0 = bf_lo(__shfl_sync(0xffffffff, v[0].x, lane & 16));
        float m1 = 0.f, s1 = 0.f;
        #pragma unroll
        for (int i = 0; i < 5; i++) {
          const uint32_t vw[4] = {v[i].x, v[i].y, v[i].z, v[i].w};
          #pragma unroll
          for (int k = 0; k < 4; k++) { const float d0 = bf_lo(vw[k]) - x0, d1 = bf_hi(vw[k]) - x0; m1 += d0 + d1; s1 = fmaf(d0, d0, fmaf(d1, d1, s1)); }
        }
        #pragma unroll
        for (int o = 8; o; o >>= 1) { m1 += __shfl_xor_sync(0xffffffff, m1, o); s1 += __shfl_xor_sync(0xffffffff, s1, o); }
        const float md = m1 * (1.f / DM), var = fmaxf(fmaf(-md, md, s1 * (1.f / DM)), 0.f);
        if ((lane & 15) == it) w0 = pack_bf16(x0 + md, sqrt_approx(rbf(rbf(var) + 1e-5f)));
      }
      publish(w0 & 0x7fffffffu);
      TRACE1(2, 8);
      if (warp == 1 && W1SL) warm(1, 0, 5);
    }
        if (warp >= 2) {
      const int ps = 3 - warp;
      {
        const uint4* src = at<uint4>(P.wq, (((qt >> 2) * 4 + (lane >> 3)) * (NH * DH) + hg * 512 + ps * 256 + (qt & 3) * 64 + (lane & 7) * 8) * 2);
        const uint32_t mine = ((hg * 2 + ps) * 256 + qt * 16 + (lane & 7) * 2 + (lane >> 4)) * 16;
        float cs[8];
        #pragma unroll
        for (int e = 0; e < 8; e++) cs[e] = 0.f;
        #pragma unroll 1
        for (int b = 0; b < 40 / CSB; b++, src += CSB * 16 * 512) {
          uint4 w[CSB];
          #pragma unroll
          for (int i = 0; i < CSB; i++) w[i] = ldg_nc(src + i * 16 * 512);
          #pragma unroll
          for (int i = 0; i < CSB; i++) add8(cs, w[i]);
          if (b == 0) {
            mbar_wait(sb + B_EP, 0);
            if (!(lane & 8)) st_tagged(at<uint4>(g->cs, mine), ~lds32(sb + SM_EP) & 1, 0, 0, 0);
          }
        }
        #pragma unroll
        for (int e = 0; e < 4; e++) {
          cs[e] = ((lane & 16) ? cs[e + 4] : cs[e]) + __shfl_xor_sync(0xffffffff, (lane & 16) ? cs[e] : cs[e + 4], 16);
          cs[e] += __shfl_xor_sync(0xffffffff, cs[e], 8);
        }
        mbar_wait(sb + B_EP, 0);
        const uint32_t tm = 0u - (lds32(sb + SM_EP) & 1);
        const uint4* const gc = at<uint4>(g->cs, ((hg * 2 + ps) * 256 + lane) * 16);
        if (!(lane & 8)) st_tagged(at<uint4>(g->cs, mine), (__float_as_uint(cs[0]) & ~1u) | (tm & 1), __float_as_uint(cs[1]), __float_as_uint(cs[2]), __float_as_uint(cs[3]));

        uint4 v[9];
        int it = 0;
        uint32_t miss;
        do {
          #pragma unroll
          for (int i = 0; i < 8; i++) v[i] = ld_tagged(gc + i * 32);
          v[8] = ld_relaxed4(at<uint4>(g->stat, qt * 512 + lane * 16));
          miss = (tag_miss(v[8].x, v[8].y, tm) | tag_miss(v[8].z, v[8].w, tm)) >> 31;
          #pragma unroll
          for (int i = 0; i < 8; i += 2) miss |= tag_miss(v[i].x, v[i+1].x, tm);
        } while (__any_sync(0xffffffff, miss & 1) && ++it < MAXPOLL);
        #pragma unroll
        for (int i = 0; i < 2; i++) {
          auto sum = [](uint32_t a, uint32_t b, uint32_t c, uint32_t d) { return (__uint_as_float(a) + __uint_as_float(b)) + (__uint_as_float(c) + __uint_as_float(d)); };
          const float c0 = sum(v[i].x, v[i+2].x, v[i+4].x, v[i+6].x), c1 = sum(v[i].y, v[i+2].y, v[i+4].y, v[i+6].y);
          const float c2 = sum(v[i].z, v[i+2].z, v[i+4].z, v[i+6].z), c3 = sum(v[i].w, v[i+2].w, v[i+4].w, v[i+6].w);
          const uint32_t h0 = pack_bf16(c0, c1), h1 = pack_bf16(c2, c3), a = sb + SM_EXT + ps * 1024 + i * 512 + (lane >> 1) * 32 + (lane & 1) * 8;
          asm volatile("st.shared.v2.u32 [%0], {%1,%2};" :: "r"(a), "r"(h0), "r"(h1) : "memory");
          asm volatile("st.shared.v2.u32 [%0], {%1,%2};" :: "r"(a + 16), "r"(pack_bf16(c0 - bf_lo(h0), c1 - bf_hi(h0))), "r"(pack_bf16(c2 - bf_lo(h1), c3 - bf_hi(h1))) : "memory");
        }
        sts128(sb + SM_STAT + lane * 16, v[8].x & 0x7fffffffu, v[8].y & 0x7fffffffu, v[8].z & 0x7fffffffu, v[8].w & 0x7fffffffu);
        proxy_fence();
        __syncwarp();
        if (lane == 0) mbar_arrive(sb + B_EXT + ps * 8);
        TRACE1(2, 6 + ps);
        if (elect_one()) l2_prefetch(at<char>(ps ? P.v : P.k, (hg * 4 * S_LEN + qt * (16 + 8 * KVPF)) * DH * 2), 4096 + 2048 * KVPF);
      }
    }
    if (warp == 1 || warp == 2) {
      #pragma unroll 1
      for (int j = 0; j < GST; j++) mbar_wait(sb + B_KE + (j & 1) * 8, (j >> 1) & 1);
      int j = GST;
      const int r0 = qt * 128 + hg * 16 + (warp - 1) * 8 + (lane >> 4);
      uint32_t e = r0 * DM * 2 + (lane & 15) * 16;
      uint4 xn = ldg_nc(at<uint4>(P.x, e)), wn = ldg_nc(at<uint4>(P.wr, (lane & 15) * 16));
      #pragma unroll 1
      for (int it = 0; it < 4; it++) {
        const uint32_t st = __shfl_sync(0xffffffff, w0, (lane & 16) + it), m2 = __byte_perm(st, 0, 0x1010);
        const float rsd = rcp_approx(bf_hi(st));
        float a = 0.f;
        #pragma unroll 1
        for (int i = 0; i < 5; i++) {
          #pragma unroll 1
          do { if (GST) mbar_pace(sb + B_KE + (j & 1) * 8, (j >> 1) & 1); j++; } while (j >= 15 && j < 20);
          uint32_t z[4] = {xn.x, xn.y, xn.z, xn.w};
          const uint32_t ww[4] = {wn.x, wn.y, wn.z, wn.w}, en = e + (i < 4 ? 256 : (it < 3 ? 1536 : 0));
          xn = ldg_nc(at<uint4>(P.x, en)); wn = ldg_nc(at<uint4>(P.wr, (i < 4 ? i * 256 + 256 : 0) + (lane & 15) * 16));
          #pragma unroll
          for (int k = 0; k < 4; k++) {
            const uint32_t n = norm2(z[k], m2, rsd);
            const float lo = bf_lo(n), hi = bf_hi(n);
            a = fmaf(lo, bf_lo(ww[k]), fmaf(hi, bf_hi(ww[k]), a));
            z[k] = pack_bf16(lo * sigmoid_f(lo), hi * sigmoid_f(hi));
          }
          stg128(at<uint4>(g->gate, e), make_uint4(z[0], z[1], z[2], z[3]));
          e = en;
        }
        #pragma unroll
        for (int o = 8; o; o >>= 1) a += __shfl_xor_sync(0xffffffff, a, o);
        uint32_t u = pack_bf16(a, 0.f);
        if (u == 0x8000u) u = 0;
        u = (u & 0x8000u) ? (~u & 0xffffu) : (u | 0x8000u);
        if (!(lane & 15)) st_relaxed(at<uint32_t>(g->key, (r0 + it * 2) * 4), (u << 16) | (uint32_t)(0xffff - r0 - it * 2));
      }
      __syncwarp();
      if (lane == 0) flag_add_release(&g->cnt_gate.v);
      TRACE1(2, 9);
    }
    if (warp == 0) {
      const int row0 = hg * 4 * S_LEN;
      uint32_t s = 0, ph = 0;
      #pragma unroll 1
      for (int c = 3; c < 20; c++) {
        const int k = (c < 10 ? c : (c < 18 ? c - 8 : c - 18)) * 64, cb = hg * 8 + (c < 10 ? 0 : 4);
        const CUtensorMap* const tm = c < 10 ? &tmW4 : &tmW3;
        const uint32_t wb = c < 10 ? U : 12288;
        const bool wx = c < 10 || c >= 18;
        const uint32_t bar = sb + B_WF + s * 8, dst = sb + SM_W + rank * 8192 + s * U;
        mbar_wait(bar + (B_WE - B_WF), ph);
        if (elect_one()) {
          mbar_expect_tx(bar, wx ? wb + U : wb);
          tma_load_3d_mc(dst, tm, bar, 0, k + rank * 16, cb);
          if (wx) tma_load_2d(sb + ((c + 2) & 7) * U, &tmX, bar, k, qt * 128);
        }
        mbar_wait(bar + (B_WE - B_WF) + 8, ph);
        if (elect_one()) {
          mbar_expect_tx(bar + 8, wb);
          tma_load_3d_mc(dst + U, tm, bar + 8, 0, k + 32 + rank * 16, cb);
        }
        s += 2;
        if (s == 6) { s = 0; ph ^= 1; }
      }
      #pragma unroll 1
      for (int i = 0; i < 128; i++) {
        const int isv = i < 5 ? (i >> 1) & 1 : (i < 127 ? ~i & 1 : 1), j = i < 4 ? i & 1 : (i + 1 - 2 * isv) >> 1;
        const uint32_t b = isv * 16 + (j & 1) * 8;
        mbar_wait(sb + (i < 4 ? B_WE + ((0x3153 >> (4 * i)) & 7) * 8 : B_KE + b), i < 4 ? i < 2 : (~j >> 1) & 1);
        if (elect_one()) {
          mbar_expect_tx(sb + B_KF + b, 2 * U);
          tma_load_2d_mc(sb + (isv ? SM_V + (j & 1) * 2 * U : (j & 1) * SM_K1) + rank * U, isv ? &tmV : &tmK, sb + B_KF + b, rank * 64, row0 + j * 128);
        }
        if (i == 4) TRACEO(3);
      }
      s = 0; ph = 1;
      #pragma unroll 1
      for (int n = 0; n < (X_SKIP(qp) ? 2 : 40); n++) {
        const int st = n < 5 ? (n == 1) : n >> 2, h = n < 5 ? max(n - 1, 0) : n & 3;
        const int u = st < 2 ? 8 + st : ((hg + st - 1) & 7);
        mbar_wait(sb + (n < 6 ? B_KE + (n < 4 ? n >> 1 : 3) * 8 : B_CE + s * 8), ph);
        if (elect_one()) {
          mbar_expect_tx(sb + B_CF + s * 8, U);
          tma_load_2d_mc(sb + c_slot(s) * U + rank * 8192, &tmWO, sb + B_CF + s * 8, u * 64, hg * 512 + ((0x3021 >> (4 * h)) & 3) * 128 + rank * 64);
        }
        if (n == 3) TRACEO(4);
        if (++s == 6) { s = 0; ph ^= 1; }
      }
      mbar_wait(sb + B_GATE, 0);
      asm volatile("fence.proxy.async.global;" ::: "memory");
      #pragma unroll 1
      for (int n = 0; n < (X_SKIP(qp) ? 0 : 2); n++) {
        mbar_wait(sb + B_CE + 32 + n * 8, 1);
        if (elect_one()) {
          mbar_expect_tx(sb + B_CF + 32 + n * 8, U);
          tma_load_2d(sb + (10 + n) * U, n ? &tmGate : &tmX, sb + B_CF + 32 + n * 8, hg * 64, qt * 128);
        }
      }
      if (!X_SKIP(qp)) {
        const uint4* const last = g->part + (size_t)(qt * 80 + hg * 8 + ((hg + 1) & 7)) * 1024;
        mbar_wait(sb + B_CE + 16, 0);
        if (elect_one()) {
          mbar_expect_tx(sb + B_CF + 8, U);
          bulk_load(sb + U, last, U, sb + B_CF + 8);
        }
      }
    } else if (warp == 2) {
      #pragma unroll 1
      for (int h = 0; h < 4; h++) {
        mbar_wait(sb + B_OS + h * 8, 0);
        #pragma unroll 1
        for (int i = 0; i < (h < 3 ? 16 : 0); i++) {
          uint32_t z = 0;
          #pragma unroll
          for (int k = 0; k < 4; k++) { const uint4 v = lds128(sb + qo_slot(h) + i * 2048 + k * 512 + lane * 16); z = taint(taint(z, v.x, v.y), v.z, v.w); }
          flag_if(sb + SM_BAD + (i & 7) * 4 + h, tainted(z));
        }
        __syncwarp();
        if (h >= 2) { proxy_fence(); if (elect_one()) mbar_arrive(sb + B_OF); }
        __syncwarp();
      }
    } else if (!elect_one()) {
    } else if (warp == 1) {
      mbar_wait(sb + B_OS + 8, 0);
      flag_wait(at<unsigned>(g->q3_done, (hg >> 1) * 128), lds32(sb + SM_EP) * 16 + qt + 1);
      asm volatile("fence.proxy.async.global;" ::: "memory");
      mbar_expect_tx(sb + B_Q3, U);
      bulk_load(sb + 5 * U, g->q3 + (qt * 8 + hg) * 1024, U, sb + B_Q3);
      flag_wait(&g->mod_done.v, lds32(sb + SM_EP) * 4);
      mbar_arrive(sb + B_GATE);
    } else {
      #pragma unroll 1
      for (int j = 2; j < 64 - KVPF; j++) {
        mbar_pace(sb + B_KE + (j & 1) * 8, (~j >> 1) & 1);
        const size_t o = (size_t)(hg * 4 * S_LEN + (j + KVPF) * 128 + qt * 8) * DH;
        if (KVPF) { l2_prefetch(P.k + o, 2048); l2_prefetch(P.v + o, 2048); }
        if (j >= 40 && j < 56) l2_prefetch(P.wo + (size_t)(hg * 512 + qt * 32 + (j - 40) * 2) * DM, 2 * DM * 2);
        if (j >= 56 && j < 60) l2_prefetch(((j & 1) ? P.x : g->gate) + (size_t)(qt * 128 + hg * 16 + (j & 2) * 4) * DM, 8 * DM * 2);
      }
    }
    __syncwarp();
    if ((warp == 1 || warp == 2) && !X_SKIP(qp)) {
      mbar_wait(sb + B_GATE, 0);
      #pragma unroll 1
      for (int i = 0; i < 4; i++) {
        const int r = warp * 8 - 8 + (i & 1) * 4 + (lane >> 3);
        const uint32_t e = ((qt * 128 + hg * 16 + r) * DM + (8 + (i >> 1)) * 64 + (lane & 7) * 8) * 2;
        if (!(i & 1)) bar_sync(8, 192);
        const uint4 xr = ldg_nc(at<uint4>(P.x, e)), gr = ld_relaxed4(at<uint4>(g->gate, e)), sv = lds128(sb + SM_BAR + 1024 + r * 128 + (((lane ^ r) & 7) << 4));
        stg128(at<uint4>(P.out, e), gated(xr, sv, gr));
        if (i == 1) bar_arrive(9, 192);
      }
    }
    cluster_arrive();
    cluster_wait();
  } else {
    const int wg = wgi - 1, t = tid & 127, cw = warp - 4;
    asm volatile("setmaxnreg.inc.sync.aligned.u32 224;");
    uint32_t q[32], p[32];
    float s[64], o[64], l[2] = {0.f, 0.f};
    const uint32_t rb = __shfl_sync(0xffffffff, map_cta(sb, lane & 1), lane), wr = sb + cw * 2048, qa = __shfl_sync(0xffffffff, wr + lane * 16, lane);
    {
      uint32_t st0 = 0, st1 = 0;
      uint32_t sl = 0, ph = 0, rprev = 0;
      if (wg == 1) bar_arrive(1, 256);
      static_for<0, 2>([&](auto pc) { constexpr int pass = decltype(pc)::v;
        float acc[pass ? 96 : 128];
        #pragma unroll 1
        for (int i = 0; i < 10; i++) {
          if (i == (pass ? SKEW1 : SKEW0) / 2) {
            if (pass == 1) {
              const uint32_t d = qa + qo_slot(0);
              #pragma unroll
              for (int e = 0; e < 8; e++) sts128(d + (e >> 2) * U + (e & 3) * 512, p[4*e], p[4*e+1], p[4*e+2], p[4*e+3]);
            }
            bar_sync(1 + wg, 256);
          }
          const uint64_t a = desc(sb, ((i + 2 + 2 * pass) & 7) * 1024 + wg * 512 + doff(0, 16)), b = desc(sb, sl * 128 + doff(SM_W, 2048));
          mbar_wait(sb + B_WF + sl, ph);
          if (i == 0) TRACE(wg, 1 + pass);
          TRACEF(1, wg, 40 + pass * 20 + 2 * i);
          wg_fence();
          wgmma_ss_tb<0, 0>(acc, a, b, i > 0);
          wgmma_ss_tb<2, 512>(acc, a, b, 1);
          wg_commit();
          mbar_wait(sb + B_WF + 8 + sl, ph);
          wg_wait<1>();
          if (i > 0) release2(rprev, lane);
          TRACEF(1, wg, 41 + pass * 20 + 2 * i);
          wg_fence();
          wgmma_ss_tb<4, 1024>(acc, a, b, 1);
          wgmma_ss_tb<6, 1536>(acc, a, b, 1);
          wg_commit();
          rprev = rb + B_WE + 8 + sl;
          sl += 16;
          if (sl == 48) { sl = 0; ph ^= 1; }
          wg_wait<1>();
          release2(rprev - 8, lane);
        }
        mbar_wait(sb + B_EXT + pass * 8, 0);
        if (pass == 0) { st0 = lds32(sb + SM_STAT + (cw * 16 + (lane >> 2)) * 4); st1 = lds32(sb + SM_STAT + (cw * 16 + 8 + (lane >> 2)) * 4); }
        {
          const uint32_t a0 = (lane & 3) ? 0u : (__byte_perm(st0, 0, 0x1010) ^ 0x80008000u), a1 = (lane & 3) ? 0u : (__byte_perm(st1, 0, 0x1010) ^ 0x80008000u);
          wg_fence();
          wgmma_rs_tb<0>(acc, a0, a1, 0u, 0u, (uint64_t)desc_lo(sb + SM_EXT + pass * 1024, 0) | ((uint64_t)2 << 32), 1);
          wg_commit();
        }
        float rs0 = rcp_approx(bf_hi(st0)) * SCALE_LOG2E, rs1 = rcp_approx(bf_hi(st1)) * SCALE_LOG2E;
        bar_arrive(1 + (wg ^ 1), 256);
        wg_wait<0>();
        fence_regs(acc);
        release2(rprev, lane);
        if constexpr (pass == 0) {
          #pragma unroll
          for (int i = 0; i < 32; i++) {
            const float r = (i & 1) ? rs1 : rs0;
            q[i] = pack_bf16(acc[2*i] * r, acc[2*i+1] * r); p[i] = pack_bf16(acc[64+2*i] * r, acc[64+2*i+1] * r);
          }
        } else {
          const uint32_t d = qa + SM_QO;
          #pragma unroll
          for (int e = 0; e < 12; e++) {
            if (e == 8) {
              mbar_wait(sb + B_KF, 0);
              bar_sync(1 + wg, 256);
              TRACE(wg, 3);
              mma_qk<0, 2>(s, q, desc(sb, 2));
              bar_arrive(1 + (wg ^ 1), 256);
              const uint32_t one = lds32(sb + SM_ONE);
              rs0 = __uint_as_float(__float_as_uint(rs0) * one); rs1 = __uint_as_float(__float_as_uint(rs1) * one);
            }
            sts128(d + (e >> 2) * U + (e & 3) * 512, pack_bf16(acc[8*e] * rs0, acc[8*e+1] * rs0), pack_bf16(acc[8*e+2] * rs1, acc[8*e+3] * rs1),
                   pack_bf16(acc[8*e+4] * rs0, acc[8*e+5] * rs0), pack_bf16(acc[8*e+6] * rs1, acc[8*e+7] * rs1));
          }
          wg_wait<0>();
          fence_regs(s);
          release2(rb + B_KE, lane);
          exp_rows<0, 64>(s, l);
          #pragma unroll
          for (int i = 0; i < 32; i++) p[i] = pack_bf16(s[2*i], s[2*i+1]);
        }
      });
    }
    unsigned tz[3] = {0, 0, 0};
    bool ready = false;
    #pragma unroll 1
    for (int j = 1; ; j += 2) {
      int ph = 0;
      #pragma unroll 1
      do {
        attn_step<1, false>(sb, rb, wr, qa, wg, lane, j, ph, s, o, p, q, l, ready, g, tz);
        ph ^= 1; j += 2;
        if (wg < 2) attn_step<0, false>(sb, rb, wr, qa, wg, lane, j - 1, ph, s, o, p, q, l, ready, g, tz);
      } while ((j & 15) != 15);
      if (j == 47) mbar_wait(sb + B_Q3, 0);
      attn_step<1, true>(sb, rb, wr, qa, wg, lane, j, 1, s, o, p, q, l, ready, g, tz);
      if (j == 63) break;
      if (wg < 2) attn_step<0, true>(sb, rb, wr, qa, wg, lane, j + 1, 0, s, o, p, q, l, ready, g, tz);
    }
    mbar_wait(sb + B_OF, 0);
    mbar_wait(sb + B_CF + wg * 8, 0);
    mbar_wait(sb + B_KF + 24, 1);
    bar_sync(1 + wg, 256);
    TRACE(wg, 4);
    mma_pv<SM_V + 2 * U, 2>(o, p, desc(sb, 2), true);
    mma_c<3>(s, sb, wg, 0, 0);
    bar_arrive(1 + (wg ^ 1), 256);
    mbar_wait(sb + B_KE + 16, 1);
    const uint32_t tag = lds32(sb + SM_EP) & 1;
    row_scale(l[0], l[1], lds32(sb + SM_ONE), sb + SM_BAD + cw * 4 + 3);
    __syncwarp();
    const uint32_t flags = lds32(sb + SM_BAD + (lane & 7) * 4);
    wg_wait<1>();
    fence_regs(o); fence_regs(p);
    release2(rb + B_KE + 24, lane);
    const uint32_t over = tainted(store_o<true>(o_addr(wr, lane) + SM_V, o, l[0], l[1]));
    if (__builtin_expect(bar_any(4 + wg, 128, __any_sync(0xffffffff, flags | over)), 0)) {
      const uint32_t bad = __shfl_sync(0xffffffff, flags, cw) | (__any_sync(0xffffffff, over) << 24);
      wg_wait<0>();
      fence_regs(s);
      redo_heads(P, sb, bad, qt * 128 + cw * 16, hg * 4);
      #pragma unroll
      for (int i = 0; i < 64; i++) s[i] = 0.f;
      __syncwarp();
      if (lane == 0) mbar_arrive(sb + B_OS + 24);
      mbar_wait(sb + B_OF, 1);
      mma_c<4>(s, sb, wg, 0, 0);
    } else if (lane == 0) mbar_arrive(sb + B_OS + 24);
    wg_wait<0>();
    release2(rb + B_CE + wg * 8, lane);
    if (X_SKIP(qp)) { cluster_arrive(); } else {
      uint4* const part = g->part + (size_t)qt * 80 * 1024 + t;
      const uint32_t tm = 0u - tag;
      uint4 v[8];
      auto fetch = [&](uint4 (&v)[8], const uint4* from) {
        #pragma unroll
        for (int i = 0; i < 8; i++) v[i] = ld_tagged(from + i * 128);
      };
      auto verify = [&](uint4 (&v)[8], auto half, const uint4* from) {
        constexpr int b = decltype(half)::v * 4;
        #pragma unroll 1
        for (int it = 0; __any_sync(0xffffffff, or_bit0(tag_miss(v[b].x, v[b+1].x, tm), tag_miss(v[b+2].x, v[b+3].x, tm))) && it < MAXPOLL; it++) {
          #pragma unroll
          for (int i = b; i < b + 4; i++) v[i] = ld_tagged(from + i * 128);
        }
      };
      int sp = 6, sl = 2 + 3 * wg, ph = 0;
      auto quarter = [&](auto site, int h, int arrive_bar) {
        mbar_wait(sb + B_CF + sl * 8, ph);
        if (h == 0) bar_sync(1 + wg, 256);
        mma_c<decltype(site)::v>(s, sb, sl, h, arrive_bar);
        if (h) { wg_wait<1>(); release2(rb + B_CE + sp * 8, lane); }
        sp = sl;
        if (++sl == 6) { sl = 0; ph ^= 1; }
      };
      auto send = [&](int st) {
        uint4* dst = part + (st < 2 ? (8 + st) * 8192 + hg * 128 : (((hg + st - 1) & 7) * 8 + hg) * 1024);
        const int ds = st < 2 ? 1024 : 128;
        wg_wait<0>();
        fence_regs(s);
        TRACEF(4, wg, 106 + (st >> 1));
        release2(rb + B_CE + sp * 8, lane);
        #pragma unroll
        for (int i = 0; i < 8; i++, dst += ds)
          st_tagged(dst, (pack_bf16(s[8*i], s[8*i+1]) & ~1u) | tag, pack_bf16(s[8*i+2], s[8*i+3]), pack_bf16(s[8*i+4], s[8*i+5]), pack_bf16(s[8*i+6], s[8*i+7]));
        sl += st ? 4 : 3;
        if (sl >= 6) { sl -= 6; ph ^= 1; }
      };
      const uint32_t ta = ((lane >> 4) * 8 + (lane & 7)) * 128 + ((((cw & 3) * 2 + ((lane >> 3) & 1)) ^ (lane & 7)) << 4), ra = (t >> 3) * 128 + (((t & 7) ^ ((t >> 3) & 7)) << 4);
      TRACEF(4, wg, 112);
      bar_sync(1 + wg, 256);
      float T[64];
      auto from = [&](int f) { return part + (hg * 8 + ((hg + 1 - f) & 7)) * 1024; };
      auto take = [&](auto half, int f, bool more) {
        verify(v, half, from(f));
        const uint4* const nx = from(f + 1);
        #pragma unroll
        for (int i = decltype(half)::v * 4; i < decltype(half)::v * 4 + 4; i++) { add8(T + 8 * i, v[i]); if (more) v[i] = ld_tagged(nx + i * 128); }
      };
      #pragma unroll 1
      for (int st = wg; ; st += 2) {
        TRACEF(4, wg, 100 + (st >> 1));
        const bool odd5 = (st & 1) && st >= 5;
        const uint4* const rows = part + ((7 + (st >> 1)) * 8 + hg) * 1024;
        quarter(IC<5>{}, 1, 0);
        if (odd5) take(IC<0>{}, st - 3, true);
        else if (st == 2) fetch(v, rows);
        quarter(IC<6>{}, 2, 0);
        if (odd5) take(IC<1>{}, st - 3, true);
        if (st < 2) mbar_wait(sb + B_OF, 1);
        quarter(IC<7>{}, 3, st < 9 ? 2 - wg : 0);
        if (st < 9) send(st);
        if (odd5) { take(IC<0>{}, st - 2, st < 9); take(IC<1>{}, st - 2, st < 9); }
        else if (st == 3) {
          fetch(v, from(2));
          #pragma unroll
          for (int i = 0; i < 64; i++) asm volatile("mov.b32 %0, 0;" : "+f"(T[i]));
        } else if (st == 2 || st == 4) {
          float a[8];
          #pragma unroll
          for (int i = 0; i < 8; i++) a[i] = 0.f;
          static_for<0, 2>([&](auto hf) {
            verify(v, hf, rows);
            #pragma unroll
            for (int i = decltype(hf)::v * 4; i < decltype(hf)::v * 4 + 4; i++) { add8(a, v[i]); if (st == 2) v[i] = ld_tagged(rows + 8192 + i * 128); }
          });
          if (st == 4) bar_sync(9, 192);
          stsm4t(sb + SM_BAR + 1024 + ta, pack_bf16(a[0], a[1]), pack_bf16(a[2], a[3]), pack_bf16(a[4], a[5]), pack_bf16(a[6], a[7]));
          bar_arrive(8, 192);
        }
        if (st >= 8) break;
        quarter(IC<8>{}, 0, 0);
      }
      cluster_arrive();
      TRACEF(4, wg, 113);
      wg_wait<0>();
      fence_regs(s);
      if (wg == 0) {
        mbar_wait(sb + B_CF + 32, 0);
        mbar_wait(sb + B_CF + 40, 0);
        __nv_bfloat16* const op = P.out + (qt * 128 + (t >> 3)) * DM + hg * 64 + (t & 7) * 8;
        bar_sync(1, 256);
        uint4 xv[8];
        #pragma unroll
        for (int i = 0; i < 8; i++) { xv[i] = lds128(sb + 10 * U + i * 2048 + ra); v[i] = lds128(sb + 11 * U + i * 2048 + ra); }
        #pragma unroll
        for (int i = 0; i < 8; i++) {
          if (!(i & 3)) bar_sync(6 + (i >> 2), 256);
          *(uint4*)(op + i * 16 * DM) = gated(xv[i], lds128(sb + i * 2048 + ra), v[i]);
        }
      } else {
        TRACEF(4, wg, 110);
        mbar_wait(sb + B_CF + 8, 1);
        #pragma unroll
        for (int i = 0; i < 8; i++) v[i] = lds128(sb + U + i * 2048 + t * 16);
        bar_arrive(1, 256);
        #pragma unroll
        for (int i = 0; i < 64; i++) T[i] += s[i];
        static_for<0, 2>([&](auto hf) {
          take(hf, 8, false);
          if (decltype(hf)::v == 0) TRACE(wg, 5);
          #pragma unroll
          for (int i = decltype(hf)::v * 4; i < decltype(hf)::v * 4 + 4; i++)
            stsm4t(sb + i * 2048 + ta, pack_bf16(T[8*i], T[8*i+1]), pack_bf16(T[8*i+2], T[8*i+3]), pack_bf16(T[8*i+4], T[8*i+5]), pack_bf16(T[8*i+6], T[8*i+7]));
          bar_arrive(6 + decltype(hf)::v, 256);
        });
      }
    }
    TRACE(wg, 6);
    cluster_wait();
  }
}

typedef CUresult (*EncodeFn)(CUtensorMap*, CUtensorMapDataType, cuuint32_t, void*, const cuuint64_t*, const cuuint64_t*, const cuuint32_t*, const cuuint32_t*,
                             CUtensorMapInterleave, CUtensorMapSwizzle, CUtensorMapL2promotion, CUtensorMapFloatOOBfill);
void make_map(EncodeFn enc, CUtensorMap* tm, const void* ptr, uint64_t inner, uint64_t outer, uint32_t box_outer, uint32_t blocks = 0) {
  cuuint64_t dims[3] = {blocks ? 64 : inner, outer, inner / 64}; cuuint64_t strides[2] = {inner * 2, 128};
  cuuint32_t box[3] = {64, box_outer, blocks}; cuuint32_t es[3] = {1, 1, 1};
  enc(tm, CU_TENSOR_MAP_DATA_TYPE_BFLOAT16, blocks ? 3 : 2, const_cast<void*>(ptr), dims, strides, box, es, CU_TENSOR_MAP_INTERLEAVE_NONE,
      CU_TENSOR_MAP_SWIZZLE_128B, CU_TENSOR_MAP_L2_PROMOTION_L2_256B, CU_TENSOR_MAP_FLOAT_OOB_FILL_NONE);
}

}

extern "C" void kernel_launch(void* const* d_in, const int* in_sizes, int n_in, void* d_out, int out_size) {
  (void)in_sizes; (void)n_in; (void)out_size;
  Params P;
  P.x = (const __nv_bfloat16*)d_in[0]; P.k = (const __nv_bfloat16*)d_in[1]; P.v = (const __nv_bfloat16*)d_in[2];
  P.wq = (const __nv_bfloat16*)d_in[3]; P.wo = (const __nv_bfloat16*)d_in[4]; P.wr = (const __nv_bfloat16*)d_in[6];
  P.out = (__nv_bfloat16*)d_out;
  cudaGetSymbolAddress((void**)&P.g, g_s);
  void* fn = nullptr; cudaDriverEntryPointQueryResult st;
  cudaGetDriverEntryPoint("cuTensorMapEncodeTiled", &fn, cudaEnableDefault, &st);
  EncodeFn enc = (EncodeFn)fn;
  CUtensorMap tmX, tmW4, tmW3, tmW1, tmK, tmV, tmWO, tmG, tmU, tmD, tmGate;
  make_map(enc, &tmGate, P.g->gate, DM, S_LEN, 128);
  make_map(enc, &tmX, P.x, DM, S_LEN, 128);
  make_map(enc, &tmW4, P.wq, NH * DH, DM, 16, 4);
  make_map(enc, &tmW3, P.wq, NH * DH, DM, 16, 3);
  make_map(enc, &tmW1, P.wq, NH * DH, DM, 128);
  make_map(enc, &tmK, P.k, DH, (uint64_t)NH * S_LEN, 128);
  make_map(enc, &tmV, P.v, DH, (uint64_t)NH * S_LEN, 128);
  make_map(enc, &tmWO, P.wo, DM, NH * DH, 64);
  make_map(enc, &tmG, d_in[7], FF, DM, 128);
  make_map(enc, &tmU, d_in[8], FF, DM, 128);
  make_map(enc, &tmD, d_in[9], DM, FF, 128);
  cudaFuncSetAttribute(fused_kernel, cudaFuncAttributeMaxDynamicSharedMemorySize, SMEM_BYTES);
  fused_kernel<<<132, 384, SMEM_BYTES, cudaStreamPerThread>>>(tmX, tmW4, tmW3, tmW1, tmK, tmV, tmWO, tmG, tmU, tmD, tmGate, P);
}
```

```cpp
#include <cuda_runtime.h>
#include <cuda_bf16.h>
#include <cuda.h>
#include <stdint.h>

#define C_EARLY 6
#define MAXPOLL (1 << 22)
#define SKEW0 18
#define SKEW1 18
#define DPOS 44
#define DPOSF 36
#define KVPF 4
#define X_SKIP(qp) false
#define W1SL 300
#define WAITMAX (1 << 19)
#define CSB 10
#define P8 16
#define FQ 2
#define GSYNC 1
#define PH 1
#define QSP 6
namespace {

constexpr int S_LEN = 2048, DM = 640, NH = 32, DH = 128, FF = 1728, TOPC = 8;
constexpr float SCALE_LOG2E = 0.08838834764831845f * 1.4426950408889634f;

struct alignas(128) Cnt { unsigned v; unsigned pad[31]; };
struct Scratch {
  alignas(128) unsigned long long ticket;
  alignas(128)
  uint4 part[16 * 8 * 9 * 1024];
  __nv_bfloat16 gate[S_LEN * DM];
  uint32_t stat[S_LEN];
  uint4 cs[NH * DH];
  float ypart[4 * TOPC * DM];
  uint4 q3[16 * 8 * 1024];
  uint32_t key[S_LEN];
  Cnt cnt_gate, cnt_mod, mod_done, q3_done[4];
  uint32_t near[128 * 8];
};
__device__ Scratch g_s;

__device__ __forceinline__ uint32_t smem_u32(const void* p) { return (uint32_t)__cvta_generic_to_shared(p); }
template <class T> __device__ __forceinline__ T* at(const void* p, uint32_t off) { uint64_t r;
  asm("{\n.reg .u32 lo, hi;\nmov.b64 {lo, hi}, %1;\nadd.cc.u32 lo, lo, %2;\naddc.u32 hi, hi, 0;\nmov.b64 %0, {lo, hi};\n}\n" : "=l"(r) : "l"(p), "r"(off)); return (T*)r; }
__device__ __forceinline__ void mbar_init(uint32_t bar, uint32_t cnt) { asm volatile("mbarrier.init.shared::cta.b64 [%0], %1;" :: "r"(bar), "r"(cnt) : "memory"); }
__device__ __forceinline__ void mbar_expect_tx(uint32_t bar, uint32_t bytes) { asm volatile("mbarrier.arrive.expect_tx.shared::cta.b64 _, [%0], %1;" :: "r"(bar), "r"(bytes) : "memory"); }
__device__ __forceinline__ void mbar_arrive(uint32_t bar) { asm volatile("mbarrier.arrive.shared::cta.b64 _, [%0];" :: "r"(bar) : "memory"); }
__device__ __forceinline__ uint32_t map_cta(uint32_t a, uint32_t cta) { uint32_t r; asm volatile("mapa.shared::cluster.u32 %0, %1, %2;" : "=r"(r) : "r"(a), "r"(cta)); return r; }
__device__ __forceinline__ void mbar_arrive_cluster(uint32_t bar) { asm volatile("mbarrier.arrive.shared::cluster.b64 _, [%0];" :: "r"(bar) : "memory"); }
__device__ __forceinline__ void mbar_wait(uint32_t bar, uint32_t parity) {
  asm volatile("{\n.reg .pred p;\n.reg .u32 c;\nmov.u32 c, 0;\nLAB_WAIT:\nmbarrier.try_wait.parity.shared::cta.b64 p, [%0], %1;\n@p bra LAB_DONE;\n"
               "add.u32 c, c, 1;\nsetp.lt.u32 p, c, %2;\n@p bra LAB_WAIT;\ntrap;\nLAB_DONE:\n}\n" :: "r"(bar), "r"(parity), "n"(WAITMAX) : "memory"); }
__device__ __forceinline__ bool mbar_test2(uint32_t bar0, uint32_t par0, uint32_t bar1, uint32_t par1) { uint32_t r;
  asm volatile("{\n.reg .pred p, q;\nmbarrier.test_wait.parity.shared::cta.b64 p, [%1], %2;\nmbarrier.test_wait.parity.shared::cta.b64 q, [%3], %4;\nand.pred p, p, q;\nselp.u32 %0, 1, 0, p;\n}\n"
               : "=r"(r) : "r"(bar0), "r"(par0), "r"(bar1), "r"(par1) : "memory"); return r; }
__device__ __forceinline__ void mbar_pace(uint32_t bar, uint32_t parity) {
  asm volatile("{\n.reg .pred p;\n.reg .u32 c;\nmov.u32 c, 0;\nLAB_WAIT:\nmbarrier.try_wait.parity.shared::cta.b64 p, [%0], %1;\n@p bra LAB_DONE;\n"
               "add.u32 c, c, 1;\nsetp.lt.u32 p, c, 64;\n@p bra LAB_WAIT;\nLAB_DONE:\n}\n" :: "r"(bar), "r"(parity) : "memory"); }
__device__ __forceinline__ void flag_wait(const unsigned* p, unsigned target, unsigned ns = 500) {
  asm volatile("{\n.reg .pred p;\n.reg .u32 c, v;\nmov.u32 c, 0;\nLAB_WAIT:\nld.relaxed.gpu.global.u32 v, [%0];\nsub.u32 v, v, %1;\nsetp.ge.s32 p, v, 0;\n@p bra LAB_DONE;\n"
               "nanosleep.u32 %2;\nadd.u32 c, c, 1;\nsetp.lt.u32 p, c, 8388608;\n@p bra LAB_WAIT;\ntrap;\nLAB_DONE:\nld.acquire.gpu.global.u32 v, [%0];\n}\n" :: "l"(p), "r"(target), "r"(ns) : "memory"); }
__device__ __forceinline__ void flag_add_release(unsigned* p) { asm volatile("fence.acq_rel.gpu;\nred.relaxed.gpu.global.add.u32 [%0], 1;" :: "l"(p) : "memory"); }
__device__ __forceinline__ void tma_load_2d(uint32_t dst, const CUtensorMap* tm, uint32_t bar, int c0, int c1) {
  asm volatile("cp.async.bulk.tensor.2d.shared::cluster.global.mbarrier::complete_tx::bytes [%0], [%1, {%3, %4}], [%2];"
    :: "r"(dst), "l"(tm), "r"(bar), "r"(c0), "r"(c1) : "memory"); }
__device__ __forceinline__ void tma_load_2d_mc(uint32_t dst, const CUtensorMap* tm, uint32_t bar, int c0, int c1) {
  asm volatile("cp.async.bulk.tensor.2d.shared::cluster.global.mbarrier::complete_tx::bytes.multicast::cluster [%0], [%1, {%3, %4}], [%2], %5;"
    :: "r"(dst), "l"(tm), "r"(bar), "r"(c0), "r"(c1), "h"((uint16_t)3) : "memory"); }
__device__ __forceinline__ void tma_load_3d(uint32_t dst, const CUtensorMap* tm, uint32_t bar, int c0, int c1, int c2) {
  asm volatile("cp.async.bulk.tensor.3d.shared::cluster.global.mbarrier::complete_tx::bytes [%0], [%1, {%3, %4, %5}], [%2];"
    :: "r"(dst), "l"(tm), "r"(bar), "r"(c0), "r"(c1), "r"(c2) : "memory"); }
__device__ __forceinline__ void tma_load_3d_mc(uint32_t dst, const CUtensorMap* tm, uint32_t bar, int c0, int c1, int c2) {
  asm volatile("cp.async.bulk.tensor.3d.shared::cluster.global.mbarrier::complete_tx::bytes.multicast::cluster [%0], [%1, {%3, %4, %5}], [%2], %6;"
    :: "r"(dst), "l"(tm), "r"(bar), "r"(c0), "r"(c1), "r"(c2), "h"((uint16_t)3) : "memory"); }
__device__ __forceinline__ void bulk_load(uint32_t dst, const void* src, uint32_t bytes, uint32_t bar) {
  asm volatile("cp.async.bulk.shared::cluster.global.mbarrier::complete_tx::bytes [%0], [%1], %2, [%3];" :: "r"(dst), "l"(src), "r"(bytes), "r"(bar) : "memory"); }
__device__ __forceinline__ void l2_prefetch(const void* p, uint32_t bytes) { asm volatile("cp.async.bulk.prefetch.L2.global [%0], %1;" :: "l"(p), "r"(bytes) : "memory"); }
__device__ __forceinline__ void wg_fence() { asm volatile("wgmma.fence.sync.aligned;" ::: "memory"); }
__device__ __forceinline__ void wg_commit() { asm volatile("wgmma.commit_group.sync.aligned;" ::: "memory"); }
template <int N> __device__ __forceinline__ void wg_wait() { asm volatile("wgmma.wait_group.sync.aligned %0;" :: "n"(N) : "memory"); }
__device__ __forceinline__ void bar_sync(int id, int n) { asm volatile("bar.sync %0, %1;" :: "r"(id), "r"(n) : "memory"); }
__device__ __forceinline__ void bar_arrive(int id, int n) { asm volatile("bar.arrive %0, %1;" :: "r"(id), "r"(n) : "memory"); }
__device__ __forceinline__ bool bar_any(int id, int n, uint32_t v) { uint32_t r;
  asm volatile("{\n.reg .pred p;\nsetp.ne.u32 p, %3, 0;\nbar.red.or.pred p, %1, %2, p;\nselp.u32 %0, 1, 0, p;\n}\n" : "=r"(r) : "r"(id), "r"(n), "r"(v) : "memory"); return r; }
__device__ __forceinline__ int sel_lt(int a, int b, int x, int y) { int r; asm("{\n.reg .pred p;\nsetp.lt.s32 p, %1, %2;\nselp.s32 %0, %3, %4, p;\n}\n" : "=r"(r) : "r"(a), "r"(b), "r"(x), "r"(y)); return r; }
__device__ __forceinline__ bool elect_one() { uint32_t r; asm volatile("{\n.reg .pred p;\nelect.sync _|p, 0xffffffff;\nselp.u32 %0, 1, 0, p;\n}\n" : "=r"(r)); return r; }
__device__ __forceinline__ void cluster_arrive() { asm volatile("barrier.cluster.arrive.relaxed.aligned;" ::: "memory"); }
__device__ __forceinline__ void cluster_wait() { asm volatile("barrier.cluster.wait.aligned;" ::: "memory"); }
__device__ __forceinline__ void proxy_fence() { asm volatile("fence.proxy.async.shared::cta;" ::: "memory"); }
__device__ __forceinline__ uint32_t pack_bf16(float lo, float hi) { uint32_t r; asm("cvt.rn.bf16x2.f32 %0, %1, %2;" : "=r"(r) : "f"(hi), "f"(lo)); return r; }
__device__ __forceinline__ float bf_lo(uint32_t v) { return __uint_as_float(v << 16); }
__device__ __forceinline__ float bf_hi(uint32_t v) { return __uint_as_float(v & 0xffff0000u); }
__device__ __forceinline__ void add8(float* a, const uint4& w) {
  a[0] += bf_lo(w.x); a[1] += bf_hi(w.x); a[2] += bf_lo(w.y); a[3] += bf_hi(w.y); a[4] += bf_lo(w.z); a[5] += bf_hi(w.z); a[6] += bf_lo(w.w); a[7] += bf_hi(w.w); }
__device__ __forceinline__ float rbf(float x) { return __bfloat162float(__float2bfloat16_rn(x)); }
__device__ __forceinline__ float ex2(float x) { float y; asm("ex2.approx.ftz.f32 %0, %1;" : "=f"(y) : "f"(x)); return y; }
__device__ __forceinline__ uint32_t lds32(uint32_t a) { uint32_t v; asm volatile("ld.shared.u32 %0, [%1];" : "=r"(v) : "r"(a) : "memory"); return v; }
__device__ __forceinline__ void sts32(uint32_t a, uint32_t v) { asm volatile("st.shared.u32 [%0], %1;" :: "r"(a), "r"(v) : "memory"); }
__device__ __forceinline__ uint4 lds128(uint32_t a) { uint4 v; asm volatile("ld.shared.v4.u32 {%0,%1,%2,%3}, [%4];" : "=r"(v.x), "=r"(v.y), "=r"(v.z), "=r"(v.w) : "r"(a) : "memory"); return v; }
__device__ __forceinline__ void sts128(uint32_t a, uint32_t x, uint32_t y, uint32_t z, uint32_t w) { asm volatile("st.shared.v4.u32 [%0], {%1,%2,%3,%4};" :: "r"(a), "r"(x), "r"(y), "r"(z), "r"(w) : "memory"); }
__device__ __forceinline__ void st_tagged(uint4* p, uint32_t x, uint32_t y, uint32_t z, uint32_t w) {
  asm volatile("st.relaxed.gpu.global.v4.u32 [%0], {%1,%2,%3,%4};" :: "l"(p), "r"(x), "r"(y), "r"(z), "r"(w) : "memory"); }
__device__ __forceinline__ uint4 ld_relaxed4(const void* p) { uint4 v;
  asm volatile("ld.relaxed.gpu.global.v4.u32 {%0,%1,%2,%3}, [%4];" : "=r"(v.x), "=r"(v.y), "=r"(v.z), "=r"(v.w) : "l"(p) : "memory"); return v; }
__device__ __forceinline__ uint4 ld_tagged(const uint4* p) { uint4 v;
  asm volatile("{\n.reg .b128 v;\nld.relaxed.gpu.global.b128 v, [%4];\nmov.b128 {%0,%1,%2,%3}, v;\n}\n" : "=r"(v.x), "=r"(v.y), "=r"(v.z), "=r"(v.w) : "l"(p) : "memory"); return v; }
__device__ __forceinline__ void reload(uint4& v, const uint4* p, bool yes = true) {
  asm volatile("{\n.reg .pred p;\nsetp.ne.u32 p, %5, 0;\n@p ld.relaxed.gpu.global.v4.u32 {%0,%1,%2,%3}, [%4];\n}\n" : "+r"(v.x), "+r"(v.y), "+r"(v.z), "+r"(v.w) : "l"(p), "r"((uint32_t)yes) : "memory"); }
#define TAG_TEST "lop3.b32 a, %0, %4, %17, 0x7E;\nlop3.b32 b, %8, %12, %17, 0x7E;\nlop3.b32 a, a, b, 1, 0xA8;\nsetp.ne.u32 p, a, 0;\nvote.sync.any.pred p, p, 0xffffffff;\n"
__device__ __forceinline__ void verify4(uint4* v, const uint4* p, uint32_t tm) {
  asm volatile("{\n.reg .pred p;\n.reg .u32 a, b, c;\n" TAG_TEST "@!p bra.uni LAB_DONE;\nmov.u32 c, 0;\nLAB_AGAIN:\n"
    "ld.relaxed.gpu.global.v4.u32 {%0,%1,%2,%3}, [%16];\nld.relaxed.gpu.global.v4.u32 {%4,%5,%6,%7}, [%16+2048];\n"
    "ld.relaxed.gpu.global.v4.u32 {%8,%9,%10,%11}, [%16+4096];\nld.relaxed.gpu.global.v4.u32 {%12,%13,%14,%15}, [%16+6144];\n"
    TAG_TEST "add.u32 c, c, 1;\nsetp.lt.and.u32 p, c, %18, p;\n@p bra.uni LAB_AGAIN;\nLAB_DONE:\n}\n"
    : "+r"(v[0].x), "+r"(v[0].y), "+r"(v[0].z), "+r"(v[0].w), "+r"(v[1].x), "+r"(v[1].y), "+r"(v[1].z), "+r"(v[1].w),
      "+r"(v[2].x), "+r"(v[2].y), "+r"(v[2].z), "+r"(v[2].w), "+r"(v[3].x), "+r"(v[3].y), "+r"(v[3].z), "+r"(v[3].w) : "l"(p), "r"(tm), "n"(MAXPOLL) : "memory"); }
__device__ __forceinline__ uint4 ldg_nc(const void* p) { uint4 v;
  asm volatile("ld.global.nc.L1::no_allocate.v4.u32 {%0,%1,%2,%3}, [%4];" : "=r"(v.x), "=r"(v.y), "=r"(v.z), "=r"(v.w) : "l"(p) : "memory"); return v; }
__device__ __forceinline__ uint32_t ldg32(const void* p) { uint32_t v; asm volatile("ld.relaxed.gpu.global.u32 %0, [%1];" : "=r"(v) : "l"(p) : "memory"); return v; }
__device__ __forceinline__ void stg128(void* p, const uint4& v) { asm volatile("st.global.v4.u32 [%0], {%1,%2,%3,%4};" :: "l"(p), "r"(v.x), "r"(v.y), "r"(v.z), "r"(v.w) : "memory"); }
__device__ __forceinline__ void st_relaxed(uint32_t* p, uint32_t v) { asm volatile("st.relaxed.gpu.global.u32 [%0], %1;" :: "l"(p), "r"(v) : "memory"); }
__device__ __forceinline__ uint32_t mul_bf2(uint32_t a, uint32_t b) { uint32_t r; asm("mul.rn.bf16x2 %0, %1, %2;" : "=r"(r) : "r"(a), "r"(b)); return r; }
__device__ __forceinline__ uint32_t add_bf2(uint32_t a, uint32_t b) { uint32_t r; asm("add.rn.bf16x2 %0, %1, %2;" : "=r"(r) : "r"(a), "r"(b)); return r; }
__device__ __forceinline__ uint32_t sub_bf2(uint32_t a, uint32_t b) { uint32_t r; asm("sub.rn.bf16x2 %0, %1, %2;" : "=r"(r) : "r"(a), "r"(b)); return r; }
__device__ __forceinline__ void stsm4(uint32_t a, uint32_t r0, uint32_t r1, uint32_t r2, uint32_t r3) {
  asm volatile("stmatrix.sync.aligned.m8n8.x4.shared.b16 [%0], {%1,%2,%3,%4};" :: "r"(a), "r"(r0), "r"(r1), "r"(r2), "r"(r3) : "memory"); }
__device__ __forceinline__ void stsm4t(uint32_t a, uint32_t r0, uint32_t r1, uint32_t r2, uint32_t r3) {
  asm volatile("stmatrix.sync.aligned.m8n8.x4.trans.shared.b16 [%0], {%1,%2,%3,%4};" :: "r"(a), "r"(r0), "r"(r1), "r"(r2), "r"(r3) : "memory"); }
__device__ __forceinline__ uint4 gated(const uint4& x, const uint4& s, const uint4& g) {
  return make_uint4(add_bf2(x.x, mul_bf2(s.x, g.x)), add_bf2(x.y, mul_bf2(s.y, g.y)), add_bf2(x.z, mul_bf2(s.z, g.z)), add_bf2(x.w, mul_bf2(s.w, g.w))); }
__device__ __forceinline__ uint32_t tag_miss(uint32_t a, uint32_t b, uint32_t tm) { uint32_t d; asm("lop3.b32 %0, %1, %2, %3, 0x7E;" : "=r"(d) : "r"(a), "r"(b), "r"(tm)); return d; }
template <int R> __device__ __forceinline__ void fence_regs(float (&d)[R]) {
  #pragma unroll
  for (int i = 0; i < R; i++) asm volatile("" : "+f"(d[i]) :: "memory"); }
template <int R> __device__ __forceinline__ void fence_regs(uint32_t (&d)[R]) {
  #pragma unroll
  for (int i = 0; i < R; i++) asm volatile("" : "+r"(d[i]) :: "memory"); }
__device__ __forceinline__ uint32_t desc_lo(uint32_t addr, uint32_t lbo_bytes) { return ((addr & 0x3FFFF) >> 4) | ((lbo_bytes >> 4) << 16); }
__device__ __forceinline__ uint64_t desc(uint32_t sb, uint32_t var = 0) {
  uint64_t d; asm("mov.b64 %0, {%1, %2};" : "=l"(d) : "r"(desc_lo(sb, 0) + var), "r"(0x40000040u)); return d; }
__host__ __device__ constexpr int doff(uint32_t off, uint32_t lbo_bytes) { return (off >> 4) | ((lbo_bytes >> 4) << 16); }
__device__ __forceinline__ float rcp_approx(float x) { float y; asm("rcp.approx.f32 %0, %1;" : "=f"(y) : "f"(x)); return y; }
__device__ __forceinline__ float rcp_fast(float x) { float y; asm("rcp.approx.ftz.f32 %0, %1;" : "=f"(y) : "f"(x)); return y; }
__device__ __forceinline__ float sqrt_approx(float x) { float y; asm("sqrt.approx.f32 %0, %1;" : "=f"(y) : "f"(x)); return y; }
__device__ __forceinline__ float sigmoid_f(float z) { return rcp_fast(1.f + ex2(z * -1.4426950408889634f)); }
__device__ __forceinline__ uint32_t norm2(uint32_t x, uint32_t mean2, float rsd) { const uint32_t d = sub_bf2(x, mean2); return pack_bf16(bf_lo(d) * rsd, bf_hi(d) * rsd); }
#define STALL(site)
#define TRACE(w, i)
#define TRACE1(w, i)
#define TRACEF(m, w, i)
#define TRACEO(i)

template <int OA, int OB> __device__ __forceinline__ void wgmma_ss_tb(float (&d)[128], uint64_t da, uint64_t db, int sd) {
  asm volatile("{\n.reg .pred p;\n.reg .b64 a, b;\nadd.s64 a, %128, %131;\nadd.s64 b, %129, %132;\nsetp.ne.b32 p, %130, 0;\n"
    "wgmma.mma_async.sync.aligned.m64n256k16.f32.bf16.bf16 {%0, %1, %2, %3, %4, %5, %6, %7, %8, %9, %10, %11, %12, %13, %14, %15, %16, %17, %18, %19, %20, %21, %22, %23, %24, %25, %26, %27, %28, %29, %30, %31, %32, %33, %34, %35, %36, %37, %38, %39, %40, %41, %42, %43, %44, %45, %46, %47, %48, %49, %50, %51, %52, %53, %54, %55, %56, %57, %58, %59, %60, %61, %62, %63, %64, %65, %66, %67, %68, %69, %70, %71, %72, %73, %74, %75, %76, %77, %78, %79, %80, %81, %82, %83, %84, %85, %86, %87, %88, %89, %90, %91, %92, %93, %94, %95, %96, %97, %98, %99, %100, %101, %102, %103, %104, %105, %106, %107, %108, %109, %110, %111, %112, %113, %114, %115, %116, %117, %118, %119, %120, %121, %122, %123, %124, %125, %126, %127}, a, b, p, 1, 1, 0, 1;\n}\n"
    : "+f"(d[0]), "+f"(d[1]), "+f"(d[2]), "+f"(d[3]), "+f"(d[4]), "+f"(d[5]), "+f"(d[6]), "+f"(d[7]), "+f"(d[8]), "+f"(d[9]), "+f"(d[10]), "+f"(d[11]), "+f"(d[12]), "+f"(d[13]), "+f"(d[14]), "+f"(d[15]), "+f"(d[16]), "+f"(d[17]), "+f"(d[18]), "+f"(d[19]), "+f"(d[20]), "+f"(d[21]), "+f"(d[22]), "+f"(d[23]), "+f"(d[24]), "+f"(d[25]), "+f"(d[26]), "+f"(d[27]), "+f"(d[28]), "+f"(d[29]), "+f"(d[30]), "+f"(d[31]), "+f"(d[32]), "+f"(d[33]), "+f"(d[34]), "+f"(d[35]), "+f"(d[36]), "+f"(d[37]), "+f"(d[38]), "+f"(d[39]), "+f"(d[40]), "+f"(d[41]), "+f"(d[42]), "+f"(d[43]), "+f"(d[44]), "+f"(d[45]), "+f"(d[46]), "+f"(d[47]), "+f"(d[48]), "+f"(d[49]), "+f"(d[50]), "+f"(d[51]), "+f"(d[52]), "+f"(d[53]), "+f"(d[54]), "+f"(d[55]), "+f"(d[56]), "+f"(d[57]), "+f"(d[58]), "+f"(d[59]), "+f"(d[60]), "+f"(d[61]), "+f"(d[62]), "+f"(d[63]), "+f"(d[64]), "+f"(d[65]), "+f"(d[66]), "+f"(d[67]), "+f"(d[68]), "+f"(d[69]), "+f"(d[70]), "+f"(d[71]), "+f"(d[72]), "+f"(d[73]), "+f"(d[74]), "+f"(d[75]), "+f"(d[76]), "+f"(d[77]), "+f"(d[78]), "+f"(d[79]), "+f"(d[80]), "+f"(d[81]), "+f"(d[82]), "+f"(d[83]), "+f"(d[84]), "+f"(d[85]), "+f"(d[86]), "+f"(d[87]), "+f"(d[88]), "+f"(d[89]), "+f"(d[90]), "+f"(d[91]), "+f"(d[92]), "+f"(d[93]), "+f"(d[94]), "+f"(d[95]), "+f"(d[96]), "+f"(d[97]), "+f"(d[98]), "+f"(d[99]), "+f"(d[100]), "+f"(d[101]), "+f"(d[102]), "+f"(d[103]), "+f"(d[104]), "+f"(d[105]), "+f"(d[106]), "+f"(d[107]), "+f"(d[108]), "+f"(d[109]), "+f"(d[110]), "+f"(d[111]), "+f"(d[112]), "+f"(d[113]), "+f"(d[114]), "+f"(d[115]), "+f"(d[116]), "+f"(d[117]), "+f"(d[118]), "+f"(d[119]), "+f"(d[120]), "+f"(d[121]), "+f"(d[122]), "+f"(d[123]), "+f"(d[124]), "+f"(d[125]), "+f"(d[126]), "+f"(d[127])
    : "l"(da), "l"(db), "r"(sd), "n"(OA), "n"(OB));
}
template <int OB> __device__ __forceinline__ void wgmma_rs_tb(float (&d)[128], uint32_t a0, uint32_t a1, uint32_t a2, uint32_t a3, uint64_t db, int sd) {
  asm volatile("{\n.reg .pred p;\n.reg .b64 b;\nadd.s64 b, %132, %134;\nsetp.ne.b32 p, %133, 0;\n"
    "wgmma.mma_async.sync.aligned.m64n256k16.f32.bf16.bf16 {%0, %1, %2, %3, %4, %5, %6, %7, %8, %9, %10, %11, %12, %13, %14, %15, %16, %17, %18, %19, %20, %21, %22, %23, %24, %25, %26, %27, %28, %29, %30, %31, %32, %33, %34, %35, %36, %37, %38, %39, %40, %41, %42, %43, %44, %45, %46, %47, %48, %49, %50, %51, %52, %53, %54, %55, %56, %57, %58, %59, %60, %61, %62, %63, %64, %65, %66, %67, %68, %69, %70, %71, %72, %73, %74, %75, %76, %77, %78, %79, %80, %81, %82, %83, %84, %85, %86, %87, %88, %89, %90, %91, %92, %93, %94, %95, %96, %97, %98, %99, %100, %101, %102, %103, %104, %105, %106, %107, %108, %109, %110, %111, %112, %113, %114, %115, %116, %117, %118, %119, %120, %121, %122, %123, %124, %125, %126, %127}, {%128, %129, %130, %131}, b, p, 1, 1, 1;\n}\n"
    : "+f"(d[0]), "+f"(d[1]), "+f"(d[2]), "+f"(d[3]), "+f"(d[4]), "+f"(d[5]), "+f"(d[6]), "+f"(d[7]), "+f"(d[8]), "+f"(d[9]), "+f"(d[10]), "+f"(d[11]), "+f"(d[12]), "+f"(d[13]), "+f"(d[14]), "+f"(d[15]), "+f"(d[16]), "+f"(d[17]), "+f"(d[18]), "+f"(d[19]), "+f"(d[20]), "+f"(d[21]), "+f"(d[22]), "+f"(d[23]), "+f"(d[24]), "+f"(d[25]), "+f"(d[26]), "+f"(d[27]), "+f"(d[28]), "+f"(d[29]), "+f"(d[30]), "+f"(d[31]), "+f"(d[32]), "+f"(d[33]), "+f"(d[34]), "+f"(d[35]), "+f"(d[36]), "+f"(d[37]), "+f"(d[38]), "+f"(d[39]), "+f"(d[40]), "+f"(d[41]), "+f"(d[42]), "+f"(d[43]), "+f"(d[44]), "+f"(d[45]), "+f"(d[46]), "+f"(d[47]), "+f"(d[48]), "+f"(d[49]), "+f"(d[50]), "+f"(d[51]), "+f"(d[52]), "+f"(d[53]), "+f"(d[54]), "+f"(d[55]), "+f"(d[56]), "+f"(d[57]), "+f"(d[58]), "+f"(d[59]), "+f"(d[60]), "+f"(d[61]), "+f"(d[62]), "+f"(d[63]), "+f"(d[64]), "+f"(d[65]), "+f"(d[66]), "+f"(d[67]), "+f"(d[68]), "+f"(d[69]), "+f"(d[70]), "+f"(d[71]), "+f"(d[72]), "+f"(d[73]), "+f"(d[74]), "+f"(d[75]), "+f"(d[76]), "+f"(d[77]), "+f"(d[78]), "+f"(d[79]), "+f"(d[80]), "+f"(d[81]), "+f"(d[82]), "+f"(d[83]), "+f"(d[84]), "+f"(d[85]), "+f"(d[86]), "+f"(d[87]), "+f"(d[88]), "+f"(d[89]), "+f"(d[90]), "+f"(d[91]), "+f"(d[92]), "+f"(d[93]), "+f"(d[94]), "+f"(d[95]), "+f"(d[96]), "+f"(d[97]), "+f"(d[98]), "+f"(d[99]), "+f"(d[100]), "+f"(d[101]), "+f"(d[102]), "+f"(d[103]), "+f"(d[104]), "+f"(d[105]), "+f"(d[106]), "+f"(d[107]), "+f"(d[108]), "+f"(d[109]), "+f"(d[110]), "+f"(d[111]), "+f"(d[112]), "+f"(d[113]), "+f"(d[114]), "+f"(d[115]), "+f"(d[116]), "+f"(d[117]), "+f"(d[118]), "+f"(d[119]), "+f"(d[120]), "+f"(d[121]), "+f"(d[122]), "+f"(d[123]), "+f"(d[124]), "+f"(d[125]), "+f"(d[126]), "+f"(d[127])
    : "r"(a0), "r"(a1), "r"(a2), "r"(a3), "l"(db), "r"(sd), "n"(OB));
}
template <int OA, int OB> __device__ __forceinline__ void wgmma_ss_tb(float (&d)[96], uint64_t da, uint64_t db, int sd) {
  asm volatile("{\n.reg .pred p;\n.reg .b64 a, b;\nadd.s64 a, %96, %99;\nadd.s64 b, %97, %100;\nsetp.ne.b32 p, %98, 0;\n"
    "wgmma.mma_async.sync.aligned.m64n192k16.f32.bf16.bf16 {%0, %1, %2, %3, %4, %5, %6, %7, %8, %9, %10, %11, %12, %13, %14, %15, %16, %17, %18, %19, %20, %21, %22, %23, %24, %25, %26, %27, %28, %29, %30, %31, %32, %33, %34, %35, %36, %37, %38, %39, %40, %41, %42, %43, %44, %45, %46, %47, %48, %49, %50, %51, %52, %53, %54, %55, %56, %57, %58, %59, %60, %61, %62, %63, %64, %65, %66, %67, %68, %69, %70, %71, %72, %73, %74, %75, %76, %77, %78, %79, %80, %81, %82, %83, %84, %85, %86, %87, %88, %89, %90, %91, %92, %93, %94, %95}, a, b, p, 1, 1, 0, 1;\n}\n"
    : "+f"(d[0]), "+f"(d[1]), "+f"(d[2]), "+f"(d[3]), "+f"(d[4]), "+f"(d[5]), "+f"(d[6]), "+f"(d[7]), "+f"(d[8]), "+f"(d[9]), "+f"(d[10]), "+f"(d[11]), "+f"(d[12]), "+f"(d[13]), "+f"(d[14]), "+f"(d[15]), "+f"(d[16]), "+f"(d[17]), "+f"(d[18]), "+f"(d[19]), "+f"(d[20]), "+f"(d[21]), "+f"(d[22]), "+f"(d[23]), "+f"(d[24]), "+f"(d[25]), "+f"(d[26]), "+f"(d[27]), "+f"(d[28]), "+f"(d[29]), "+f"(d[30]), "+f"(d[31]), "+f"(d[32]), "+f"(d[33]), "+f"(d[34]), "+f"(d[35]), "+f"(d[36]), "+f"(d[37]), "+f"(d[38]), "+f"(d[39]), "+f"(d[40]), "+f"(d[41]), "+f"(d[42]), "+f"(d[43]), "+f"(d[44]), "+f"(d[45]), "+f"(d[46]), "+f"(d[47]), "+f"(d[48]), "+f"(d[49]), "+f"(d[50]), "+f"(d[51]), "+f"(d[52]), "+f"(d[53]), "+f"(d[54]), "+f"(d[55]), "+f"(d[56]), "+f"(d[57]), "+f"(d[58]), "+f"(d[59]), "+f"(d[60]), "+f"(d[61]), "+f"(d[62]), "+f"(d[63]), "+f"(d[64]), "+f"(d[65]), "+f"(d[66]), "+f"(d[67]), "+f"(d[68]), "+f"(d[69]), "+f"(d[70]), "+f"(d[71]), "+f"(d[72]), "+f"(d[73]), "+f"(d[74]), "+f"(d[75]), "+f"(d[76]), "+f"(d[77]), "+f"(d[78]), "+f"(d[79]), "+f"(d[80]), "+f"(d[81]), "+f"(d[82]), "+f"(d[83]), "+f"(d[84]), "+f"(d[85]), "+f"(d[86]), "+f"(d[87]), "+f"(d[88]), "+f"(d[89]), "+f"(d[90]), "+f"(d[91]), "+f"(d[92]), "+f"(d[93]), "+f"(d[94]), "+f"(d[95])
    : "l"(da), "l"(db), "r"(sd), "n"(OA), "n"(OB));
}
template <int OB> __device__ __forceinline__ void wgmma_rs_tb(float (&d)[96], uint32_t a0, uint32_t a1, uint32_t a2, uint32_t a3, uint64_t db, int sd) {
  asm volatile("{\n.reg .pred p;\n.reg .b64 b;\nadd.s64 b, %100, %102;\nsetp.ne.b32 p, %101, 0;\n"
    "wgmma.mma_async.sync.aligned.m64n192k16.f32.bf16.bf16 {%0, %1, %2, %3, %4, %5, %6, %7, %8, %9, %10, %11, %12, %13, %14, %15, %16, %17, %18, %19, %20, %21, %22, %23, %24, %25, %26, %27, %28, %29, %30, %31, %32, %33, %34, %35, %36, %37, %38, %39, %40, %41, %42, %43, %44, %45, %46, %47, %48, %49, %50, %51, %52, %53, %54, %55, %56, %57, %58, %59, %60, %61, %62, %63, %64, %65, %66, %67, %68, %69, %70, %71, %72, %73, %74, %75, %76, %77, %78, %79, %80, %81, %82, %83, %84, %85, %86, %87, %88, %89, %90, %91, %92, %93, %94, %95}, {%96, %97, %98, %99}, b, p, 1, 1, 1;\n}\n"
    : "+f"(d[0]), "+f"(d[1]), "+f"(d[2]), "+f"(d[3]), "+f"(d[4]), "+f"(d[5]), "+f"(d[6]), "+f"(d[7]), "+f"(d[8]), "+f"(d[9]), "+f"(d[10]), "+f"(d[11]), "+f"(d[12]), "+f"(d[13]), "+f"(d[14]), "+f"(d[15]), "+f"(d[16]), "+f"(d[17]), "+f"(d[18]), "+f"(d[19]), "+f"(d[20]), "+f"(d[21]), "+f"(d[22]), "+f"(d[23]), "+f"(d[24]), "+f"(d[25]), "+f"(d[26]), "+f"(d[27]), "+f"(d[28]), "+f"(d[29]), "+f"(d[30]), "+f"(d[31]), "+f"(d[32]), "+f"(d[33]), "+f"(d[34]), "+f"(d[35]), "+f"(d[36]), "+f"(d[37]), "+f"(d[38]), "+f"(d[39]), "+f"(d[40]), "+f"(d[41]), "+f"(d[42]), "+f"(d[43]), "+f"(d[44]), "+f"(d[45]), "+f"(d[46]), "+f"(d[47]), "+f"(d[48]), "+f"(d[49]), "+f"(d[50]), "+f"(d[51]), "+f"(d[52]), "+f"(d[53]), "+f"(d[54]), "+f"(d[55]), "+f"(d[56]), "+f"(d[57]), "+f"(d[58]), "+f"(d[59]), "+f"(d[60]), "+f"(d[61]), "+f"(d[62]), "+f"(d[63]), "+f"(d[64]), "+f"(d[65]), "+f"(d[66]), "+f"(d[67]), "+f"(d[68]), "+f"(d[69]), "+f"(d[70]), "+f"(d[71]), "+f"(d[72]), "+f"(d[73]), "+f"(d[74]), "+f"(d[75]), "+f"(d[76]), "+f"(d[77]), "+f"(d[78]), "+f"(d[79]), "+f"(d[80]), "+f"(d[81]), "+f"(d[82]), "+f"(d[83]), "+f"(d[84]), "+f"(d[85]), "+f"(d[86]), "+f"(d[87]), "+f"(d[88]), "+f"(d[89]), "+f"(d[90]), "+f"(d[91]), "+f"(d[92]), "+f"(d[93]), "+f"(d[94]), "+f"(d[95])
    : "r"(a0), "r"(a1), "r"(a2), "r"(a3), "l"(db), "r"(sd), "n"(OB));
}
template <int OA, int OB> __device__ __forceinline__ void wgmma_ss_tb(float (&d)[64], uint64_t da, uint64_t db, int sd) {
  asm volatile("{\n.reg .pred p;\n.reg .b64 a, b;\nadd.s64 a, %64, %67;\nadd.s64 b, %65, %68;\nsetp.ne.b32 p, %66, 0;\n"
    "wgmma.mma_async.sync.aligned.m64n128k16.f32.bf16.bf16 {%0, %1, %2, %3, %4, %5, %6, %7, %8, %9, %10, %11, %12, %13, %14, %15, %16, %17, %18, %19, %20, %21, %22, %23, %24, %25, %26, %27, %28, %29, %30, %31, %32, %33, %34, %35, %36, %37, %38, %39, %40, %41, %42, %43, %44, %45, %46, %47, %48, %49, %50, %51, %52, %53, %54, %55, %56, %57, %58, %59, %60, %61, %62, %63}, a, b, p, 1, 1, 0, 1;\n}\n"
    : "+f"(d[0]), "+f"(d[1]), "+f"(d[2]), "+f"(d[3]), "+f"(d[4]), "+f"(d[5]), "+f"(d[6]), "+f"(d[7]), "+f"(d[8]), "+f"(d[9]), "+f"(d[10]), "+f"(d[11]), "+f"(d[12]), "+f"(d[13]), "+f"(d[14]), "+f"(d[15]), "+f"(d[16]), "+f"(d[17]), "+f"(d[18]), "+f"(d[19]), "+f"(d[20]), "+f"(d[21]), "+f"(d[22]), "+f"(d[23]), "+f"(d[24]), "+f"(d[25]), "+f"(d[26]), "+f"(d[27]), "+f"(d[28]), "+f"(d[29]), "+f"(d[30]), "+f"(d[31]), "+f"(d[32]), "+f"(d[33]), "+f"(d[34]), "+f"(d[35]), "+f"(d[36]), "+f"(d[37]), "+f"(d[38]), "+f"(d[39]), "+f"(d[40]), "+f"(d[41]), "+f"(d[42]), "+f"(d[43]), "+f"(d[44]), "+f"(d[45]), "+f"(d[46]), "+f"(d[47]), "+f"(d[48]), "+f"(d[49]), "+f"(d[50]), "+f"(d[51]), "+f"(d[52]), "+f"(d[53]), "+f"(d[54]), "+f"(d[55]), "+f"(d[56]), "+f"(d[57]), "+f"(d[58]), "+f"(d[59]), "+f"(d[60]), "+f"(d[61]), "+f"(d[62]), "+f"(d[63])
    : "l"(da), "l"(db), "r"(sd), "n"(OA), "n"(OB));
}
template <int OB> __device__ __forceinline__ void wgmma_rs_tb(float (&d)[64], uint32_t a0, uint32_t a1, uint32_t a2, uint32_t a3, uint64_t db, int sd) {
  asm volatile("{\n.reg .pred p;\n.reg .b64 b;\nadd.s64 b, %68, %70;\nsetp.ne.b32 p, %69, 0;\n"
    "wgmma.mma_async.sync.aligned.m64n128k16.f32.bf16.bf16 {%0, %1, %2, %3, %4, %5, %6, %7, %8, %9, %10, %11, %12, %13, %14, %15, %16, %17, %18, %19, %20, %21, %22, %23, %24, %25, %26, %27, %28, %29, %30, %31, %32, %33, %34, %35, %36, %37, %38, %39, %40, %41, %42, %43, %44, %45, %46, %47, %48, %49, %50, %51, %52, %53, %54, %55, %56, %57, %58, %59, %60, %61, %62, %63}, {%64, %65, %66, %67}, b, p, 1, 1, 1;\n}\n"
    : "+f"(d[0]), "+f"(d[1]), "+f"(d[2]), "+f"(d[3]), "+f"(d[4]), "+f"(d[5]), "+f"(d[6]), "+f"(d[7]), "+f"(d[8]), "+f"(d[9]), "+f"(d[10]), "+f"(d[11]), "+f"(d[12]), "+f"(d[13]), "+f"(d[14]), "+f"(d[15]), "+f"(d[16]), "+f"(d[17]), "+f"(d[18]), "+f"(d[19]), "+f"(d[20]), "+f"(d[21]), "+f"(d[22]), "+f"(d[23]), "+f"(d[24]), "+f"(d[25]), "+f"(d[26]), "+f"(d[27]), "+f"(d[28]), "+f"(d[29]), "+f"(d[30]), "+f"(d[31]), "+f"(d[32]), "+f"(d[33]), "+f"(d[34]), "+f"(d[35]), "+f"(d[36]), "+f"(d[37]), "+f"(d[38]), "+f"(d[39]), "+f"(d[40]), "+f"(d[41]), "+f"(d[42]), "+f"(d[43]), "+f"(d[44]), "+f"(d[45]), "+f"(d[46]), "+f"(d[47]), "+f"(d[48]), "+f"(d[49]), "+f"(d[50]), "+f"(d[51]), "+f"(d[52]), "+f"(d[53]), "+f"(d[54]), "+f"(d[55]), "+f"(d[56]), "+f"(d[57]), "+f"(d[58]), "+f"(d[59]), "+f"(d[60]), "+f"(d[61]), "+f"(d[62]), "+f"(d[63])
    : "r"(a0), "r"(a1), "r"(a2), "r"(a3), "l"(db), "r"(sd), "n"(OB));
}
template <int OA, int OB> __device__ __forceinline__ void wgmma_ss_ta(float (&d)[64], uint64_t da, uint64_t db, int sd) {
  asm volatile("{\n.reg .pred p;\n.reg .b64 a, b;\nadd.s64 a, %64, %67;\nadd.s64 b, %65, %68;\nsetp.ne.b32 p, %66, 0;\n"
    "wgmma.mma_async.sync.aligned.m64n128k16.f32.bf16.bf16 {%0, %1, %2, %3, %4, %5, %6, %7, %8, %9, %10, %11, %12, %13, %14, %15, %16, %17, %18, %19, %20, %21, %22, %23, %24, %25, %26, %27, %28, %29, %30, %31, %32, %33, %34, %35, %36, %37, %38, %39, %40, %41, %42, %43, %44, %45, %46, %47, %48, %49, %50, %51, %52, %53, %54, %55, %56, %57, %58, %59, %60, %61, %62, %63}, a, b, p, 1, 1, 1, 0;\n}\n"
    : "+f"(d[0]), "+f"(d[1]), "+f"(d[2]), "+f"(d[3]), "+f"(d[4]), "+f"(d[5]), "+f"(d[6]), "+f"(d[7]), "+f"(d[8]), "+f"(d[9]), "+f"(d[10]), "+f"(d[11]), "+f"(d[12]), "+f"(d[13]), "+f"(d[14]), "+f"(d[15]), "+f"(d[16]), "+f"(d[17]), "+f"(d[18]), "+f"(d[19]), "+f"(d[20]), "+f"(d[21]), "+f"(d[22]), "+f"(d[23]), "+f"(d[24]), "+f"(d[25]), "+f"(d[26]), "+f"(d[27]), "+f"(d[28]), "+f"(d[29]), "+f"(d[30]), "+f"(d[31]), "+f"(d[32]), "+f"(d[33]), "+f"(d[34]), "+f"(d[35]), "+f"(d[36]), "+f"(d[37]), "+f"(d[38]), "+f"(d[39]), "+f"(d[40]), "+f"(d[41]), "+f"(d[42]), "+f"(d[43]), "+f"(d[44]), "+f"(d[45]), "+f"(d[46]), "+f"(d[47]), "+f"(d[48]), "+f"(d[49]), "+f"(d[50]), "+f"(d[51]), "+f"(d[52]), "+f"(d[53]), "+f"(d[54]), "+f"(d[55]), "+f"(d[56]), "+f"(d[57]), "+f"(d[58]), "+f"(d[59]), "+f"(d[60]), "+f"(d[61]), "+f"(d[62]), "+f"(d[63])
    : "l"(da), "l"(db), "r"(sd), "n"(OA), "n"(OB));
}
template <int OB> __device__ __forceinline__ void wgmma_rs(float (&d)[64], uint32_t a0, uint32_t a1, uint32_t a2, uint32_t a3, uint64_t db, int sd) {
  asm volatile("{\n.reg .pred p;\n.reg .b64 b;\nadd.s64 b, %68, %70;\nsetp.ne.b32 p, %69, 0;\n"
    "wgmma.mma_async.sync.aligned.m64n128k16.f32.bf16.bf16 {%0, %1, %2, %3, %4, %5, %6, %7, %8, %9, %10, %11, %12, %13, %14, %15, %16, %17, %18, %19, %20, %21, %22, %23, %24, %25, %26, %27, %28, %29, %30, %31, %32, %33, %34, %35, %36, %37, %38, %39, %40, %41, %42, %43, %44, %45, %46, %47, %48, %49, %50, %51, %52, %53, %54, %55, %56, %57, %58, %59, %60, %61, %62, %63}, {%64, %65, %66, %67}, b, p, 1, 1, 0;\n}\n"
    : "+f"(d[0]), "+f"(d[1]), "+f"(d[2]), "+f"(d[3]), "+f"(d[4]), "+f"(d[5]), "+f"(d[6]), "+f"(d[7]), "+f"(d[8]), "+f"(d[9]), "+f"(d[10]), "+f"(d[11]), "+f"(d[12]), "+f"(d[13]), "+f"(d[14]), "+f"(d[15]), "+f"(d[16]), "+f"(d[17]), "+f"(d[18]), "+f"(d[19]), "+f"(d[20]), "+f"(d[21]), "+f"(d[22]), "+f"(d[23]), "+f"(d[24]), "+f"(d[25]), "+f"(d[26]), "+f"(d[27]), "+f"(d[28]), "+f"(d[29]), "+f"(d[30]), "+f"(d[31]), "+f"(d[32]), "+f"(d[33]), "+f"(d[34]), "+f"(d[35]), "+f"(d[36]), "+f"(d[37]), "+f"(d[38]), "+f"(d[39]), "+f"(d[40]), "+f"(d[41]), "+f"(d[42]), "+f"(d[43]), "+f"(d[44]), "+f"(d[45]), "+f"(d[46]), "+f"(d[47]), "+f"(d[48]), "+f"(d[49]), "+f"(d[50]), "+f"(d[51]), "+f"(d[52]), "+f"(d[53]), "+f"(d[54]), "+f"(d[55]), "+f"(d[56]), "+f"(d[57]), "+f"(d[58]), "+f"(d[59]), "+f"(d[60]), "+f"(d[61]), "+f"(d[62]), "+f"(d[63])
    : "r"(a0), "r"(a1), "r"(a2), "r"(a3), "l"(db), "r"(sd), "n"(OB));
}
template <int OA, int OB> __device__ __forceinline__ void wgmma_ss_ta(float (&d)[4], uint64_t da, uint64_t db, int sd) {
  asm volatile("{\n.reg .pred p;\n.reg .b64 a, b;\nadd.s64 a, %4, %7;\nadd.s64 b, %5, %8;\nsetp.ne.b32 p, %6, 0;\n"
    "wgmma.mma_async.sync.aligned.m64n8k16.f32.bf16.bf16 {%0, %1, %2, %3}, a, b, p, 1, 1, 1, 0;\n}\n"
    : "+f"(d[0]), "+f"(d[1]), "+f"(d[2]), "+f"(d[3])
    : "l"(da), "l"(db), "r"(sd), "n"(OA), "n"(OB));
}

constexpr uint32_t U = 16384;
constexpr uint32_t SM_QO = 2 * U, SM_W = 8 * U, SM_V = 8 * U, SM_K1 = 12 * U, SM_BAR = 14 * U;
constexpr uint32_t B_WF = SM_BAR, B_KF = SM_BAR + 48, B_CF = SM_BAR + 80, B_GATE = SM_BAR + 128, B_OF = SM_BAR + 136, B_EP = SM_BAR + 144, B_EXT = SM_BAR + 152, B_Q3 = SM_BAR + 168, B_ANN = SM_BAR + 176,
                   B_WE = SM_BAR + 192, B_KE = SM_BAR + 240, B_CE = SM_BAR + 288, B_OS = SM_BAR + 344;
constexpr uint32_t SM_EP = SM_BAR + 384;
constexpr uint32_t SM_ONE = SM_BAR + 388;
constexpr uint32_t SM_STAT = SM_BAR + 400, SM_EXT = SM_STAT + 512;
constexpr uint32_t SM_BAD = SM_EXT + 2048;
constexpr int SMEM_BYTES = SM_BAR + 3072;
__device__ __forceinline__ uint32_t c_slot(int s) { return (0xBADC10u >> (4 * s)) & 15; }

struct Params {
  const __nv_bfloat16 *x, *k, *v, *wq, *wo, *wr;
  __nv_bfloat16* out;
  Scratch* g;
};

__device__ __forceinline__ void release2(uint32_t rbar, int lane) { if (lane < 2) mbar_arrive_cluster(rbar); }
__device__ __forceinline__ void pin_after(uint32_t a, float e0, float e1) {
  asm volatile("{\n.reg .pred p;\nsetp.lt.f32 p, %1, %2;\n@p st.shared.u32 [%0], %0;\n}\n" :: "r"(a), "f"(e0), "f"(-e1) : "memory"); }
__device__ __forceinline__ void lds128_after(uint32_t& x, uint32_t& y, uint32_t& z, uint32_t& w, uint32_t a, float e0, float e1) {
  asm volatile("{\n.reg .pred p;\nsetp.geu.f32 p, %5, %6;\n@p ld.shared.v4.u32 {%0,%1,%2,%3}, [%4];\n}\n" : "+r"(x), "+r"(y), "+r"(z), "+r"(w) : "r"(a), "f"(e0), "f"(-e1) : "memory"); }
__device__ __forceinline__ uint32_t launch_of(unsigned long long ticket) { return (uint32_t)(ticket / 132) + 1; }

__device__ __forceinline__ void attn_slow(float (&o)[64], float& i0, float& i1, const __nv_bfloat16* __restrict__ X, const __nv_bfloat16* __restrict__ WQ, uint32_t st0, uint32_t st1,
                                          const __nv_bfloat16* __restrict__ K, const __nv_bfloat16* __restrict__ V, int lane) {
  uint32_t q[32];
  #pragma unroll
  for (int i = 0; i < 64; i++) o[i] = 0.f;
  const int g = lane >> 2, qd = lane & 3;
  #pragma unroll 1
  for (int k0 = 0; k0 < DM; k0 += 16) {
    uint32_t a[4];
    #pragma unroll
    for (int e = 0; e < 4; e++) {
      const uint32_t xv = *(const uint32_t*)(X + (size_t)(g + (e & 1) * 8) * DM + k0 + (e >> 1) * 8 + 2 * qd);
      const float mb = bf_lo((e & 1) ? st1 : st0);
      a[e] = pack_bf16(bf_lo(xv) - mb, bf_hi(xv) - mb);
    }
    const unsigned short* wr = (const unsigned short*)(WQ + (size_t)(k0 + 2 * qd) * (NH * DH) + g);
    #pragma unroll
    for (int nb = 0; nb < 16; nb++) {
      uint32_t b0 = (uint32_t)wr[nb * 8] | ((uint32_t)wr[nb * 8 + NH * DH] << 16);
      uint32_t b1 = (uint32_t)wr[nb * 8 + 8 * NH * DH] | ((uint32_t)wr[nb * 8 + 9 * NH * DH] << 16);
      asm volatile("mma.sync.aligned.m16n8k16.row.col.f32.bf16.bf16.f32 {%0,%1,%2,%3}, {%4,%5,%6,%7}, {%8,%9}, {%0,%1,%2,%3};"
        : "+f"(o[nb*4]), "+f"(o[nb*4+1]), "+f"(o[nb*4+2]), "+f"(o[nb*4+3]) : "r"(a[0]), "r"(a[1]), "r"(a[2]), "r"(a[3]), "r"(b0), "r"(b1));
    }
  }
  {
    const float r0 = rcp_approx(bf_hi(st0)) * SCALE_LOG2E, r1 = rcp_approx(bf_hi(st1)) * SCALE_LOG2E;
    #pragma unroll
    for (int i = 0; i < 16; i++) { q[2*i] = pack_bf16(o[4*i] * r0, o[4*i+1] * r0); q[2*i+1] = pack_bf16(o[4*i+2] * r1, o[4*i+3] * r1); }
    #pragma unroll
    for (int i = 0; i < 64; i++) o[i] = 0.f;
  }
  float m0 = -INFINITY, m1 = -INFINITY, l0 = 0.f, l1 = 0.f;
  #pragma unroll 1
  for (int n0 = 0; n0 < S_LEN; n0 += 16) {
    float s[8];
    #pragma unroll
    for (int i = 0; i < 8; i++) s[i] = 0.f;
    #pragma unroll
    for (int nb = 0; nb < 2; nb++) {
      const uint32_t* kr = (const uint32_t*)(K + (size_t)(n0 + nb * 8 + g) * DH) + qd;
      #pragma unroll
      for (int kk = 0; kk < 8; kk++) {
        uint32_t b0 = kr[kk * 8], b1 = kr[kk * 8 + 4];
        asm volatile("mma.sync.aligned.m16n8k16.row.col.f32.bf16.bf16.f32 {%0,%1,%2,%3}, {%4,%5,%6,%7}, {%8,%9}, {%0,%1,%2,%3};"
          : "+f"(s[nb*4]), "+f"(s[nb*4+1]), "+f"(s[nb*4+2]), "+f"(s[nb*4+3]) : "r"(q[kk*4]), "r"(q[kk*4+1]), "r"(q[kk*4+2]), "r"(q[kk*4+3]), "r"(b0), "r"(b1));
      }
    }
    float x0 = fmaxf(fmaxf(s[0], s[1]), fmaxf(s[4], s[5])), x1 = fmaxf(fmaxf(s[2], s[3]), fmaxf(s[6], s[7]));
    x0 = fmaxf(x0, __shfl_xor_sync(0xffffffff, x0, 1)); x1 = fmaxf(x1, __shfl_xor_sync(0xffffffff, x1, 1));
    x0 = fmaxf(x0, __shfl_xor_sync(0xffffffff, x0, 2)); x1 = fmaxf(x1, __shfl_xor_sync(0xffffffff, x1, 2));
    const float n0m = fmaxf(m0, x0), n1m = fmaxf(m1, x1);
    const float sh0 = (n0m == -INFINITY) ? 0.f : n0m, sh1 = (n1m == -INFINITY) ? 0.f : n1m;
    const float c0 = ex2(m0 - sh0), c1 = ex2(m1 - sh1);
    m0 = n0m; m1 = n1m;
    s[0] = ex2(s[0] - sh0); s[1] = ex2(s[1] - sh0); s[4] = ex2(s[4] - sh0); s[5] = ex2(s[5] - sh0);
    s[2] = ex2(s[2] - sh1); s[3] = ex2(s[3] - sh1); s[6] = ex2(s[6] - sh1); s[7] = ex2(s[7] - sh1);
    l0 = l0 * c0 + (s[0] + s[1]) + (s[4] + s[5]); l1 = l1 * c1 + (s[2] + s[3]) + (s[6] + s[7]);
    const uint32_t a0 = pack_bf16(s[0], s[1]), a1 = pack_bf16(s[2], s[3]), a2 = pack_bf16(s[4], s[5]), a3 = pack_bf16(s[6], s[7]);
    const unsigned short* vr = (const unsigned short*)(V + (size_t)(n0 + 2 * qd) * DH + g);
    #pragma unroll
    for (int nb = 0; nb < 16; nb++) {
      uint32_t b0 = (uint32_t)vr[nb * 8] | ((uint32_t)vr[nb * 8 + DH] << 16);
      uint32_t b1 = (uint32_t)vr[nb * 8 + 8 * DH] | ((uint32_t)vr[nb * 8 + 9 * DH] << 16);
      o[nb*4] *= c0; o[nb*4+1] *= c0; o[nb*4+2] *= c1; o[nb*4+3] *= c1;
      asm volatile("mma.sync.aligned.m16n8k16.row.col.f32.bf16.bf16.f32 {%0,%1,%2,%3}, {%4,%5,%6,%7}, {%8,%9}, {%0,%1,%2,%3};"
        : "+f"(o[nb*4]), "+f"(o[nb*4+1]), "+f"(o[nb*4+2]), "+f"(o[nb*4+3]) : "r"(a0), "r"(a1), "r"(a2), "r"(a3), "r"(b0), "r"(b1));
    }
  }
  l0 += __shfl_xor_sync(0xffffffff, l0, 1); l1 += __shfl_xor_sync(0xffffffff, l1, 1);
  l0 += __shfl_xor_sync(0xffffffff, l0, 2); l1 += __shfl_xor_sync(0xffffffff, l1, 2);
  i0 = rcp_approx(l0); i1 = rcp_approx(l1);
}

__device__ __forceinline__ void flag_if(uint32_t a, bool c) { asm volatile("{\n.reg .pred p;\nsetp.ne.u32 p, %1, 0;\n@p st.shared.u8 [%0], 1;\n}\n" :: "r"(a), "r"((uint32_t)c) : "memory"); }
__device__ __forceinline__ void row_scale(float& l0, float& l1, int one, uint32_t flag) {
  l0 += __shfl_xor_sync(0xffffffff, l0, one); l1 += __shfl_xor_sync(0xffffffff, l1, one);
  l0 += __shfl_xor_sync(0xffffffff, l0, 2); l1 += __shfl_xor_sync(0xffffffff, l1, 2);
  flag_if(flag, !((l0 >= 0.00390625f) && (l0 <= 1.8446744e19f) && (l1 >= 0.00390625f) && (l1 <= 1.8446744e19f)));
  l0 = rcp_fast(l0); l1 = rcp_fast(l1);
}
__device__ __forceinline__ uint32_t taint(uint32_t z, uint32_t a, uint32_t b) { asm("fma.rn.bf16x2 %0, %1, %2, %0;" : "+r"(z) : "r"(a), "r"(b)); return z; }
__device__ __forceinline__ bool tainted(uint32_t z) { return (taint(0u, z, 0u) & 0x7fff7fffu) != 0; }

__device__ __forceinline__ uint32_t qo_slot(int h) { return SM_QO + ((0x3102 >> (4 * h)) & 3) * 2 * U; }
__device__ __forceinline__ uint32_t o_addr(uint32_t wr, int lane) { return wr + (lane & 15) * 128 + (((lane >> 4) ^ (lane & 7)) << 4); }
template <bool CHECK> __device__ __forceinline__ uint32_t store_o(uint32_t a, const float (&o)[64], float i0, float i1) {
  uint32_t z = 0;
  #pragma unroll
  for (int i = 0; i < 8; i++) {
    const uint32_t w0 = pack_bf16(o[8*i] * i0, o[8*i+1] * i0), w1 = pack_bf16(o[8*i+2] * i1, o[8*i+3] * i1), w2 = pack_bf16(o[8*i+4] * i0, o[8*i+5] * i0), w3 = pack_bf16(o[8*i+6] * i1, o[8*i+7] * i1);
    stsm4((a ^ ((i & 3) << 5)) + (i >> 2) * U, w0, w1, w2, w3);
    if (CHECK) z = taint(taint(z, w0, w1), w2, w3);
  }
  return z;
}

__device__ __noinline__ void redo_heads(const Params& P, uint32_t sb, uint32_t bad, int row0, int head0) {
  const int lane = threadIdx.x & 31;
  const uint32_t st0 = lds32(sb + SM_STAT + ((row0 & 127) + (lane >> 2)) * 4), st1 = lds32(sb + SM_STAT + ((row0 & 127) + 8 + (lane >> 2)) * 4);
  #pragma unroll 1
  for (int h = 0; h < 4; h++) {
    if (!((bad >> (8 * h)) & 1)) continue;
    float o[64], i0, i1;
    attn_slow(o, i0, i1, P.x + (size_t)row0 * DM, P.wq + (head0 + h) * DH, st0, st1, P.k + (size_t)(head0 + h) * S_LEN * DH, P.v + (size_t)(head0 + h) * S_LEN * DH, lane);
    store_o<false>(o_addr(sb + (row0 & 127) * 128, lane) + qo_slot(h), o, i0, i1);
  }
}

template <int K> struct IC { static constexpr int v = K; };
template <int K, int N, class F> __device__ __forceinline__ void static_for(F&& f) { if constexpr (K < N) { f(IC<K>{}); static_for<K + 1, N>(f); } }
template <uint32_t OFF, int SITE> __device__ __forceinline__ void mma_qk(float (&s)[64], const uint32_t (&q)[32], uint64_t d0) {
  wg_fence();
  static_for<0, 8>([&](auto kc) { constexpr int k = decltype(kc)::v; wgmma_rs<doff(OFF, 16) - SITE + (k / 4) * 1024 + (k % 4) * 2>(s, q[k*4], q[k*4+1], q[k*4+2], q[k*4+3], d0, k > 0); });
  wg_commit();
}
template <uint32_t OFF, int SITE> __device__ __forceinline__ void mma_pv(float (&o)[64], const uint32_t (&p)[32], uint64_t d0, bool keep) {
  wg_fence();
  static_for<0, 8>([&](auto kc) { constexpr int k = decltype(kc)::v; wgmma_rs_tb<doff(OFF, U) - SITE + k * 128>(o, p[k*4], p[k*4+1], p[k*4+2], p[k*4+3], d0, (k > 0) || keep); });
  wg_commit();
}
template <int I0, int I1>
__device__ __forceinline__ void exp_rows(float (&s)[64], float (&l)[2]) {
  #pragma unroll
  for (int i = I0; i < I1; i += 2) {
    s[i] = ex2(s[i]); s[i+1] = ex2(s[i+1]);
    l[(i >> 1) & 1] += s[i] + s[i+1];
  }
}

template <int KS, bool EDGE>
__device__ __forceinline__ void attn_step(uint32_t sb, uint32_t rb, uint32_t wr, uint32_t qa, int wg, int lane, int j, int ph, float (&s)[64], float (&o)[64], uint32_t (&p)[32], uint32_t (&q)[32],
                                          float (&l)[2], bool& ready, Scratch* g, unsigned (&tz)[3]) {
  constexpr bool FIRST = EDGE && !KS, LAST = EDGE && KS;
  TRACEF(2, wg, 32 + j);
  STALL(1);
  if (!ready) {
    mbar_wait(sb + B_KF + 24 - KS * 8, KS ? ph : ph ^ 1);
    mbar_wait(sb + B_KF + KS * 8, ph);
  }
  bar_sync(1 + wg, 256);
  mma_qk<KS * SM_K1, EDGE>(s, q, desc(sb, EDGE));
  mma_pv<SM_V + (1 - KS) * 2 * U, EDGE>(o, p, desc(sb, EDGE), !KS || LAST || ((j & 15) != 1));
  bar_arrive(1 + (wg ^ 1), 256);
  const int one = FIRST ? lds32(sb + SM_ONE) : 1;
  wg_wait<1>();
  fence_regs(s);
  release2(rb + B_KE + KS * 8, lane);
  float i0 = l[0], i1 = l[1];
  if (FIRST) { row_scale(i0, i1, one, sb + SM_BAD - 1 + ((wr - sb) >> 9) + (j >> 4)); l[0] = fminf(i0, 0.f); l[1] = fminf(i1, 0.f); }
  constexpr int DP = FIRST ? DPOSF : (LAST && DPOS < 7 * QSP ? 7 * QSP : DPOS);
  if (LAST) {
    fence_regs(q);
    const uint32_t a = qa + qo_slot(j >> 4);
    static_for<0, 8>([&](auto ic) { constexpr int i = decltype(ic)::v;
      lds128_after(q[4*i], q[4*i+1], q[4*i+2], q[4*i+3], a + (i >> 2) * U + (i & 3) * 512, l[0], l[1]);
      exp_rows<i * QSP, i < 7 ? (i + 1) * QSP : DP>(s, l);
    });
  } else exp_rows<0, DP>(s, l);
  pin_after(sb + SM_BAD, l[0], l[1]);
  exp_rows<DP, 64>(s, l);
  wg_wait<0>();
  fence_regs(o); fence_regs(p);
  release2(rb + B_KE + 24 - KS * 8, lane);
  ready = mbar_test2(sb + B_KF + 16 + KS * 8, ph, sb + B_KF + 8 - KS * 8, KS ? ph ^ 1 : ph);
  if (FIRST) {
    const int h = (j >> 4) - 1;
    store_o<false>(o_addr(wr, lane) + qo_slot(h), o, i0, i1);
    if (lane == 0) mbar_arrive(sb + B_OS + h * 8);
  }
  #pragma unroll
  for (int i = 0; i < 32; i++) p[i] = pack_bf16(s[2*i], s[2*i+1]);
}

template <int SITE> __device__ __forceinline__ void mma_c(float (&acc)[64], uint32_t sb, int slot, int h, int arrive_bar) {
  const uint64_t a = desc(sb, c_slot(slot) * 1024 + SITE), b = desc(sb, h * 2048 + SITE);
  wg_fence();
  static_for<0, 8>([&](auto kc) { constexpr int k = decltype(kc)::v;
    if (k == C_EARLY && arrive_bar) bar_arrive(arrive_bar, 256);
    wgmma_ss_ta<doff(0, 16) - SITE + k * 128, doff(SM_QO, 16) - SITE + (k >> 2) * 1024 + (k & 3) * 2>(acc, a, b, k > 0 || h > 0);
  });
  wg_commit();
}

__device__ __forceinline__ void side_cta(const Params& P, const CUtensorMap* tmX, const CUtensorMap* tmW, const CUtensorMap* tmG, const CUtensorMap* tmU,
                                         const CUtensorMap* tmD, uint32_t sb, int m) {
  const int tid = threadIdx.x, warp = __shfl_sync(0xffffffff, tid >> 5, 0), lane = tid & 31;
  const uint32_t XS = sb + 12 * U, HS = XS + 10240, BF = sb + SM_BAR, BE = BF + 96, XF = BE + 96, XE = XF + 32, BW = XE + 32, SEL = BW + 16, KEY = SEL + 64;
  Scratch* const g = P.g;
  const int nj = m < 3 ? 14 : 12, nd = m < 3 ? 4 : 3, f0 = m * 448;
  if (elect_one()) { mbar_init(BF + warp * 8, 1); mbar_init(BE + warp * 8, 4); if (warp < 9) mbar_init(XF + warp * 8, (warp & 4) ? 8 : 1); }
  if (tid == 32) sts32(SEL + 32, launch_of(atomicAdd(&g->ticket, 1ull)));
  __syncthreads();
  const uint32_t launch = lds32(SEL + 32);
  if (warp == 0) {
    if (elect_one()) {
      mbar_expect_tx(BW, 10 * U);
      #pragma unroll 1
      for (int i = 0; i < 10; i++) tma_load_2d(sb + i * U, tmW, BW, m * 1024 + (i < 5 ? 448 : 960), (i < 5 ? i : i - 5) * 128);
    }
    #pragma unroll 1
    for (int n = 0, qt = 0, c = 0; n < 160; n++) {
      const uint32_t bar = XF + (n & 3) * 8;
      mbar_wait(bar + 32, ((n >> 2) & 1) ^ 1);
      if (elect_one()) {
        mbar_expect_tx(bar, U);
        tma_load_2d(sb + (10 + (n & 3)) * U, tmX, bar, c * 64, qt * 128);
        if (c == 0 && qt < 15) l2_prefetch(P.x + (size_t)(qt * 128 + 128 + m * 32) * DM, 32 * DM * 2);
      }
      if (++c == 10) { c = 0; qt++; }
    }
  } else if (warp == 1) {
    #pragma unroll 1
    for (int qt = 0; qt < 16; qt++) {
      bar_sync(2, 288);
      if (lane == 0) asm volatile("fence.acq_rel.gpu;\nst.relaxed.gpu.global.u32 [%0], %1;" :: "l"(&g->q3_done[m].v), "r"(launch * 16 + qt + 1) : "memory");
    }
  } else if (warp >= 4) {
    float acc[64], cs[32];
    mbar_wait(BW, 0);
    #pragma unroll 1
    for (int c = 0; c < 10; c++) {
      wg_fence();
      static_for<0, 4>([&](auto kc) { constexpr int k = decltype(kc)::v;
        wgmma_rs_tb<doff(0, 5 * U) + k * 128>(acc, 0x3f803f80u, 0x3f803f80u, 0x3f803f80u, 0x3f803f80u, desc(sb, c * 512), k || c); });
      wg_commit();
      wg_wait<0>();
    }
    fence_regs(acc);
    #pragma unroll
    for (int i = 0; i < 32; i++) cs[i] = -acc[(i >> 1) * 4 + (i & 1)];
    fence_regs(cs);
    #pragma unroll 1
    for (int qt = 0, n = 0; qt < 16; qt++) {
      const uint32_t* const sp = g->stat + qt * 128 + (warp - 4) * 16 + (lane >> 2);
      uint32_t st0, st1;
      #pragma unroll 1
      for (int c = 0; c < 10; c++, n++) {
        const uint64_t a = desc(sb, (n & 3) * 1024 + (warp >> 3) * 512), b = desc(sb, c * 512);
        mbar_wait(XF + (n & 3) * 8, (n >> 2) & 1);
        wg_fence();
        static_for<0, 4>([&](auto kc) { constexpr int k = decltype(kc)::v; wgmma_ss_tb<doff(10 * U, 16) + k * 2, doff(0, 5 * U) + k * 128>(acc, a, b, k || c); });
        wg_commit();
        if (c == 9) { st0 = ldg32(sp); st1 = ldg32(sp + 8); }
        wg_wait<1>();
        if (c && lane == 0) mbar_arrive(XE + ((n - 1) & 3) * 8);
      }
      #pragma unroll 1
      for (int it = 0; __any_sync(0xffffffff, tag_miss(st0, st1, launch << 31) >> 31) && it < MAXPOLL; it++) { st0 = ldg32(sp); st1 = ldg32(sp + 8); }
      st0 &= 0x7fffffffu; st1 &= 0x7fffffffu;
      const float rs[2] = {rcp_approx(bf_hi(st0)) * SCALE_LOG2E, rcp_approx(bf_hi(st1)) * SCALE_LOG2E}, nm[2] = {bf_lo(st0), bf_lo(st1)};
      wg_wait<0>();
      fence_regs(acc);
      if (lane == 0) mbar_arrive(XE + ((n - 1) & 3) * 8);
      STALL(7);
      uint4* const dst = g->q3 + (qt * 8 + m * 2) * 1024 + (warp - 4) * 128 + lane;
      #pragma unroll
      for (int e = 0; e < 8; e++) {
        uint32_t w[4];
        #pragma unroll
        for (int i = 0; i < 4; i++)
          w[i] = pack_bf16(fmaf(nm[i & 1], cs[4*e + (i & 2)], acc[8*e + 2*i]) * rs[i & 1], fmaf(nm[i & 1], cs[4*e + (i & 2) + 1], acc[8*e + 2*i + 1]) * rs[i & 1]);
        dst[(e >> 2) * 1024 + (e & 3) * 32] = make_uint4(w[0], w[1], w[2], w[3]);
      }
      bar_sync(2, 288);
    }
  }
  if (tid == 64) flag_wait(&g->cnt_gate.v, launch * 256);
  __syncthreads();
  TRACE(0, 1);
  if (tid >= 256 && tid < 320) sts128(HS + 3072 + tid * 16, 0, 0, 0, 0);
  if (warp < 4) {
    uint4 k4[4];
    #pragma unroll
    for (int i = 0; i < 4; i++) k4[i] = ld_relaxed4(g->key + warp * 512 + i * 128 + lane * 4);
    uint32_t bound = 0;
    #pragma unroll 1
    for (int c = 0; c < TOPC; c++) {
      uint32_t b = 0;
      #pragma unroll
      for (int i = 0; i < 4; i++) b = max(max(max(b, k4[i].x - bound), k4[i].y - bound), max(k4[i].z - bound, k4[i].w - bound));
      bound += __reduce_max_sync(0xffffffff, b);
      if (lane == 0) sts32(KEY + (warp * TOPC + c) * 4, bound);
    }
    bar_sync(1, 128);
    const uint32_t v = lds32(KEY + lane * 4);
    int n = 0;
    #pragma unroll 1
    for (int j = 0; j < 32; j++) n += __shfl_sync(0xffffffff, v, j) > v;
    if (n < TOPC) sts32(SEL + n * 4, v);
  }
  __syncthreads();
  #pragma unroll 1
  for (int i = tid; i < TOPC * 80; i += 384) {
    const int row = 0xffff - (lds32(SEL + (i & 7) * 4) & 0xffff);
    const uint32_t st = ldg32(g->stat + row), m2 = __byte_perm(st, 0, 0x1010);
    const float rsd = rcp_approx(bf_hi(st & 0x7fffffffu));
    const uint4 v = ldg_nc((const uint4*)(P.x + (size_t)row * DM) + (i >> 3));
    sts128(XS + i * 16, norm2(v.x, m2, rsd), norm2(v.y, m2, rsd), norm2(v.z, m2, rsd), norm2(v.w, m2, rsd));
  }
  proxy_fence();
  __syncthreads();
  TRACE(0, 2);
  uint32_t sl = 0, ph = 0;
  if (warp == 0) {
    #pragma unroll 1
    for (int job = 0; job < nj + 10; job++) {
      const bool up = job < nj;
      #pragma unroll 1
      for (int i = 0; i < (up ? 5 : nd); i++) {
        mbar_wait(BE + sl * 8, ph ^ 1);
        if (elect_one()) {
          mbar_expect_tx(BF + sl * 8, U);
          tma_load_2d(sb + sl * U, up ? ((job & 1) ? tmU : tmG) : tmD, BF + sl * 8, up ? f0 + (job >> 1) * 64 : (job - nj) * 64, (up ? 0 : f0) + i * 128);
        }
        if (++sl == 12) { sl = 0; ph ^= 1; }
      }
    }
  } else if ((warp >> 2) == 1) {
    float gs[4];
    #pragma unroll 1
    for (int job = 0; job < nj + 10; job++) {
      const bool up = job < nj;
      if (job == nj) { proxy_fence(); bar_sync(1, 128); }
      float ac[4][4], acc[4];
      uint32_t prev = 0;
      #pragma unroll 1
      for (int i = 0; i < (up ? 5 : nd); i++) {
        const uint64_t a = desc(sb, sl * 1024 + 0x10000), b = (uint64_t)(desc_lo(up ? XS : HS, 128) + i * 128) | (8ull << 32);
        mbar_wait(BF + sl * 8, ph);
        wg_fence();
        static_for<0, 8>([&](auto kc) { constexpr int k = decltype(kc)::v; wgmma_ss_ta<k * 128, k * 16>(ac[k & 3], a, b, k > 3 || i > 0); });
        wg_commit();
        wg_wait<1>();
        if (i && lane == 0) mbar_arrive(prev);
        prev = BE + sl * 8;
        if (++sl == 12) { sl = 0; ph ^= 1; }
      }
      wg_wait<0>();
      if (lane == 0) mbar_arrive(prev);
      #pragma unroll
      for (int e = 0; e < 4; e++) fence_regs(ac[e]);
      #pragma unroll
      for (int e = 0; e < 4; e++) acc[e] = (ac[0][e] + ac[1][e]) + (ac[2][e] + ac[3][e]);
      STALL(9);
      const int f = (warp & 3) * 16 + (lane >> 2), tk = (lane & 3) * 2;
      if (!up) {
        float* y = g->ypart + (m * DM + (job - nj) * 64 + f) * TOPC + tk;
        *(float2*)y = make_float2(acc[0], acc[1]); *(float2*)(y + 8 * TOPC) = make_float2(acc[2], acc[3]);
      } else {
        #pragma unroll
        for (int e = 0; e < 4; e++) {
          const float z = rbf(acc[e]);
          if (job & 1) asm volatile("st.shared.u16 [%0], %1;" :: "r"(HS + (job >> 1) * 1024 + ((f >> 3) + (e >> 1)) * 128 + (tk + (e & 1)) * 16 + (f & 7) * 2), "h"((uint16_t)pack_bf16(gs[e] * z, 0.f)) : "memory");
          gs[e] = rbf(z * sigmoid_f(z));
        }
      }
    }
  }
  __syncthreads();
  TRACE(0, 3);
  if (tid == 0) { flag_add_release(&g->cnt_mod.v); flag_wait(&g->cnt_mod.v, launch * 4, 50); }
  __syncthreads();
  #pragma unroll 1
  for (int i = tid; i < 2 * DM; i += 384) {
    const int t = 2 * m + (i & 1), col = i >> 1;
    const uint32_t key = lds32(SEL + t * 4);
    const float* yp = g->ypart + col * TOPC + t;
    const float y = rbf((__ldcg(yp) + __ldcg(yp + TOPC * DM)) + (__ldcg(yp + 2 * TOPC * DM) + __ldcg(yp + 3 * TOPC * DM)));
    const float rs = rbf(sigmoid_f(bf_hi((key >> 31) ? key & 0x7fffffffu : ~key)));
    const uint32_t xn = lds32(XS + (col >> 3) * 128 + t * 16 + (col & 6) * 2);
    const float z = rbf(((col & 1) ? bf_hi(xn) : bf_lo(xn)) + rbf(y * rs));
    g->gate[(size_t)(0xffff - (key & 0xffff)) * DM + col] = __float2bfloat16_rn(z * sigmoid_f(z));
  }
  __syncthreads();
  if (tid == 0) flag_add_release(&g->mod_done.v);
  TRACE(0, 4);
}

__global__ void __cluster_dims__(2, 1, 1) __launch_bounds__(384, 1) fused_kernel(const __grid_constant__ CUtensorMap tmX, const __grid_constant__ CUtensorMap tmW4,
    const __grid_constant__ CUtensorMap tmW3, const __grid_constant__ CUtensorMap tmW1,
    const __grid_constant__ CUtensorMap tmK, const __grid_constant__ CUtensorMap tmV, const __grid_constant__ CUtensorMap tmWO,
    const __grid_constant__ CUtensorMap tmG, const __grid_constant__ CUtensorMap tmU, const __grid_constant__ CUtensorMap tmD,
    const __grid_constant__ CUtensorMap tmGate, const __grid_constant__ Params P) {
  extern __shared__ __align__(1024) uint8_t smem_raw[];
  const uint32_t sb = smem_u32(smem_raw);
  const int tid = threadIdx.x, lane = tid & 31;
  const int rank = blockIdx.x & 1, cl = blockIdx.x >> 1;
  if (cl >= 64) {
    side_cta(P, &tmX, &tmW1, &tmG, &tmU, &tmD, sb, blockIdx.x & 3);
    return;
  }
  const int rr = ((cl - 36) * 37) >> 8, kk = cl - 36 - rr * 7, qp = sel_lt(cl, 4, PH, sel_lt(cl, 36, (cl - 4) & 7, kk + sel_lt(kk, PH, 0, 1)));
  const int hg = sel_lt(cl, 4, cl + 4, sel_lt(cl, 36, (cl - 4) >> 3, 4 + rr)), qt = qp * 2 + rank;
  const int warp = __shfl_sync(0xffffffff, tid >> 5, 0), wgi = warp >> 2;
  Scratch* const g = P.g;
  if (elect_one()) {
    #pragma unroll
    for (int i = 0; i < 4; i++) mbar_init(sb + SM_BAR + warp * 32 + i * 8, 1 << ((0x333444000000ull >> (4 * warp)) & 7));
    if (warp == 0) {
      mbar_expect_tx(sb + B_WF, 2 * U);
      tma_load_2d(sb + 2 * U, &tmX, sb + B_WF, 0, qt * 128);
      tma_load_3d(sb + SM_W, &tmW4, sb + B_WF, 0, 0, hg * 8);
      tma_load_3d(sb + SM_W + 8192, &tmW4, sb + B_WF, 0, 16, hg * 8);
    }
    asm volatile("fence.mbarrier_init.release.cluster;" ::: "memory");
  }
  __syncwarp();
  cluster_arrive();
  unsigned long long ticket = 0;
  if (tid == 64) asm volatile("atom.relaxed.gpu.global.add.u64 %0, [%1], 1;" : "=l"(ticket) : "l"(&g->ticket) : "memory");
  cluster_wait();
  if (warp == 0 && elect_one()) {
    #pragma unroll
    for (int i = 1; i < 6; i++) {
      mbar_expect_tx(sb + B_WF + i * 8, (i & 1) ? U : 2 * U);
      tma_load_3d_mc(sb + SM_W + i * U + rank * 8192, &tmW4, sb + B_WF + i * 8, 0, i * 32 + rank * 16, hg * 8);
      if (!(i & 1)) tma_load_2d(sb + (2 + i / 2) * U, &tmX, sb + B_WF + i * 8, i * 32, qt * 128);
    }
  }
  STALL(14);
  if (wgi == 0) {
    asm volatile("setmaxnreg.dec.sync.aligned.u32 56;");
    uint32_t w0 = 0;
    if (warp == 1 || warp == 2) {
      if (warp == 2 && lane < 12) sts128(sb + SM_EXT + 1024 + (lane >= 6 ? 1024 - 96 : 0) + lane * 16, 0, 0, 0, 0);
      __syncwarp();
      if (tid == 64) { sts32(sb + SM_ONE, 1); sts32(sb + SM_EP, launch_of(ticket)); mbar_arrive(sb + B_EP); }
      __syncwarp();
      mbar_pace(sb + B_WF, 0);
      TRACEO(1);
      auto warm = [&](int ps, int i0, int i1) {
        const uint32_t o = (((qt >> 2) * 4 + (lane & 3) + (lane >> 2) * 16) * (NH * DH) + hg * 512 + ps * 256 + (qt & 3) * 64) * 2;
        #pragma unroll 1
        for (int i = i0; i < i1; i++) {
          asm volatile("prefetch.global.L2 [%0];" :: "l"(at<char>(P.wq, o + i * 256 * (NH * DH))) : "memory");
          if (ps) __nanosleep(W1SL);
        }
      };
      if (elect_one()) l2_prefetch(P.x + (size_t)(qt * 128 + hg * 16 + warp * 8 - 6) * DM, 6 * DM * 2);
      if (warp == 1) warm(0, 1, 5);
      auto publish = [&](uint32_t w) { if (!(lane & 12)) st_relaxed(at<uint32_t>(g->stat, (qt * 128 + hg * 16 + (warp - 1) * 8 + (lane & 3) * 2 + (lane >> 4)) * 4), w ^ (lds32(sb + SM_EP) << 31)); };
      mbar_wait(sb + B_EP, 0);
      publish(0x80000000u);
      const int r0 = qt * 128 + hg * 16 + (warp - 1) * 8 + (lane >> 4);
      const uint32_t e = r0 * DM * 2 + (lane & 15) * 16;
      uint4 vn[5];
      #pragma unroll
      for (int i = 0; i < 5; i++) vn[i] = ldg_nc(at<uint4>(P.x, e) + i * 16);
      #pragma unroll 1
      for (int it = 0; it < 4; it++) {
        uint4 v[5];
        #pragma unroll
        for (int i = 0; i < 5; i++) { v[i] = vn[i]; if (it < 3) vn[i] = ldg_nc(at<uint4>(P.x, e + (it + 1) * 2560) + i * 16); }
        const float x0 = bf_lo(__shfl_sync(0xffffffff, v[0].x, lane & 16));
        float m1 = 0.f, s1 = 0.f;
        #pragma unroll
        for (int i = 0; i < 5; i++) {
          const uint32_t vw[4] = {v[i].x, v[i].y, v[i].z, v[i].w};
          #pragma unroll
          for (int k = 0; k < 4; k++) { const float d0 = bf_lo(vw[k]) - x0, d1 = bf_hi(vw[k]) - x0; m1 += d0 + d1; s1 = fmaf(d0, d0, fmaf(d1, d1, s1)); }
        }
        #pragma unroll
        for (int o = 8; o; o >>= 1) { m1 += __shfl_xor_sync(0xffffffff, m1, o); s1 += __shfl_xor_sync(0xffffffff, s1, o); }
        const float md = m1 * (1.f / DM), var = fmaxf(fmaf(-md, md, s1 * (1.f / DM)), 0.f);
        if ((lane & 15) == it) w0 = pack_bf16(x0 + md, sqrt_approx(rbf(rbf(var) + 1e-5f)));
      }
      STALL(5);
      publish(w0 & 0x7fffffffu);
      TRACE1(2, 8);
      if (warp == 1 && W1SL) warm(1, 0, 5);
    }
        if (warp >= 2) {
      const int ps = 3 - warp;
      {
        const uint4* src = at<uint4>(P.wq, (((qt >> 2) * 4 + (lane >> 3)) * (NH * DH) + hg * 512 + ps * 256 + (qt & 3) * 64 + (lane & 7) * 8) * 2);
        const uint32_t mine = ((hg * 2 + ps) * 256 + qt * 16 + (lane & 7) * 2 + (lane >> 4)) * 16;
        float cs[8];
        #pragma unroll
        for (int e = 0; e < 8; e++) cs[e] = 0.f;
        #pragma unroll 1
        for (int b = 0; b < 40 / CSB; b++, src += CSB * 16 * 512) {
          uint4 w[CSB];
          #pragma unroll
          for (int i = 0; i < CSB; i++) w[i] = ldg_nc(src + i * 16 * 512);
          #pragma unroll
          for (int i = 0; i < CSB; i++) add8(cs, w[i]);
          if (b == 0) {
            mbar_wait(sb + B_EP, 0);
            if (!(lane & 8)) st_tagged(at<uint4>(g->cs, mine), ~lds32(sb + SM_EP) & 1, 0, 0, 0);
          }
        }
        #pragma unroll
        for (int e = 0; e < 4; e++) {
          cs[e] = ((lane & 16) ? cs[e + 4] : cs[e]) + __shfl_xor_sync(0xffffffff, (lane & 16) ? cs[e] : cs[e + 4], 16);
          cs[e] += __shfl_xor_sync(0xffffffff, cs[e], 8);
        }
        STALL(6);
        mbar_wait(sb + B_EP, 0);
        const uint32_t tm = 0u - (lds32(sb + SM_EP) & 1);
        const uint4* const gc = at<uint4>(g->cs, ((hg * 2 + ps) * 256 + lane) * 16);
        if (!(lane & 8)) st_tagged(at<uint4>(g->cs, mine), (__float_as_uint(cs[0]) & ~1u) | (tm & 1), __float_as_uint(cs[1]), __float_as_uint(cs[2]), __float_as_uint(cs[3]));

        uint4 v[9];
        int it = 0;
        uint32_t miss;
        do {
          #pragma unroll
          for (int i = 0; i < 8; i++) v[i] = ld_tagged(gc + i * 32);
          v[8] = ld_relaxed4(at<uint4>(g->stat, qt * 512 + lane * 16));
          miss = (tag_miss(v[8].x, v[8].y, tm) | tag_miss(v[8].z, v[8].w, tm)) >> 31;
          #pragma unroll
          for (int i = 0; i < 8; i += 2) miss |= tag_miss(v[i].x, v[i+1].x, tm);
        } while (__any_sync(0xffffffff, miss & 1) && ++it < MAXPOLL);
        #pragma unroll
        for (int i = 0; i < 2; i++) {
          auto sum = [](uint32_t a, uint32_t b, uint32_t c, uint32_t d) { return (__uint_as_float(a) + __uint_as_float(b)) + (__uint_as_float(c) + __uint_as_float(d)); };
          const float c0 = sum(v[i].x, v[i+2].x, v[i+4].x, v[i+6].x), c1 = sum(v[i].y, v[i+2].y, v[i+4].y, v[i+6].y);
          const float c2 = sum(v[i].z, v[i+2].z, v[i+4].z, v[i+6].z), c3 = sum(v[i].w, v[i+2].w, v[i+4].w, v[i+6].w);
          const uint32_t h0 = pack_bf16(c0, c1), h1 = pack_bf16(c2, c3), a = sb + SM_EXT + ps * 1024 + i * 512 + (lane >> 1) * 32 + (lane & 1) * 8;
          asm volatile("st.shared.v2.u32 [%0], {%1,%2};" :: "r"(a), "r"(h0), "r"(h1) : "memory");
          asm volatile("st.shared.v2.u32 [%0], {%1,%2};" :: "r"(a + 16), "r"(pack_bf16(c0 - bf_lo(h0), c1 - bf_hi(h0))), "r"(pack_bf16(c2 - bf_lo(h1), c3 - bf_hi(h1))) : "memory");
        }
        sts128(sb + SM_STAT + lane * 16, v[8].x & 0x7fffffffu, v[8].y & 0x7fffffffu, v[8].z & 0x7fffffffu, v[8].w & 0x7fffffffu);
        proxy_fence();
        __syncwarp();
        if (lane == 0) mbar_arrive(sb + B_EXT + ps * 8);
        TRACE1(2, 6 + ps);
        if (elect_one()) l2_prefetch(at<char>(ps ? P.v : P.k, (hg * 4 * S_LEN + qt * (16 + 8 * KVPF)) * DH * 2), 4096 + 2048 * KVPF);
      }
    }
    if (warp == 1 || warp == 2) {
      int j = 0;
      const int r0 = qt * 128 + hg * 16 + (warp - 1) * 8 + (lane >> 4);
      uint32_t e = r0 * DM * 2 + (lane & 15) * 16;
      uint4 xn = ldg_nc(at<uint4>(P.x, e)), wn = ldg_nc(at<uint4>(P.wr, (lane & 15) * 16));
      #pragma unroll 1
      for (int it = 0; it < 4; it++) {
        const uint32_t st = __shfl_sync(0xffffffff, w0, (lane & 16) + it), m2 = __byte_perm(st, 0, 0x1010);
        const float rsd = rcp_approx(bf_hi(st));
        float a = 0.f;
        #pragma unroll 1
        for (int i = 0; i < 5; i++) {
          #pragma unroll 1
          do { mbar_pace(sb + B_KE + (j & 1) * 8, (j >> 1) & 1); j++; } while (j < 3 || (j >= 15 && j < 20));
          STALL(8);
          uint32_t z[4] = {xn.x, xn.y, xn.z, xn.w};
          const uint32_t ww[4] = {wn.x, wn.y, wn.z, wn.w}, en = e + (i < 4 ? 256 : (it < 3 ? 1536 : 0));
          xn = ldg_nc(at<uint4>(P.x, en)); wn = ldg_nc(at<uint4>(P.wr, (i < 4 ? i * 256 + 256 : 0) + (lane & 15) * 16));
          #pragma unroll
          for (int k = 0; k < 4; k++) {
            const uint32_t n = norm2(z[k], m2, rsd);
            const float lo = bf_lo(n), hi = bf_hi(n);
            a = fmaf(lo, bf_lo(ww[k]), fmaf(hi, bf_hi(ww[k]), a));
            z[k] = pack_bf16(lo * sigmoid_f(lo), hi * sigmoid_f(hi));
          }
          stg128(at<uint4>(g->gate, e), make_uint4(z[0], z[1], z[2], z[3]));
          e = en;
        }
        #pragma unroll
        for (int o = 8; o; o >>= 1) a += __shfl_xor_sync(0xffffffff, a, o);
        uint32_t u = pack_bf16(a, 0.f);
        if (u == 0x8000u) u = 0;
        u = (u & 0x8000u) ? (~u & 0xffffu) : (u | 0x8000u);
        if (!(lane & 15)) st_relaxed(at<uint32_t>(g->key, (r0 + it * 2) * 4), (u << 16) | (uint32_t)(0xffff - r0 - it * 2));
      }
      __syncwarp();
      if (lane == 0) flag_add_release(&g->cnt_gate.v);
      TRACE1(2, 9);
    }
    if (warp == 0) {
      const int row0 = hg * 4 * S_LEN;
      uint32_t s = 0, ph = 0;
      #pragma unroll 1
      for (int c = 3; c < 20; c++) {
        const int k = (c < 10 ? c : (c < 18 ? c - 8 : c - 18)) * 64, cb = hg * 8 + (c < 10 ? 0 : 4);
        const CUtensorMap* const tm = c < 10 ? &tmW4 : &tmW3;
        const uint32_t wb = c < 10 ? U : 12288;
        const bool wx = c < 10 || c >= 18;
        const uint32_t bar = sb + B_WF + s * 8, dst = sb + SM_W + rank * 8192 + s * U;
        mbar_wait(bar + (B_WE - B_WF), ph);
        if (elect_one()) {
          mbar_expect_tx(bar, wx ? wb + U : wb);
          tma_load_3d_mc(dst, tm, bar, 0, k + rank * 16, cb);
          if (wx) tma_load_2d(sb + ((c + 2) & 7) * U, &tmX, bar, k, qt * 128);
        }
        mbar_wait(bar + (B_WE - B_WF) + 8, ph);
        if (elect_one()) {
          mbar_expect_tx(bar + 8, wb);
          tma_load_3d_mc(dst + U, tm, bar + 8, 0, k + 32 + rank * 16, cb);
        }
        s += 2;
        if (s == 6) { s = 0; ph ^= 1; }
      }
      #pragma unroll 1
      for (int i = 0; i < 128; i++) {
        const int isv = i < 5 ? (i >> 1) & 1 : (i < 127 ? ~i & 1 : 1), j = i < 4 ? i & 1 : (i + 1 - 2 * isv) >> 1;
        const uint32_t b = isv * 16 + (j & 1) * 8;
        STALL(11);
        if (i) mbar_wait(sb + (i < 4 ? B_WE + ((0x3150 >> (4 * i)) & 7) * 8 : B_KE + b), i < 4 ? i < 2 : (~j >> 1) & 1);
        if (elect_one()) {
          mbar_expect_tx(sb + B_KF + b, 2 * U);
          tma_load_2d_mc(sb + (isv ? SM_V + (j & 1) * 2 * U : (j & 1) * SM_K1) + rank * U, isv ? &tmV : &tmK, sb + B_KF + b, rank * 64, row0 + j * 128);
          if (GSYNC && i == 125) mbar_arrive(sb + B_ANN);
        }
        if (i == 4) TRACEO(3);
      }
      s = 0; ph = 1;
      #pragma unroll 1
      for (int n = 0; n < (X_SKIP(qp) ? 2 : 40); n++) {
        const int st = n < 5 ? (n == 1) : n >> 2, h = n < 5 ? max(n - 1, 0) : n & 3;
        const int u = st < 2 ? 8 + st : ((hg + st - 1) & 7);
        STALL(12);
        mbar_wait(sb + (n < 6 ? B_KE + (n < 4 ? n >> 1 : 3) * 8 : B_CE + s * 8), ph);
        if (elect_one()) {
          mbar_expect_tx(sb + B_CF + s * 8, U);
          tma_load_2d_mc(sb + c_slot(s) * U + rank * 8192, &tmWO, sb + B_CF + s * 8, u * 64, hg * 512 + ((0x3021 >> (4 * h)) & 3) * 128 + rank * 64);
        }
        if (n == 3) TRACEO(4);
        if (++s == 6) { s = 0; ph ^= 1; }
      }
      mbar_wait(sb + B_GATE, 0);
      asm volatile("fence.proxy.async.global;" ::: "memory");
      #pragma unroll 1
      for (int n = 0; n < (X_SKIP(qp) ? 0 : 2); n++) {
        mbar_wait(sb + B_CE + 32 + n * 8, 1);
        if (elect_one()) {
          mbar_expect_tx(sb + B_CF + 32 + n * 8, U);
          tma_load_2d(sb + (10 + n) * U, n ? &tmGate : &tmX, sb + B_CF + 32 + n * 8, hg * 64, qt * 128);
        }
      }
      if (!X_SKIP(qp)) {
        const uint4* const last = g->part + (size_t)((qt * 8 + hg) * 9 + 8) * 1024;
        mbar_wait(sb + B_CE + P8, 0);
        if (elect_one()) {
          mbar_expect_tx(sb + B_CF + 8, U);
          bulk_load(sb + U, last, U, sb + B_CF + 8);
        }
      }
    } else if (warp == 2) {
      #pragma unroll 1
      for (int h = 0; h < 4; h++) {
        mbar_wait(sb + B_OS + h * 8, 0);
        STALL(13);
        #pragma unroll 1
        for (int i = 0; i < (h < 3 ? 16 : 0); i++) {
          uint32_t z = 0;
          #pragma unroll
          for (int k = 0; k < 4; k++) { const uint4 v = lds128(sb + qo_slot(h) + i * 2048 + k * 512 + lane * 16); z = taint(taint(z, v.x, v.y), v.z, v.w); }
          flag_if(sb + SM_BAD + (i & 7) * 4 + h, tainted(z));
        }
        if (GSYNC && h == 2) {
          const uint32_t launch = lds32(sb + SM_EP);
          uint32_t* const mine = at<uint32_t>(g->near, (qt * 8 + hg) * 32 + (lane & 7) * 4);
          st_relaxed(mine, launch - 1);
          mbar_wait(sb + B_ANN, 0);
          mbar_wait(sb + B_KE, 1);
          st_relaxed(mine, launch);
          #pragma unroll 1
          for (int it = 0; __any_sync(0xffffffff, ldg32(at<uint32_t>(g->near, qp * 512 + lane * 16)) != launch) && it < MAXPOLL; it++) {}
        }
        __syncwarp();
        if (h >= 2) { proxy_fence(); if (elect_one()) mbar_arrive(sb + B_OF); }
        __syncwarp();
      }
    } else if (!elect_one()) {
    } else if (warp == 1) {
      mbar_wait(sb + B_OS + 8, 0);
      flag_wait(at<unsigned>(g->q3_done, (hg >> 1) * 128), lds32(sb + SM_EP) * 16 + qt + 1);
      asm volatile("fence.proxy.async.global;" ::: "memory");
      mbar_expect_tx(sb + B_Q3, U);
      bulk_load(sb + 5 * U, g->q3 + (qt * 8 + hg) * 1024, U, sb + B_Q3);
      flag_wait(&g->mod_done.v, lds32(sb + SM_EP) * 4);
      mbar_arrive(sb + B_GATE);
    } else {
      #pragma unroll 1
      for (int j = 2; j < 64 - KVPF; j++) {
        mbar_pace(sb + B_KE + (j & 1) * 8, (~j >> 1) & 1);
        const size_t o = (size_t)(hg * 4 * S_LEN + (j + KVPF) * 128 + qt * 8) * DH;
        if (KVPF) { l2_prefetch(P.k + o, 2048); l2_prefetch(P.v + o, 2048); }
        if (j >= 40 && j < 56) l2_prefetch(P.wo + (size_t)(hg * 512 + qt * 32 + (j - 40) * 2) * DM, 2 * DM * 2);
        if (j >= 56 && j < 60) l2_prefetch(((j & 1) ? P.x : g->gate) + (size_t)(qt * 128 + hg * 16 + (j & 2) * 4) * DM, 8 * DM * 2);
      }
    }
    __syncwarp();
    if ((warp == 1 || warp == 2) && !X_SKIP(qp)) {
      mbar_wait(sb + B_GATE, 0);
      #pragma unroll 1
      for (int i = 0; i < 4; i++) {
        const int r = warp * 8 - 8 + (i & 1) * 4 + (lane >> 3);
        const uint32_t e = ((qt * 128 + hg * 16 + r) * DM + (8 + (i >> 1)) * 64 + (lane & 7) * 8) * 2;
        if (!(i & 1)) bar_sync(8, 192);
        STALL(10);
        const uint4 xr = ldg_nc(at<uint4>(P.x, e)), gr = ld_relaxed4(at<uint4>(g->gate, e)), sv = lds128(sb + SM_BAR + 1024 + r * 128 + (((lane ^ r) & 7) << 4));
        stg128(at<uint4>(P.out, e), gated(xr, sv, gr));
        if (i == 1) bar_arrive(9, 192);
      }
    }
    cluster_arrive();
    cluster_wait();
  } else {
    const int wg = wgi - 1, t = tid & 127, cw = warp - 4;
    asm volatile("setmaxnreg.inc.sync.aligned.u32 224;");
    uint32_t q[32], p[32];
    float s[64], o[64], l[2] = {0.f, 0.f};
    const uint32_t rb = __shfl_sync(0xffffffff, map_cta(sb, lane & 1), lane), wr = sb + cw * 2048, qa = __shfl_sync(0xffffffff, wr + lane * 16, lane);
    {
      uint32_t st0 = 0, st1 = 0;
      uint32_t sl = 0, ph = 0, rprev = 0;
      if (wg == 1) bar_arrive(1, 256);
      static_for<0, 2>([&](auto pc) { constexpr int pass = decltype(pc)::v;
        float acc[pass ? 96 : 128];
        #pragma unroll 1
        for (int i = 0; i < 10; i++) {
          if (i == (pass ? SKEW1 : SKEW0) / 2) {
            if (pass == 1) {
              const uint32_t d = qa + qo_slot(0);
              #pragma unroll
              for (int e = 0; e < 8; e++) sts128(d + (e >> 2) * U + (e & 3) * 512, p[4*e], p[4*e+1], p[4*e+2], p[4*e+3]);
            }
            bar_sync(1 + wg, 256);
          }
          const uint64_t a = desc(sb, ((i + 2 + 2 * pass) & 7) * 1024 + wg * 512 + doff(0, 16)), b = desc(sb, sl * 128 + doff(SM_W, 2048));
          STALL(4);
          mbar_wait(sb + B_WF + sl, ph);
          if (i == 0) TRACE(wg, 1 + pass);
          TRACEF(1, wg, 40 + pass * 20 + 2 * i);
          wg_fence();
          wgmma_ss_tb<0, 0>(acc, a, b, i > 0);
          wgmma_ss_tb<2, 512>(acc, a, b, 1);
          wg_commit();
          mbar_wait(sb + B_WF + 8 + sl, ph);
          wg_wait<1>();
          if (i > 0) release2(rprev, lane);
          TRACEF(1, wg, 41 + pass * 20 + 2 * i);
          wg_fence();
          wgmma_ss_tb<4, 1024>(acc, a, b, 1);
          wgmma_ss_tb<6, 1536>(acc, a, b, 1);
          wg_commit();
          rprev = rb + B_WE + 8 + sl;
          sl += 16;
          if (sl == 48) { sl = 0; ph ^= 1; }
          wg_wait<1>();
          release2(rprev - 8, lane);
        }
        mbar_wait(sb + B_EXT + pass * 8, 0);
        if (pass == 0) { st0 = lds32(sb + SM_STAT + (cw * 16 + (lane >> 2)) * 4); st1 = lds32(sb + SM_STAT + (cw * 16 + 8 + (lane >> 2)) * 4); }
        {
          const uint32_t a0 = (lane & 3) ? 0u : (__byte_perm(st0, 0, 0x1010) ^ 0x80008000u), a1 = (lane & 3) ? 0u : (__byte_perm(st1, 0, 0x1010) ^ 0x80008000u);
          wg_fence();
          wgmma_rs_tb<0>(acc, a0, a1, 0u, 0u, (uint64_t)desc_lo(sb + SM_EXT + pass * 1024, 0) | ((uint64_t)2 << 32), 1);
          wg_commit();
        }
        float rs0 = rcp_approx(bf_hi(st0)) * SCALE_LOG2E, rs1 = rcp_approx(bf_hi(st1)) * SCALE_LOG2E;
        bar_arrive(1 + (wg ^ 1), 256);
        wg_wait<0>();
        fence_regs(acc);
        release2(rprev, lane);
        if constexpr (pass == 0) {
          #pragma unroll
          for (int i = 0; i < 32; i++) {
            const float r = (i & 1) ? rs1 : rs0;
            q[i] = pack_bf16(acc[2*i] * r, acc[2*i+1] * r); p[i] = pack_bf16(acc[64+2*i] * r, acc[64+2*i+1] * r);
          }
        } else {
          const uint32_t d = qa + SM_QO;
          #pragma unroll
          for (int e = 0; e < 12; e++) {
            if (e == 8) {
              mbar_wait(sb + B_KF, 0);
              bar_sync(1 + wg, 256);
              TRACE(wg, 3);
              mma_qk<0, 2>(s, q, desc(sb, 2));
              bar_arrive(1 + (wg ^ 1), 256);
              const uint32_t one = lds32(sb + SM_ONE);
              rs0 = __uint_as_float(__float_as_uint(rs0) * one); rs1 = __uint_as_float(__float_as_uint(rs1) * one);
            }
            sts128(d + (e >> 2) * U + (e & 3) * 512, pack_bf16(acc[8*e] * rs0, acc[8*e+1] * rs0), pack_bf16(acc[8*e+2] * rs1, acc[8*e+3] * rs1),
                   pack_bf16(acc[8*e+4] * rs0, acc[8*e+5] * rs0), pack_bf16(acc[8*e+6] * rs1, acc[8*e+7] * rs1));
          }
          wg_wait<0>();
          fence_regs(s);
          release2(rb + B_KE, lane);
          exp_rows<0, 64>(s, l);
          #pragma unroll
          for (int i = 0; i < 32; i++) p[i] = pack_bf16(s[2*i], s[2*i+1]);
        }
      });
    }
    unsigned tz[3] = {0, 0, 0};
    bool ready = false;
    #pragma unroll 1
    for (int j = 1; ; j += 2) {
      int ph = 0;
      #pragma unroll 1
      do {
        attn_step<1, false>(sb, rb, wr, qa, wg, lane, j, ph, s, o, p, q, l, ready, g, tz);
        ph ^= 1; j += 2;
        if (wg < 2) attn_step<0, false>(sb, rb, wr, qa, wg, lane, j - 1, ph, s, o, p, q, l, ready, g, tz);
      } while ((j & 15) != 15);
      if (j == 47) mbar_wait(sb + B_Q3, 0);
      attn_step<1, true>(sb, rb, wr, qa, wg, lane, j, 1, s, o, p, q, l, ready, g, tz);
      if (j == 63) break;
      if (wg < 2) attn_step<0, true>(sb, rb, wr, qa, wg, lane, j + 1, 0, s, o, p, q, l, ready, g, tz);
    }
    mbar_wait(sb + B_OF, 0);
    mbar_wait(sb + B_CF + wg * 8, 0);
    mbar_wait(sb + B_KF + 24, 1);
    bar_sync(1 + wg, 256);
    TRACE(wg, 4);
    mma_pv<SM_V + 2 * U, 2>(o, p, desc(sb, 2), true);
    mma_c<3>(s, sb, wg, 0, 0);
    bar_arrive(1 + (wg ^ 1), 256);
    mbar_wait(sb + B_KE + 16, 1);
    const uint32_t tag = lds32(sb + SM_EP) & 1;
    row_scale(l[0], l[1], lds32(sb + SM_ONE), sb + SM_BAD + cw * 4 + 3);
    __syncwarp();
    const uint32_t flags = lds32(sb + SM_BAD + (lane & 7) * 4);
    wg_wait<1>();
    fence_regs(o); fence_regs(p);
    release2(rb + B_KE + 24, lane);
    const uint32_t over = tainted(store_o<true>(o_addr(wr, lane) + SM_V, o, l[0], l[1]));
    if (__builtin_expect(bar_any(4 + wg, 128, __any_sync(0xffffffff, flags | over)), 0)) {
      const uint32_t bad = __shfl_sync(0xffffffff, flags, cw) | (__any_sync(0xffffffff, over) << 24);
      wg_wait<0>();
      fence_regs(s);
      redo_heads(P, sb, bad, qt * 128 + cw * 16, hg * 4);
      #pragma unroll
      for (int i = 0; i < 64; i++) s[i] = 0.f;
      __syncwarp();
      if (lane == 0) mbar_arrive(sb + B_OS + 24);
      mbar_wait(sb + B_OF, 1);
      mma_c<4>(s, sb, wg, 0, 0);
    } else if (lane == 0) mbar_arrive(sb + B_OS + 24);
    wg_wait<0>();
    release2(rb + B_CE + wg * 8, lane);
    if (X_SKIP(qp)) { cluster_arrive(); } else {
      const uint4* in = at<uint4>(g->part, (((qt * 8 + hg) * 9 + wg) * 1024 + t) * 16);
      const uint32_t tm = 0u - tag;
      uint4 v[8];
      auto fetch = [&](auto half, const uint4* from) {
        #pragma unroll
        for (int i = decltype(half)::v * 4; i < decltype(half)::v * 4 + 4; i++) reload(v[i], from + i * 128);
      };
      auto verify = [&](auto half, const uint4* from) { verify4(v + decltype(half)::v * 4, from + decltype(half)::v * 512, tm); };
      int sp = 6, sl = 2 + 3 * wg, ph = 0;
      auto quarter = [&](auto site, int h, int arrive_bar) {
        STALL(2);
        mbar_wait(sb + B_CF + sl * 8, ph);
        if (h == 0) bar_sync(1 + wg, 256);
        mma_c<decltype(site)::v>(s, sb, sl, h, arrive_bar);
        if (h) { wg_wait<1>(); release2(rb + B_CE + sp * 8, lane); }
        sp = sl;
        if (++sl == 6) { sl = 0; ph ^= 1; }
      };
      auto send = [&](int st) {
        uint4* dst = at<uint4>(g->part, ((qt * 72 + st) * 1024 + (st < 2 ? hg * 128 : ((hg + st - 1) & 7) * 9216) + t) * 16);
        const uint32_t ds = st < 2 ? 9 * U : 2048;
        wg_wait<0>();
        fence_regs(s);
        TRACEF(4, wg, 106 + (st >> 1));
        release2(rb + B_CE + sp * 8, lane);
        STALL(3);
        #pragma unroll
        for (int i = 0; i < 8; i++, dst = at<uint4>(dst, ds))
          st_tagged(dst, (pack_bf16(s[8*i], s[8*i+1]) & ~1u) | tag, pack_bf16(s[8*i+2], s[8*i+3]), pack_bf16(s[8*i+4], s[8*i+5]), pack_bf16(s[8*i+6], s[8*i+7]));
        sl += st ? 4 : 3;
        if (sl >= 6) { sl -= 6; ph ^= 1; }
      };
      const uint32_t ta = ((lane >> 4) * 8 + (lane & 7)) * 128 + ((((cw & 3) * 2 + ((lane >> 3) & 1)) ^ (lane & 7)) << 4), ra = (t >> 3) * 128 + (((t & 7) ^ ((t >> 3) & 7)) << 4);
      float T[64];
      #pragma unroll
      for (int i = 0; i < 8; i++) asm volatile("mov.b64 {%0,%1}, 0;\nmov.b64 {%2,%3}, 0;" : "=r"(v[i].x), "=r"(v[i].y), "=r"(v[i].z), "=r"(v[i].w));
      #pragma unroll
      for (int i = 0; i < 64; i += 2) asm volatile("mov.b64 {%0,%1}, 0;" : "=f"(T[i]), "=f"(T[i+1]));
      TRACEF(4, wg, 112);
      bar_sync(1 + wg, 256);
      auto take = [&](auto half, int back, bool more) {
        verify(half, in - back * 1024);
        const uint4* const nx = in - (back - 1) * 1024;
        #pragma unroll
        for (int i = decltype(half)::v * 4; i < decltype(half)::v * 4 + 4; i++) { add8(T + 8 * i, v[i]); reload(v[i], nx + i * 128, more); }
      };
      #pragma unroll 1
      for (int st = wg; ; st += 2, in += 2048) {
        TRACEF(4, wg, 100 + (st >> 1));
        const bool odd5 = (st & 1) && st >= 5;
        quarter(IC<5>{}, 1, 0);
        if (odd5) take(IC<0>{}, 3, true);
        else if (st == 2) fetch(IC<0>{}, in - 2048);
        quarter(IC<6>{}, 2, 0);
        if (odd5) take(IC<1>{}, 3, true);
        else if (st == 2) fetch(IC<1>{}, in - 2048);
        if (st < 2) mbar_wait(sb + B_OF, 1);
        quarter(IC<7>{}, 3, st < 9 ? 2 - wg : 0);
        if (st < 9) send(st);
        if (odd5) { take(IC<0>{}, 2, st < 9); take(IC<1>{}, 2, st < 9); }
        else if (st == 3) {
          fetch(IC<0>{}, in - 1024); fetch(IC<1>{}, in - 1024);
        } else if (st == 2 || st == 4) {
          const uint4* const rows = at<uint4>(in - 3072, st == 2 ? U : 0);
          float a[8];
          #pragma unroll
          for (int i = 0; i < 8; i++) a[i] = 0.f;
          static_for<0, 2>([&](auto hf) {
            verify(hf, rows);
            #pragma unroll
            for (int i = decltype(hf)::v * 4; i < decltype(hf)::v * 4 + 4; i++) { add8(a, v[i]); reload(v[i], rows + 1024 + i * 128, st == 2); }
          });
          if (st == 4) bar_sync(9, 192);
          stsm4t(sb + SM_BAR + 1024 + ta, pack_bf16(a[0], a[1]), pack_bf16(a[2], a[3]), pack_bf16(a[4], a[5]), pack_bf16(a[6], a[7]));
          bar_arrive(8, 192);
        }
        if (st >= 8) break;
        quarter(IC<8>{}, 0, 0);
      }
      cluster_arrive();
      TRACEF(4, wg, 113);
      wg_wait<0>();
      fence_regs(s);
      if (wg == 0) {
        mbar_wait(sb + B_CF + 32, 0);
        mbar_wait(sb + B_CF + 40, 0);
        uint4* const op = at<uint4>(P.out, ((qt * 128 + (t >> 3)) * DM + hg * 64 + (t & 7) * 8) * 2);
        bar_sync(1, 256);
        uint4 xv[8];
        #pragma unroll
        for (int i = 0; i < 8; i++) { xv[i] = lds128(sb + 10 * U + i * 2048 + ra); v[i] = lds128(sb + 11 * U + i * 2048 + ra); }
        #pragma unroll
        for (int i = 0; i < 8; i++) {
          if (i % (8 / FQ) == 0) bar_sync(12 + i / (8 / FQ), 256);
          stg128(op + i * 2 * DM, gated(xv[i], lds128(sb + i * 2048 + ra), v[i]));
        }
      } else {
        TRACEF(4, wg, 110);
        #pragma unroll
        for (int i = 0; i < 64; i++) T[i] += s[i];
        fence_regs(T);
        mbar_wait(sb + B_CF + 8, 1);
        #pragma unroll
        for (int i = 0; i < 8; i++) v[i] = lds128(sb + U + i * 2048 + t * 16);
        bar_arrive(1, 256);
        static_for<0, 8>([&](auto ic) { constexpr int i = decltype(ic)::v;
          if (!(i & 3)) verify(IC<i / 4>{}, in - 1024);
          add8(T + 8 * i, v[i]);
          stsm4t(sb + i * 2048 + ta, pack_bf16(T[8*i], T[8*i+1]), pack_bf16(T[8*i+2], T[8*i+3]), pack_bf16(T[8*i+4], T[8*i+5]), pack_bf16(T[8*i+6], T[8*i+7]));
          if ((i + 1) % (8 / FQ) == 0) bar_arrive(12 + i / (8 / FQ), 256);
        });
      }
    }
    TRACE(wg, 6);
    cluster_wait();
  }
}

typedef CUresult (*EncodeFn)(CUtensorMap*, CUtensorMapDataType, cuuint32_t, void*, const cuuint64_t*, const cuuint64_t*, const cuuint32_t*, const cuuint32_t*,
                             CUtensorMapInterleave, CUtensorMapSwizzle, CUtensorMapL2promotion, CUtensorMapFloatOOBfill);
void make_map(EncodeFn enc, CUtensorMap* tm, const void* ptr, uint64_t inner, uint64_t outer, uint32_t box_outer, uint32_t blocks = 0) {
  cuuint64_t dims[3] = {blocks ? 64 : inner, outer, inner / 64}; cuuint64_t strides[2] = {inner * 2, 128};
  cuuint32_t box[3] = {64, box_outer, blocks}; cuuint32_t es[3] = {1, 1, 1};
  enc(tm, CU_TENSOR_MAP_DATA_TYPE_BFLOAT16, blocks ? 3 : 2, const_cast<void*>(ptr), dims, strides, box, es, CU_TENSOR_MAP_INTERLEAVE_NONE,
      CU_TENSOR_MAP_SWIZZLE_128B, CU_TENSOR_MAP_L2_PROMOTION_L2_256B, CU_TENSOR_MAP_FLOAT_OOB_FILL_NONE);
}

}

extern "C" void kernel_launch(void* const* d_in, const int* in_sizes, int n_in, void* d_out, int out_size) {
  (void)in_sizes; (void)n_in; (void)out_size;
  Params P;
  P.x = (const __nv_bfloat16*)d_in[0]; P.k = (const __nv_bfloat16*)d_in[1]; P.v = (const __nv_bfloat16*)d_in[2];
  P.wq = (const __nv_bfloat16*)d_in[3]; P.wo = (const __nv_bfloat16*)d_in[4]; P.wr = (const __nv_bfloat16*)d_in[6];
  P.out = (__nv_bfloat16*)d_out;
  cudaGetSymbolAddress((void**)&P.g, g_s);
  void* fn = nullptr; cudaDriverEntryPointQueryResult st;
  cudaGetDriverEntryPoint("cuTensorMapEncodeTiled", &fn, cudaEnableDefault, &st);
  EncodeFn enc = (EncodeFn)fn;
  CUtensorMap tmX, tmW4, tmW3, tmW1, tmK, tmV, tmWO, tmG, tmU, tmD, tmGate;
  make_map(enc, &tmGate, P.g->gate, DM, S_LEN, 128);
  make_map(enc, &tmX, P.x, DM, S_LEN, 128);
  make_map(enc, &tmW4, P.wq, NH * DH, DM, 16, 4);
  make_map(enc, &tmW3, P.wq, NH * DH, DM, 16, 3);
  make_map(enc, &tmW1, P.wq, NH * DH, DM, 128);
  make_map(enc, &tmK, P.k, DH, (uint64_t)NH * S_LEN, 128);
  make_map(enc, &tmV, P.v, DH, (uint64_t)NH * S_LEN, 128);
  make_map(enc, &tmWO, P.wo, DM, NH * DH, 64);
  make_map(enc, &tmG, d_in[7], FF, DM, 128);
  make_map(enc, &tmU, d_in[8], FF, DM, 128);
  make_map(enc, &tmD, d_in[9], DM, FF, 128);
  cudaFuncSetAttribute(fused_kernel, cudaFuncAttributeMaxDynamicSharedMemorySize, SMEM_BYTES);
  fused_kernel<<<132, 384, SMEM_BYTES, cudaStreamPerThread>>>(tmX, tmW4, tmW3, tmW1, tmK, tmV, tmWO, tmG, tmU, tmD, tmGate, P);
}
```

```cpp
#include <cuda_runtime.h>
#include <cuda_bf16.h>
#include <cuda.h>
#include <stdint.h>

#define C_EARLY 6
#define MAXPOLL (1 << 22)
#define SKEW0 18
#define DPOS 44
#define DPOSF 36
#define KVPF 2
#define X_SKIP(qp) false
#define W1SL 300
#define WAITMAX (1 << 19)
#define CSB 10
#define P8 16
#define FQ 2
#define GSYNC 1
#define PH 1
#define XRC 15
#define QSP 6
namespace {

constexpr int S_LEN = 2048, DM = 640, NH = 32, DH = 128, FF = 1728, TOPC = 8;
constexpr float SCALE_LOG2E = 0.08838834764831845f * 1.4426950408889634f;

struct alignas(128) Cnt { unsigned v; unsigned pad[31]; };
struct Scratch {
  alignas(128) unsigned long long ticket;
  alignas(128)
  uint4 part[16 * 8 * 9 * 1024];
  __nv_bfloat16 gate[S_LEN * DM];
  uint32_t stat[S_LEN];
  uint4 cs[NH * DH];
  float ypart[4 * TOPC * DM];
  uint4 q3[16 * 8 * 1024];
  uint32_t key[S_LEN];
  Cnt cnt_gate, cnt_mod, mod_done, q3_done[4];
  uint32_t near[128 * 8];
};
__device__ Scratch g_s;

__device__ __forceinline__ uint32_t smem_u32(const void* p) { return (uint32_t)__cvta_generic_to_shared(p); }
template <class T> __device__ __forceinline__ T* at(const void* p, uint32_t off) { uint64_t r;
  asm("{\n.reg .u32 lo, hi;\nmov.b64 {lo, hi}, %1;\nadd.cc.u32 lo, lo, %2;\naddc.u32 hi, hi, 0;\nmov.b64 %0, {lo, hi};\n}\n" : "=l"(r) : "l"(p), "r"(off)); return (T*)r; }
__device__ __forceinline__ void mbar_init(uint32_t bar, uint32_t cnt) { asm volatile("mbarrier.init.shared::cta.b64 [%0], %1;" :: "r"(bar), "r"(cnt) : "memory"); }
__device__ __forceinline__ void mbar_expect_tx(uint32_t bar, uint32_t bytes) { asm volatile("mbarrier.arrive.expect_tx.shared::cta.b64 _, [%0], %1;" :: "r"(bar), "r"(bytes) : "memory"); }
__device__ __forceinline__ void mbar_arrive(uint32_t bar) { asm volatile("mbarrier.arrive.shared::cta.b64 _, [%0];" :: "r"(bar) : "memory"); }
__device__ __forceinline__ uint32_t map_cta(uint32_t a, uint32_t cta) { uint32_t r; asm volatile("mapa.shared::cluster.u32 %0, %1, %2;" : "=r"(r) : "r"(a), "r"(cta)); return r; }
__device__ __forceinline__ void mbar_arrive_cluster(uint32_t bar) { asm volatile("mbarrier.arrive.shared::cluster.b64 _, [%0];" :: "r"(bar) : "memory"); }
__device__ __forceinline__ void mbar_wait(uint32_t bar, uint32_t parity) {
  asm volatile("{\n.reg .pred p;\n.reg .u32 c;\nmov.u32 c, 0;\nLAB_WAIT:\nmbarrier.try_wait.parity.shared::cta.b64 p, [%0], %1;\n@p bra LAB_DONE;\n"
               "add.u32 c, c, 1;\nsetp.lt.u32 p, c, %2;\n@p bra LAB_WAIT;\ntrap;\nLAB_DONE:\n}\n" :: "r"(bar), "r"(parity), "n"(WAITMAX) : "memory"); }
__device__ __forceinline__ bool mbar_test2(uint32_t bar0, uint32_t par0, uint32_t bar1, uint32_t par1) { uint32_t r;
  asm volatile("{\n.reg .pred p, q;\nmbarrier.test_wait.parity.shared::cta.b64 p, [%1], %2;\nmbarrier.test_wait.parity.shared::cta.b64 q, [%3], %4;\nand.pred p, p, q;\nselp.u32 %0, 1, 0, p;\n}\n"
               : "=r"(r) : "r"(bar0), "r"(par0), "r"(bar1), "r"(par1) : "memory"); return r; }
__device__ __forceinline__ void mbar_pace(uint32_t bar, uint32_t parity) {
  asm volatile("{\n.reg .pred p;\n.reg .u32 c;\nmov.u32 c, 0;\nLAB_WAIT:\nmbarrier.try_wait.parity.shared::cta.b64 p, [%0], %1;\n@p bra LAB_DONE;\n"
               "add.u32 c, c, 1;\nsetp.lt.u32 p, c, 64;\n@p bra LAB_WAIT;\nLAB_DONE:\n}\n" :: "r"(bar), "r"(parity) : "memory"); }
__device__ __forceinline__ void flag_wait(const unsigned* p, unsigned target, unsigned ns = 500) {
  asm volatile("{\n.reg .pred p;\n.reg .u32 c, v;\nmov.u32 c, 0;\nLAB_WAIT:\nld.relaxed.gpu.global.u32 v, [%0];\nsub.u32 v, v, %1;\nsetp.ge.s32 p, v, 0;\n@p bra LAB_DONE;\n"
               "nanosleep.u32 %2;\nadd.u32 c, c, 1;\nsetp.lt.u32 p, c, 8388608;\n@p bra LAB_WAIT;\ntrap;\nLAB_DONE:\nld.acquire.gpu.global.u32 v, [%0];\n}\n" :: "l"(p), "r"(target), "r"(ns) : "memory"); }
__device__ __forceinline__ void flag_add_release(unsigned* p) { asm volatile("fence.acq_rel.gpu;\nred.relaxed.gpu.global.add.u32 [%0], 1;" :: "l"(p) : "memory"); }
__device__ __forceinline__ void tma_load_2d(uint32_t dst, const CUtensorMap* tm, uint32_t bar, int c0, int c1) {
  asm volatile("cp.async.bulk.tensor.2d.shared::cluster.global.mbarrier::complete_tx::bytes [%0], [%1, {%3, %4}], [%2];"
    :: "r"(dst), "l"(tm), "r"(bar), "r"(c0), "r"(c1) : "memory"); }
__device__ __forceinline__ void tma_load_2d_mc(uint32_t dst, const CUtensorMap* tm, uint32_t bar, int c0, int c1) {
  asm volatile("cp.async.bulk.tensor.2d.shared::cluster.global.mbarrier::complete_tx::bytes.multicast::cluster [%0], [%1, {%3, %4}], [%2], %5;"
    :: "r"(dst), "l"(tm), "r"(bar), "r"(c0), "r"(c1), "h"((uint16_t)3) : "memory"); }
__device__ __forceinline__ void tma_load_3d(uint32_t dst, const CUtensorMap* tm, uint32_t bar, int c0, int c1, int c2) {
  asm volatile("cp.async.bulk.tensor.3d.shared::cluster.global.mbarrier::complete_tx::bytes [%0], [%1, {%3, %4, %5}], [%2];"
    :: "r"(dst), "l"(tm), "r"(bar), "r"(c0), "r"(c1), "r"(c2) : "memory"); }
__device__ __forceinline__ void tma_load_3d_mc(uint32_t dst, const CUtensorMap* tm, uint32_t bar, int c0, int c1, int c2) {
  asm volatile("cp.async.bulk.tensor.3d.shared::cluster.global.mbarrier::complete_tx::bytes.multicast::cluster [%0], [%1, {%3, %4, %5}], [%2], %6;"
    :: "r"(dst), "l"(tm), "r"(bar), "r"(c0), "r"(c1), "r"(c2), "h"((uint16_t)3) : "memory"); }
__device__ __forceinline__ void bulk_load(uint32_t dst, const void* src, uint32_t bytes, uint32_t bar) {
  asm volatile("cp.async.bulk.shared::cluster.global.mbarrier::complete_tx::bytes [%0], [%1], %2, [%3];" :: "r"(dst), "l"(src), "r"(bytes), "r"(bar) : "memory"); }
__device__ __forceinline__ void l2_prefetch(const void* p, uint32_t bytes) { asm volatile("cp.async.bulk.prefetch.L2.global [%0], %1;" :: "l"(p), "r"(bytes) : "memory"); }
__device__ __forceinline__ void wg_fence() { asm volatile("wgmma.fence.sync.aligned;" ::: "memory"); }
__device__ __forceinline__ void wg_commit() { asm volatile("wgmma.commit_group.sync.aligned;" ::: "memory"); }
template <int N> __device__ __forceinline__ void wg_wait() { asm volatile("wgmma.wait_group.sync.aligned %0;" :: "n"(N) : "memory"); }
__device__ __forceinline__ void bar_sync(int id, int n) { asm volatile("bar.sync %0, %1;" :: "r"(id), "r"(n) : "memory"); }
__device__ __forceinline__ void bar_arrive(int id, int n) { asm volatile("bar.arrive %0, %1;" :: "r"(id), "r"(n) : "memory"); }
__device__ __forceinline__ bool bar_any(int id, int n, uint32_t v) { uint32_t r;
  asm volatile("{\n.reg .pred p;\nsetp.ne.u32 p, %3, 0;\nbar.red.or.pred p, %1, %2, p;\nselp.u32 %0, 1, 0, p;\n}\n" : "=r"(r) : "r"(id), "r"(n), "r"(v) : "memory"); return r; }
__device__ __forceinline__ int sel_lt(int a, int b, int x, int y) { int r; asm("{\n.reg .pred p;\nsetp.lt.s32 p, %1, %2;\nselp.s32 %0, %3, %4, p;\n}\n" : "=r"(r) : "r"(a), "r"(b), "r"(x), "r"(y)); return r; }
__device__ __forceinline__ bool elect_one() { uint32_t r; asm volatile("{\n.reg .pred p;\nelect.sync _|p, 0xffffffff;\nselp.u32 %0, 1, 0, p;\n}\n" : "=r"(r)); return r; }
__device__ __forceinline__ void cluster_arrive() { asm volatile("barrier.cluster.arrive.relaxed.aligned;" ::: "memory"); }
__device__ __forceinline__ void cluster_wait() { asm volatile("barrier.cluster.wait.aligned;" ::: "memory"); }
__device__ __forceinline__ void proxy_fence() { asm volatile("fence.proxy.async.shared::cta;" ::: "memory"); }
__device__ __forceinline__ uint32_t pack_bf16(float lo, float hi) { uint32_t r; asm("cvt.rn.bf16x2.f32 %0, %1, %2;" : "=r"(r) : "f"(hi), "f"(lo)); return r; }
__device__ __forceinline__ float bf_lo(uint32_t v) { return __uint_as_float(v << 16); }
__device__ __forceinline__ float bf_hi(uint32_t v) { return __uint_as_float(v & 0xffff0000u); }
__device__ __forceinline__ void add8(float* a, const uint4& w) {
  a[0] += bf_lo(w.x); a[1] += bf_hi(w.x); a[2] += bf_lo(w.y); a[3] += bf_hi(w.y); a[4] += bf_lo(w.z); a[5] += bf_hi(w.z); a[6] += bf_lo(w.w); a[7] += bf_hi(w.w); }
__device__ __forceinline__ float rbf(float x) { return __bfloat162float(__float2bfloat16_rn(x)); }
__device__ __forceinline__ float ex2(float x) { float y; asm("ex2.approx.ftz.f32 %0, %1;" : "=f"(y) : "f"(x)); return y; }
__device__ __forceinline__ uint32_t lds32(uint32_t a) { uint32_t v; asm volatile("ld.shared.u32 %0, [%1];" : "=r"(v) : "r"(a) : "memory"); return v; }
__device__ __forceinline__ void sts32(uint32_t a, uint32_t v) { asm volatile("st.shared.u32 [%0], %1;" :: "r"(a), "r"(v) : "memory"); }
__device__ __forceinline__ uint4 lds128(uint32_t a) { uint4 v; asm volatile("ld.shared.v4.u32 {%0,%1,%2,%3}, [%4];" : "=r"(v.x), "=r"(v.y), "=r"(v.z), "=r"(v.w) : "r"(a) : "memory"); return v; }
__device__ __forceinline__ void sts128(uint32_t a, uint32_t x, uint32_t y, uint32_t z, uint32_t w) { asm volatile("st.shared.v4.u32 [%0], {%1,%2,%3,%4};" :: "r"(a), "r"(x), "r"(y), "r"(z), "r"(w) : "memory"); }
__device__ __forceinline__ void sts128_if(bool c, uint32_t a, uint32_t x, uint32_t y, uint32_t z, uint32_t w) {
  asm volatile("{\n.reg .pred p;\nsetp.ne.u32 p, %5, 0;\n@p st.shared.v4.u32 [%0], {%1,%2,%3,%4};\n}\n" :: "r"(a), "r"(x), "r"(y), "r"(z), "r"(w), "r"((uint32_t)c) : "memory"); }
__device__ __forceinline__ void st_tagged(uint4* p, uint32_t x, uint32_t y, uint32_t z, uint32_t w) {
  asm volatile("st.relaxed.gpu.global.v4.u32 [%0], {%1,%2,%3,%4};" :: "l"(p), "r"(x), "r"(y), "r"(z), "r"(w) : "memory"); }
__device__ __forceinline__ uint4 ld_relaxed4(const void* p) { uint4 v;
  asm volatile("ld.relaxed.gpu.global.v4.u32 {%0,%1,%2,%3}, [%4];" : "=r"(v.x), "=r"(v.y), "=r"(v.z), "=r"(v.w) : "l"(p) : "memory"); return v; }
__device__ __forceinline__ uint4 ld_tagged(const uint4* p) { uint4 v;
  asm volatile("{\n.reg .b128 v;\nld.relaxed.gpu.global.b128 v, [%4];\nmov.b128 {%0,%1,%2,%3}, v;\n}\n" : "=r"(v.x), "=r"(v.y), "=r"(v.z), "=r"(v.w) : "l"(p) : "memory"); return v; }
__device__ __forceinline__ void reload(uint4& v, const uint4* p, bool yes = true) {
  asm volatile("{\n.reg .pred p;\nsetp.ne.u32 p, %5, 0;\n@p ld.relaxed.gpu.global.v4.u32 {%0,%1,%2,%3}, [%4];\n}\n" : "+r"(v.x), "+r"(v.y), "+r"(v.z), "+r"(v.w) : "l"(p), "r"((uint32_t)yes) : "memory"); }
#define TAG_TEST "lop3.b32 a, %0, %4, %17, 0x7E;\nlop3.b32 b, %8, %12, %17, 0x7E;\nlop3.b32 a, a, b, 1, 0xA8;\nsetp.ne.u32 p, a, 0;\nvote.sync.any.pred p, p, 0xffffffff;\n"
__device__ __forceinline__ void verify4(uint4* v, const uint4* p, uint32_t tm) {
  asm volatile("{\n.reg .pred p;\n.reg .u32 a, b, c;\n" TAG_TEST "@!p bra.uni LAB_DONE;\nmov.u32 c, 0;\nLAB_AGAIN:\n"
    "ld.relaxed.gpu.global.v4.u32 {%0,%1,%2,%3}, [%16];\nld.relaxed.gpu.global.v4.u32 {%4,%5,%6,%7}, [%16+2048];\n"
    "ld.relaxed.gpu.global.v4.u32 {%8,%9,%10,%11}, [%16+4096];\nld.relaxed.gpu.global.v4.u32 {%12,%13,%14,%15}, [%16+6144];\n"
    TAG_TEST "add.u32 c, c, 1;\nsetp.lt.and.u32 p, c, %18, p;\n@p bra.uni LAB_AGAIN;\nLAB_DONE:\n}\n"
    : "+r"(v[0].x), "+r"(v[0].y), "+r"(v[0].z), "+r"(v[0].w), "+r"(v[1].x), "+r"(v[1].y), "+r"(v[1].z), "+r"(v[1].w),
      "+r"(v[2].x), "+r"(v[2].y), "+r"(v[2].z), "+r"(v[2].w), "+r"(v[3].x), "+r"(v[3].y), "+r"(v[3].z), "+r"(v[3].w) : "l"(p), "r"(tm), "n"(MAXPOLL) : "memory"); }
__device__ __forceinline__ uint4 ldg_nc(const void* p) { uint4 v;
  asm volatile("ld.global.nc.L1::no_allocate.v4.u32 {%0,%1,%2,%3}, [%4];" : "=r"(v.x), "=r"(v.y), "=r"(v.z), "=r"(v.w) : "l"(p) : "memory"); return v; }
__device__ __forceinline__ uint32_t ldg32(const void* p) { uint32_t v; asm volatile("ld.relaxed.gpu.global.u32 %0, [%1];" : "=r"(v) : "l"(p) : "memory"); return v; }
__device__ __forceinline__ void stg128(void* p, const uint4& v) { asm volatile("st.global.v4.u32 [%0], {%1,%2,%3,%4};" :: "l"(p), "r"(v.x), "r"(v.y), "r"(v.z), "r"(v.w) : "memory"); }
__device__ __forceinline__ void st_relaxed(uint32_t* p, uint32_t v) { asm volatile("st.relaxed.gpu.global.u32 [%0], %1;" :: "l"(p), "r"(v) : "memory"); }
__device__ __forceinline__ uint32_t mul_bf2(uint32_t a, uint32_t b) { uint32_t r; asm("mul.rn.bf16x2 %0, %1, %2;" : "=r"(r) : "r"(a), "r"(b)); return r; }
__device__ __forceinline__ uint32_t add_bf2(uint32_t a, uint32_t b) { uint32_t r; asm("add.rn.bf16x2 %0, %1, %2;" : "=r"(r) : "r"(a), "r"(b)); return r; }
__device__ __forceinline__ uint32_t sub_bf2(uint32_t a, uint32_t b) { uint32_t r; asm("sub.rn.bf16x2 %0, %1, %2;" : "=r"(r) : "r"(a), "r"(b)); return r; }
__device__ __forceinline__ void stsm4(uint32_t a, uint32_t r0, uint32_t r1, uint32_t r2, uint32_t r3) {
  asm volatile("stmatrix.sync.aligned.m8n8.x4.shared.b16 [%0], {%1,%2,%3,%4};" :: "r"(a), "r"(r0), "r"(r1), "r"(r2), "r"(r3) : "memory"); }
__device__ __forceinline__ void stsm4t(uint32_t a, uint32_t r0, uint32_t r1, uint32_t r2, uint32_t r3) {
  asm volatile("stmatrix.sync.aligned.m8n8.x4.trans.shared.b16 [%0], {%1,%2,%3,%4};" :: "r"(a), "r"(r0), "r"(r1), "r"(r2), "r"(r3) : "memory"); }
__device__ __forceinline__ uint4 gated(const uint4& x, const uint4& s, const uint4& g) {
  return make_uint4(add_bf2(x.x, mul_bf2(s.x, g.x)), add_bf2(x.y, mul_bf2(s.y, g.y)), add_bf2(x.z, mul_bf2(s.z, g.z)), add_bf2(x.w, mul_bf2(s.w, g.w))); }
__device__ __forceinline__ uint32_t tag_miss(uint32_t a, uint32_t b, uint32_t tm) { uint32_t d; asm("lop3.b32 %0, %1, %2, %3, 0x7E;" : "=r"(d) : "r"(a), "r"(b), "r"(tm)); return d; }
template <int R> __device__ __forceinline__ void fence_regs(float (&d)[R]) {
  #pragma unroll
  for (int i = 0; i < R; i++) asm volatile("" : "+f"(d[i]) :: "memory"); }
template <int R> __device__ __forceinline__ void fence_regs(uint32_t (&d)[R]) {
  #pragma unroll
  for (int i = 0; i < R; i++) asm volatile("" : "+r"(d[i]) :: "memory"); }
__device__ __forceinline__ uint32_t desc_lo(uint32_t addr, uint32_t lbo_bytes) { return ((addr & 0x3FFFF) >> 4) | ((lbo_bytes >> 4) << 16); }
__device__ __forceinline__ uint64_t desc(uint32_t sb, uint32_t var = 0) {
  uint64_t d; asm("mov.b64 %0, {%1, %2};" : "=l"(d) : "r"(desc_lo(sb, 0) + var), "r"(0x40000040u)); return d; }
__host__ __device__ constexpr int doff(uint32_t off, uint32_t lbo_bytes) { return (off >> 4) | ((lbo_bytes >> 4) << 16); }
__device__ __forceinline__ float rcp_approx(float x) { float y; asm("rcp.approx.f32 %0, %1;" : "=f"(y) : "f"(x)); return y; }
__device__ __forceinline__ float rcp_fast(float x) { float y; asm("rcp.approx.ftz.f32 %0, %1;" : "=f"(y) : "f"(x)); return y; }
__device__ __forceinline__ float sqrt_approx(float x) { float y; asm("sqrt.approx.f32 %0, %1;" : "=f"(y) : "f"(x)); return y; }
__device__ __forceinline__ float sigmoid_f(float z) { return rcp_fast(1.f + ex2(z * -1.4426950408889634f)); }
__device__ __forceinline__ uint32_t norm2(uint32_t x, uint32_t mean2, float rsd) { const uint32_t d = sub_bf2(x, mean2); return pack_bf16(bf_lo(d) * rsd, bf_hi(d) * rsd); }
#define STALL(site)
#define TRACE(w, i)
#define TRACE1(w, i)
#define TRACEF(m, w, i)
#define TRACEO(i)

template <int OA, int OB> __device__ __forceinline__ void wgmma_ss_tb(float (&d)[128], uint64_t da, uint64_t db, int sd) {
  asm volatile("{\n.reg .pred p;\n.reg .b64 a, b;\nadd.s64 a, %128, %131;\nadd.s64 b, %129, %132;\nsetp.ne.b32 p, %130, 0;\n"
    "wgmma.mma_async.sync.aligned.m64n256k16.f32.bf16.bf16 {%0, %1, %2, %3, %4, %5, %6, %7, %8, %9, %10, %11, %12, %13, %14, %15, %16, %17, %18, %19, %20, %21, %22, %23, %24, %25, %26, %27, %28, %29, %30, %31, %32, %33, %34, %35, %36, %37, %38, %39, %40, %41, %42, %43, %44, %45, %46, %47, %48, %49, %50, %51, %52, %53, %54, %55, %56, %57, %58, %59, %60, %61, %62, %63, %64, %65, %66, %67, %68, %69, %70, %71, %72, %73, %74, %75, %76, %77, %78, %79, %80, %81, %82, %83, %84, %85, %86, %87, %88, %89, %90, %91, %92, %93, %94, %95, %96, %97, %98, %99, %100, %101, %102, %103, %104, %105, %106, %107, %108, %109, %110, %111, %112, %113, %114, %115, %116, %117, %118, %119, %120, %121, %122, %123, %124, %125, %126, %127}, a, b, p, 1, 1, 0, 1;\n}\n"
    : "+f"(d[0]), "+f"(d[1]), "+f"(d[2]), "+f"(d[3]), "+f"(d[4]), "+f"(d[5]), "+f"(d[6]), "+f"(d[7]), "+f"(d[8]), "+f"(d[9]), "+f"(d[10]), "+f"(d[11]), "+f"(d[12]), "+f"(d[13]), "+f"(d[14]), "+f"(d[15]), "+f"(d[16]), "+f"(d[17]), "+f"(d[18]), "+f"(d[19]), "+f"(d[20]), "+f"(d[21]), "+f"(d[22]), "+f"(d[23]), "+f"(d[24]), "+f"(d[25]), "+f"(d[26]), "+f"(d[27]), "+f"(d[28]), "+f"(d[29]), "+f"(d[30]), "+f"(d[31]), "+f"(d[32]), "+f"(d[33]), "+f"(d[34]), "+f"(d[35]), "+f"(d[36]), "+f"(d[37]), "+f"(d[38]), "+f"(d[39]), "+f"(d[40]), "+f"(d[41]), "+f"(d[42]), "+f"(d[43]), "+f"(d[44]), "+f"(d[45]), "+f"(d[46]), "+f"(d[47]), "+f"(d[48]), "+f"(d[49]), "+f"(d[50]), "+f"(d[51]), "+f"(d[52]), "+f"(d[53]), "+f"(d[54]), "+f"(d[55]), "+f"(d[56]), "+f"(d[57]), "+f"(d[58]), "+f"(d[59]), "+f"(d[60]), "+f"(d[61]), "+f"(d[62]), "+f"(d[63]), "+f"(d[64]), "+f"(d[65]), "+f"(d[66]), "+f"(d[67]), "+f"(d[68]), "+f"(d[69]), "+f"(d[70]), "+f"(d[71]), "+f"(d[72]), "+f"(d[73]), "+f"(d[74]), "+f"(d[75]), "+f"(d[76]), "+f"(d[77]), "+f"(d[78]), "+f"(d[79]), "+f"(d[80]), "+f"(d[81]), "+f"(d[82]), "+f"(d[83]), "+f"(d[84]), "+f"(d[85]), "+f"(d[86]), "+f"(d[87]), "+f"(d[88]), "+f"(d[89]), "+f"(d[90]), "+f"(d[91]), "+f"(d[92]), "+f"(d[93]), "+f"(d[94]), "+f"(d[95]), "+f"(d[96]), "+f"(d[97]), "+f"(d[98]), "+f"(d[99]), "+f"(d[100]), "+f"(d[101]), "+f"(d[102]), "+f"(d[103]), "+f"(d[104]), "+f"(d[105]), "+f"(d[106]), "+f"(d[107]), "+f"(d[108]), "+f"(d[109]), "+f"(d[110]), "+f"(d[111]), "+f"(d[112]), "+f"(d[113]), "+f"(d[114]), "+f"(d[115]), "+f"(d[116]), "+f"(d[117]), "+f"(d[118]), "+f"(d[119]), "+f"(d[120]), "+f"(d[121]), "+f"(d[122]), "+f"(d[123]), "+f"(d[124]), "+f"(d[125]), "+f"(d[126]), "+f"(d[127])
    : "l"(da), "l"(db), "r"(sd), "n"(OA), "n"(OB));
}
template <int OB> __device__ __forceinline__ void wgmma_rs_tb(float (&d)[128], uint32_t a0, uint32_t a1, uint32_t a2, uint32_t a3, uint64_t db, int sd) {
  asm volatile("{\n.reg .pred p;\n.reg .b64 b;\nadd.s64 b, %132, %134;\nsetp.ne.b32 p, %133, 0;\n"
    "wgmma.mma_async.sync.aligned.m64n256k16.f32.bf16.bf16 {%0, %1, %2, %3, %4, %5, %6, %7, %8, %9, %10, %11, %12, %13, %14, %15, %16, %17, %18, %19, %20, %21, %22, %23, %24, %25, %26, %27, %28, %29, %30, %31, %32, %33, %34, %35, %36, %37, %38, %39, %40, %41, %42, %43, %44, %45, %46, %47, %48, %49, %50, %51, %52, %53, %54, %55, %56, %57, %58, %59, %60, %61, %62, %63, %64, %65, %66, %67, %68, %69, %70, %71, %72, %73, %74, %75, %76, %77, %78, %79, %80, %81, %82, %83, %84, %85, %86, %87, %88, %89, %90, %91, %92, %93, %94, %95, %96, %97, %98, %99, %100, %101, %102, %103, %104, %105, %106, %107, %108, %109, %110, %111, %112, %113, %114, %115, %116, %117, %118, %119, %120, %121, %122, %123, %124, %125, %126, %127}, {%128, %129, %130, %131}, b, p, 1, 1, 1;\n}\n"
    : "+f"(d[0]), "+f"(d[1]), "+f"(d[2]), "+f"(d[3]), "+f"(d[4]), "+f"(d[5]), "+f"(d[6]), "+f"(d[7]), "+f"(d[8]), "+f"(d[9]), "+f"(d[10]), "+f"(d[11]), "+f"(d[12]), "+f"(d[13]), "+f"(d[14]), "+f"(d[15]), "+f"(d[16]), "+f"(d[17]), "+f"(d[18]), "+f"(d[19]), "+f"(d[20]), "+f"(d[21]), "+f"(d[22]), "+f"(d[23]), "+f"(d[24]), "+f"(d[25]), "+f"(d[26]), "+f"(d[27]), "+f"(d[28]), "+f"(d[29]), "+f"(d[30]), "+f"(d[31]), "+f"(d[32]), "+f"(d[33]), "+f"(d[34]), "+f"(d[35]), "+f"(d[36]), "+f"(d[37]), "+f"(d[38]), "+f"(d[39]), "+f"(d[40]), "+f"(d[41]), "+f"(d[42]), "+f"(d[43]), "+f"(d[44]), "+f"(d[45]), "+f"(d[46]), "+f"(d[47]), "+f"(d[48]), "+f"(d[49]), "+f"(d[50]), "+f"(d[51]), "+f"(d[52]), "+f"(d[53]), "+f"(d[54]), "+f"(d[55]), "+f"(d[56]), "+f"(d[57]), "+f"(d[58]), "+f"(d[59]), "+f"(d[60]), "+f"(d[61]), "+f"(d[62]), "+f"(d[63]), "+f"(d[64]), "+f"(d[65]), "+f"(d[66]), "+f"(d[67]), "+f"(d[68]), "+f"(d[69]), "+f"(d[70]), "+f"(d[71]), "+f"(d[72]), "+f"(d[73]), "+f"(d[74]), "+f"(d[75]), "+f"(d[76]), "+f"(d[77]), "+f"(d[78]), "+f"(d[79]), "+f"(d[80]), "+f"(d[81]), "+f"(d[82]), "+f"(d[83]), "+f"(d[84]), "+f"(d[85]), "+f"(d[86]), "+f"(d[87]), "+f"(d[88]), "+f"(d[89]), "+f"(d[90]), "+f"(d[91]), "+f"(d[92]), "+f"(d[93]), "+f"(d[94]), "+f"(d[95]), "+f"(d[96]), "+f"(d[97]), "+f"(d[98]), "+f"(d[99]), "+f"(d[100]), "+f"(d[101]), "+f"(d[102]), "+f"(d[103]), "+f"(d[104]), "+f"(d[105]), "+f"(d[106]), "+f"(d[107]), "+f"(d[108]), "+f"(d[109]), "+f"(d[110]), "+f"(d[111]), "+f"(d[112]), "+f"(d[113]), "+f"(d[114]), "+f"(d[115]), "+f"(d[116]), "+f"(d[117]), "+f"(d[118]), "+f"(d[119]), "+f"(d[120]), "+f"(d[121]), "+f"(d[122]), "+f"(d[123]), "+f"(d[124]), "+f"(d[125]), "+f"(d[126]), "+f"(d[127])
    : "r"(a0), "r"(a1), "r"(a2), "r"(a3), "l"(db), "r"(sd), "n"(OB));
}
template <int OA, int OB> __device__ __forceinline__ void wgmma_ss_tb(float (&d)[96], uint64_t da, uint64_t db, int sd) {
  asm volatile("{\n.reg .pred p;\n.reg .b64 a, b;\nadd.s64 a, %96, %99;\nadd.s64 b, %97, %100;\nsetp.ne.b32 p, %98, 0;\n"
    "wgmma.mma_async.sync.aligned.m64n192k16.f32.bf16.bf16 {%0, %1, %2, %3, %4, %5, %6, %7, %8, %9, %10, %11, %12, %13, %14, %15, %16, %17, %18, %19, %20, %21, %22, %23, %24, %25, %26, %27, %28, %29, %30, %31, %32, %33, %34, %35, %36, %37, %38, %39, %40, %41, %42, %43, %44, %45, %46, %47, %48, %49, %50, %51, %52, %53, %54, %55, %56, %57, %58, %59, %60, %61, %62, %63, %64, %65, %66, %67, %68, %69, %70, %71, %72, %73, %74, %75, %76, %77, %78, %79, %80, %81, %82, %83, %84, %85, %86, %87, %88, %89, %90, %91, %92, %93, %94, %95}, a, b, p, 1, 1, 0, 1;\n}\n"
    : "+f"(d[0]), "+f"(d[1]), "+f"(d[2]), "+f"(d[3]), "+f"(d[4]), "+f"(d[5]), "+f"(d[6]), "+f"(d[7]), "+f"(d[8]), "+f"(d[9]), "+f"(d[10]), "+f"(d[11]), "+f"(d[12]), "+f"(d[13]), "+f"(d[14]), "+f"(d[15]), "+f"(d[16]), "+f"(d[17]), "+f"(d[18]), "+f"(d[19]), "+f"(d[20]), "+f"(d[21]), "+f"(d[22]), "+f"(d[23]), "+f"(d[24]), "+f"(d[25]), "+f"(d[26]), "+f"(d[27]), "+f"(d[28]), "+f"(d[29]), "+f"(d[30]), "+f"(d[31]), "+f"(d[32]), "+f"(d[33]), "+f"(d[34]), "+f"(d[35]), "+f"(d[36]), "+f"(d[37]), "+f"(d[38]), "+f"(d[39]), "+f"(d[40]), "+f"(d[41]), "+f"(d[42]), "+f"(d[43]), "+f"(d[44]), "+f"(d[45]), "+f"(d[46]), "+f"(d[47]), "+f"(d[48]), "+f"(d[49]), "+f"(d[50]), "+f"(d[51]), "+f"(d[52]), "+f"(d[53]), "+f"(d[54]), "+f"(d[55]), "+f"(d[56]), "+f"(d[57]), "+f"(d[58]), "+f"(d[59]), "+f"(d[60]), "+f"(d[61]), "+f"(d[62]), "+f"(d[63]), "+f"(d[64]), "+f"(d[65]), "+f"(d[66]), "+f"(d[67]), "+f"(d[68]), "+f"(d[69]), "+f"(d[70]), "+f"(d[71]), "+f"(d[72]), "+f"(d[73]), "+f"(d[74]), "+f"(d[75]), "+f"(d[76]), "+f"(d[77]), "+f"(d[78]), "+f"(d[79]), "+f"(d[80]), "+f"(d[81]), "+f"(d[82]), "+f"(d[83]), "+f"(d[84]), "+f"(d[85]), "+f"(d[86]), "+f"(d[87]), "+f"(d[88]), "+f"(d[89]), "+f"(d[90]), "+f"(d[91]), "+f"(d[92]), "+f"(d[93]), "+f"(d[94]), "+f"(d[95])
    : "l"(da), "l"(db), "r"(sd), "n"(OA), "n"(OB));
}
template <int OB> __device__ __forceinline__ void wgmma_rs_tb(float (&d)[96], uint32_t a0, uint32_t a1, uint32_t a2, uint32_t a3, uint64_t db, int sd) {
  asm volatile("{\n.reg .pred p;\n.reg .b64 b;\nadd.s64 b, %100, %102;\nsetp.ne.b32 p, %101, 0;\n"
    "wgmma.mma_async.sync.aligned.m64n192k16.f32.bf16.bf16 {%0, %1, %2, %3, %4, %5, %6, %7, %8, %9, %10, %11, %12, %13, %14, %15, %16, %17, %18, %19, %20, %21, %22, %23, %24, %25, %26, %27, %28, %29, %30, %31, %32, %33, %34, %35, %36, %37, %38, %39, %40, %41, %42, %43, %44, %45, %46, %47, %48, %49, %50, %51, %52, %53, %54, %55, %56, %57, %58, %59, %60, %61, %62, %63, %64, %65, %66, %67, %68, %69, %70, %71, %72, %73, %74, %75, %76, %77, %78, %79, %80, %81, %82, %83, %84, %85, %86, %87, %88, %89, %90, %91, %92, %93, %94, %95}, {%96, %97, %98, %99}, b, p, 1, 1, 1;\n}\n"
    : "+f"(d[0]), "+f"(d[1]), "+f"(d[2]), "+f"(d[3]), "+f"(d[4]), "+f"(d[5]), "+f"(d[6]), "+f"(d[7]), "+f"(d[8]), "+f"(d[9]), "+f"(d[10]), "+f"(d[11]), "+f"(d[12]), "+f"(d[13]), "+f"(d[14]), "+f"(d[15]), "+f"(d[16]), "+f"(d[17]), "+f"(d[18]), "+f"(d[19]), "+f"(d[20]), "+f"(d[21]), "+f"(d[22]), "+f"(d[23]), "+f"(d[24]), "+f"(d[25]), "+f"(d[26]), "+f"(d[27]), "+f"(d[28]), "+f"(d[29]), "+f"(d[30]), "+f"(d[31]), "+f"(d[32]), "+f"(d[33]), "+f"(d[34]), "+f"(d[35]), "+f"(d[36]), "+f"(d[37]), "+f"(d[38]), "+f"(d[39]), "+f"(d[40]), "+f"(d[41]), "+f"(d[42]), "+f"(d[43]), "+f"(d[44]), "+f"(d[45]), "+f"(d[46]), "+f"(d[47]), "+f"(d[48]), "+f"(d[49]), "+f"(d[50]), "+f"(d[51]), "+f"(d[52]), "+f"(d[53]), "+f"(d[54]), "+f"(d[55]), "+f"(d[56]), "+f"(d[57]), "+f"(d[58]), "+f"(d[59]), "+f"(d[60]), "+f"(d[61]), "+f"(d[62]), "+f"(d[63]), "+f"(d[64]), "+f"(d[65]), "+f"(d[66]), "+f"(d[67]), "+f"(d[68]), "+f"(d[69]), "+f"(d[70]), "+f"(d[71]), "+f"(d[72]), "+f"(d[73]), "+f"(d[74]), "+f"(d[75]), "+f"(d[76]), "+f"(d[77]), "+f"(d[78]), "+f"(d[79]), "+f"(d[80]), "+f"(d[81]), "+f"(d[82]), "+f"(d[83]), "+f"(d[84]), "+f"(d[85]), "+f"(d[86]), "+f"(d[87]), "+f"(d[88]), "+f"(d[89]), "+f"(d[90]), "+f"(d[91]), "+f"(d[92]), "+f"(d[93]), "+f"(d[94]), "+f"(d[95])
    : "r"(a0), "r"(a1), "r"(a2), "r"(a3), "l"(db), "r"(sd), "n"(OB));
}
template <int OA, int OB> __device__ __forceinline__ void wgmma_ss_tb(float (&d)[64], uint64_t da, uint64_t db, int sd) {
  asm volatile("{\n.reg .pred p;\n.reg .b64 a, b;\nadd.s64 a, %64, %67;\nadd.s64 b, %65, %68;\nsetp.ne.b32 p, %66, 0;\n"
    "wgmma.mma_async.sync.aligned.m64n128k16.f32.bf16.bf16 {%0, %1, %2, %3, %4, %5, %6, %7, %8, %9, %10, %11, %12, %13, %14, %15, %16, %17, %18, %19, %20, %21, %22, %23, %24, %25, %26, %27, %28, %29, %30, %31, %32, %33, %34, %35, %36, %37, %38, %39, %40, %41, %42, %43, %44, %45, %46, %47, %48, %49, %50, %51, %52, %53, %54, %55, %56, %57, %58, %59, %60, %61, %62, %63}, a, b, p, 1, 1, 0, 1;\n}\n"
    : "+f"(d[0]), "+f"(d[1]), "+f"(d[2]), "+f"(d[3]), "+f"(d[4]), "+f"(d[5]), "+f"(d[6]), "+f"(d[7]), "+f"(d[8]), "+f"(d[9]), "+f"(d[10]), "+f"(d[11]), "+f"(d[12]), "+f"(d[13]), "+f"(d[14]), "+f"(d[15]), "+f"(d[16]), "+f"(d[17]), "+f"(d[18]), "+f"(d[19]), "+f"(d[20]), "+f"(d[21]), "+f"(d[22]), "+f"(d[23]), "+f"(d[24]), "+f"(d[25]), "+f"(d[26]), "+f"(d[27]), "+f"(d[28]), "+f"(d[29]), "+f"(d[30]), "+f"(d[31]), "+f"(d[32]), "+f"(d[33]), "+f"(d[34]), "+f"(d[35]), "+f"(d[36]), "+f"(d[37]), "+f"(d[38]), "+f"(d[39]), "+f"(d[40]), "+f"(d[41]), "+f"(d[42]), "+f"(d[43]), "+f"(d[44]), "+f"(d[45]), "+f"(d[46]), "+f"(d[47]), "+f"(d[48]), "+f"(d[49]), "+f"(d[50]), "+f"(d[51]), "+f"(d[52]), "+f"(d[53]), "+f"(d[54]), "+f"(d[55]), "+f"(d[56]), "+f"(d[57]), "+f"(d[58]), "+f"(d[59]), "+f"(d[60]), "+f"(d[61]), "+f"(d[62]), "+f"(d[63])
    : "l"(da), "l"(db), "r"(sd), "n"(OA), "n"(OB));
}
template <int OB> __device__ __forceinline__ void wgmma_rs_tb(float (&d)[64], uint32_t a0, uint32_t a1, uint32_t a2, uint32_t a3, uint64_t db, int sd) {
  asm volatile("{\n.reg .pred p;\n.reg .b64 b;\nadd.s64 b, %68, %70;\nsetp.ne.b32 p, %69, 0;\n"
    "wgmma.mma_async.sync.aligned.m64n128k16.f32.bf16.bf16 {%0, %1, %2, %3, %4, %5, %6, %7, %8, %9, %10, %11, %12, %13, %14, %15, %16, %17, %18, %19, %20, %21, %22, %23, %24, %25, %26, %27, %28, %29, %30, %31, %32, %33, %34, %35, %36, %37, %38, %39, %40, %41, %42, %43, %44, %45, %46, %47, %48, %49, %50, %51, %52, %53, %54, %55, %56, %57, %58, %59, %60, %61, %62, %63}, {%64, %65, %66, %67}, b, p, 1, 1, 1;\n}\n"
    : "+f"(d[0]), "+f"(d[1]), "+f"(d[2]), "+f"(d[3]), "+f"(d[4]), "+f"(d[5]), "+f"(d[6]), "+f"(d[7]), "+f"(d[8]), "+f"(d[9]), "+f"(d[10]), "+f"(d[11]), "+f"(d[12]), "+f"(d[13]), "+f"(d[14]), "+f"(d[15]), "+f"(d[16]), "+f"(d[17]), "+f"(d[18]), "+f"(d[19]), "+f"(d[20]), "+f"(d[21]), "+f"(d[22]), "+f"(d[23]), "+f"(d[24]), "+f"(d[25]), "+f"(d[26]), "+f"(d[27]), "+f"(d[28]), "+f"(d[29]), "+f"(d[30]), "+f"(d[31]), "+f"(d[32]), "+f"(d[33]), "+f"(d[34]), "+f"(d[35]), "+f"(d[36]), "+f"(d[37]), "+f"(d[38]), "+f"(d[39]), "+f"(d[40]), "+f"(d[41]), "+f"(d[42]), "+f"(d[43]), "+f"(d[44]), "+f"(d[45]), "+f"(d[46]), "+f"(d[47]), "+f"(d[48]), "+f"(d[49]), "+f"(d[50]), "+f"(d[51]), "+f"(d[52]), "+f"(d[53]), "+f"(d[54]), "+f"(d[55]), "+f"(d[56]), "+f"(d[57]), "+f"(d[58]), "+f"(d[59]), "+f"(d[60]), "+f"(d[61]), "+f"(d[62]), "+f"(d[63])
    : "r"(a0), "r"(a1), "r"(a2), "r"(a3), "l"(db), "r"(sd), "n"(OB));
}
template <int OA, int OB> __device__ __forceinline__ void wgmma_ss_ta(float (&d)[64], uint64_t da, uint64_t db, int sd) {
  asm volatile("{\n.reg .pred p;\n.reg .b64 a, b;\nadd.s64 a, %64, %67;\nadd.s64 b, %65, %68;\nsetp.ne.b32 p, %66, 0;\n"
    "wgmma.mma_async.sync.aligned.m64n128k16.f32.bf16.bf16 {%0, %1, %2, %3, %4, %5, %6, %7, %8, %9, %10, %11, %12, %13, %14, %15, %16, %17, %18, %19, %20, %21, %22, %23, %24, %25, %26, %27, %28, %29, %30, %31, %32, %33, %34, %35, %36, %37, %38, %39, %40, %41, %42, %43, %44, %45, %46, %47, %48, %49, %50, %51, %52, %53, %54, %55, %56, %57, %58, %59, %60, %61, %62, %63}, a, b, p, 1, 1, 1, 0;\n}\n"
    : "+f"(d[0]), "+f"(d[1]), "+f"(d[2]), "+f"(d[3]), "+f"(d[4]), "+f"(d[5]), "+f"(d[6]), "+f"(d[7]), "+f"(d[8]), "+f"(d[9]), "+f"(d[10]), "+f"(d[11]), "+f"(d[12]), "+f"(d[13]), "+f"(d[14]), "+f"(d[15]), "+f"(d[16]), "+f"(d[17]), "+f"(d[18]), "+f"(d[19]), "+f"(d[20]), "+f"(d[21]), "+f"(d[22]), "+f"(d[23]), "+f"(d[24]), "+f"(d[25]), "+f"(d[26]), "+f"(d[27]), "+f"(d[28]), "+f"(d[29]), "+f"(d[30]), "+f"(d[31]), "+f"(d[32]), "+f"(d[33]), "+f"(d[34]), "+f"(d[35]), "+f"(d[36]), "+f"(d[37]), "+f"(d[38]), "+f"(d[39]), "+f"(d[40]), "+f"(d[41]), "+f"(d[42]), "+f"(d[43]), "+f"(d[44]), "+f"(d[45]), "+f"(d[46]), "+f"(d[47]), "+f"(d[48]), "+f"(d[49]), "+f"(d[50]), "+f"(d[51]), "+f"(d[52]), "+f"(d[53]), "+f"(d[54]), "+f"(d[55]), "+f"(d[56]), "+f"(d[57]), "+f"(d[58]), "+f"(d[59]), "+f"(d[60]), "+f"(d[61]), "+f"(d[62]), "+f"(d[63])
    : "l"(da), "l"(db), "r"(sd), "n"(OA), "n"(OB));
}
template <int OB> __device__ __forceinline__ void wgmma_rs(float (&d)[64], uint32_t a0, uint32_t a1, uint32_t a2, uint32_t a3, uint64_t db, int sd) {
  asm volatile("{\n.reg .pred p;\n.reg .b64 b;\nadd.s64 b, %68, %70;\nsetp.ne.b32 p, %69, 0;\n"
    "wgmma.mma_async.sync.aligned.m64n128k16.f32.bf16.bf16 {%0, %1, %2, %3, %4, %5, %6, %7, %8, %9, %10, %11, %12, %13, %14, %15, %16, %17, %18, %19, %20, %21, %22, %23, %24, %25, %26, %27, %28, %29, %30, %31, %32, %33, %34, %35, %36, %37, %38, %39, %40, %41, %42, %43, %44, %45, %46, %47, %48, %49, %50, %51, %52, %53, %54, %55, %56, %57, %58, %59, %60, %61, %62, %63}, {%64, %65, %66, %67}, b, p, 1, 1, 0;\n}\n"
    : "+f"(d[0]), "+f"(d[1]), "+f"(d[2]), "+f"(d[3]), "+f"(d[4]), "+f"(d[5]), "+f"(d[6]), "+f"(d[7]), "+f"(d[8]), "+f"(d[9]), "+f"(d[10]), "+f"(d[11]), "+f"(d[12]), "+f"(d[13]), "+f"(d[14]), "+f"(d[15]), "+f"(d[16]), "+f"(d[17]), "+f"(d[18]), "+f"(d[19]), "+f"(d[20]), "+f"(d[21]), "+f"(d[22]), "+f"(d[23]), "+f"(d[24]), "+f"(d[25]), "+f"(d[26]), "+f"(d[27]), "+f"(d[28]), "+f"(d[29]), "+f"(d[30]), "+f"(d[31]), "+f"(d[32]), "+f"(d[33]), "+f"(d[34]), "+f"(d[35]), "+f"(d[36]), "+f"(d[37]), "+f"(d[38]), "+f"(d[39]), "+f"(d[40]), "+f"(d[41]), "+f"(d[42]), "+f"(d[43]), "+f"(d[44]), "+f"(d[45]), "+f"(d[46]), "+f"(d[47]), "+f"(d[48]), "+f"(d[49]), "+f"(d[50]), "+f"(d[51]), "+f"(d[52]), "+f"(d[53]), "+f"(d[54]), "+f"(d[55]), "+f"(d[56]), "+f"(d[57]), "+f"(d[58]), "+f"(d[59]), "+f"(d[60]), "+f"(d[61]), "+f"(d[62]), "+f"(d[63])
    : "r"(a0), "r"(a1), "r"(a2), "r"(a3), "l"(db), "r"(sd), "n"(OB));
}
template <int OA, int OB> __device__ __forceinline__ void wgmma_ss_ta(float (&d)[4], uint64_t da, uint64_t db, int sd) {
  asm volatile("{\n.reg .pred p;\n.reg .b64 a, b;\nadd.s64 a, %4, %7;\nadd.s64 b, %5, %8;\nsetp.ne.b32 p, %6, 0;\n"
    "wgmma.mma_async.sync.aligned.m64n8k16.f32.bf16.bf16 {%0, %1, %2, %3}, a, b, p, 1, 1, 1, 0;\n}\n"
    : "+f"(d[0]), "+f"(d[1]), "+f"(d[2]), "+f"(d[3])
    : "l"(da), "l"(db), "r"(sd), "n"(OA), "n"(OB));
}

constexpr uint32_t U = 16384;
constexpr uint32_t SM_QO = 2 * U, SM_W = 8 * U, SM_V = 8 * U, SM_K1 = 12 * U, SM_BAR = 14 * U;
constexpr uint32_t B_WF = SM_BAR, B_KF = SM_BAR + 48, B_CF = SM_BAR + 80, B_GATE = SM_BAR + 128, B_OF = SM_BAR + 136, B_EP = SM_BAR + 144, B_EXT = SM_BAR + 152, B_Q3 = SM_BAR + 168, B_ANN = SM_BAR + 176,
                   B_WE = SM_BAR + 192, B_KE = SM_BAR + 240, B_CE = SM_BAR + 288, B_OS = SM_BAR + 344;
constexpr uint32_t SM_EP = SM_BAR + 384;
constexpr uint32_t SM_ONE = SM_BAR + 388;
constexpr uint32_t SM_STAT = SM_BAR + 400, SM_EXT = SM_STAT + 512;
constexpr uint32_t SM_BAD = SM_EXT + 2048;
constexpr int SMEM_BYTES = SM_BAR + 3072;
__device__ __forceinline__ uint32_t c_slot(int s) { return (0xBADC10u >> (4 * s)) & 15; }

struct Params {
  const __nv_bfloat16 *x, *k, *v, *wq, *wo, *wr;
  __nv_bfloat16* out;
  Scratch* g;
};

__device__ __forceinline__ void release2(uint32_t rbar, int lane) { if (lane < 2) mbar_arrive_cluster(rbar); }
__device__ __forceinline__ void pin_after(uint32_t a, float e0, float e1) {
  asm volatile("{\n.reg .pred p;\nsetp.lt.f32 p, %1, %2;\n@p st.shared.u32 [%0], %0;\n}\n" :: "r"(a), "f"(e0), "f"(-e1) : "memory"); }
__device__ __forceinline__ void lds128_after(uint32_t& x, uint32_t& y, uint32_t& z, uint32_t& w, uint32_t a, float e0, float e1) {
  asm volatile("{\n.reg .pred p;\nsetp.geu.f32 p, %5, %6;\n@p ld.shared.v4.u32 {%0,%1,%2,%3}, [%4];\n}\n" : "+r"(x), "+r"(y), "+r"(z), "+r"(w) : "r"(a), "f"(e0), "f"(-e1) : "memory"); }
__device__ __forceinline__ uint32_t launch_of(unsigned long long ticket) { return (uint32_t)(ticket / 132) + 1; }

__device__ __forceinline__ void attn_slow(float (&o)[64], float& i0, float& i1, const __nv_bfloat16* __restrict__ X, const __nv_bfloat16* __restrict__ WQ, uint32_t st0, uint32_t st1,
                                          const __nv_bfloat16* __restrict__ K, const __nv_bfloat16* __restrict__ V, int lane) {
  uint32_t q[32];
  #pragma unroll
  for (int i = 0; i < 64; i++) o[i] = 0.f;
  const int g = lane >> 2, qd = lane & 3;
  #pragma unroll 1
  for (int k0 = 0; k0 < DM; k0 += 16) {
    uint32_t a[4];
    #pragma unroll
    for (int e = 0; e < 4; e++) {
      const uint32_t xv = *(const uint32_t*)(X + (size_t)(g + (e & 1) * 8) * DM + k0 + (e >> 1) * 8 + 2 * qd);
      const float mb = bf_lo((e & 1) ? st1 : st0);
      a[e] = pack_bf16(bf_lo(xv) - mb, bf_hi(xv) - mb);
    }
    const unsigned short* wr = (const unsigned short*)(WQ + (size_t)(k0 + 2 * qd) * (NH * DH) + g);
    #pragma unroll
    for (int nb = 0; nb < 16; nb++) {
      uint32_t b0 = (uint32_t)wr[nb * 8] | ((uint32_t)wr[nb * 8 + NH * DH] << 16);
      uint32_t b1 = (uint32_t)wr[nb * 8 + 8 * NH * DH] | ((uint32_t)wr[nb * 8 + 9 * NH * DH] << 16);
      asm volatile("mma.sync.aligned.m16n8k16.row.col.f32.bf16.bf16.f32 {%0,%1,%2,%3}, {%4,%5,%6,%7}, {%8,%9}, {%0,%1,%2,%3};"
        : "+f"(o[nb*4]), "+f"(o[nb*4+1]), "+f"(o[nb*4+2]), "+f"(o[nb*4+3]) : "r"(a[0]), "r"(a[1]), "r"(a[2]), "r"(a[3]), "r"(b0), "r"(b1));
    }
  }
  {
    const float r0 = rcp_approx(bf_hi(st0)) * SCALE_LOG2E, r1 = rcp_approx(bf_hi(st1)) * SCALE_LOG2E;
    #pragma unroll
    for (int i = 0; i < 16; i++) { q[2*i] = pack_bf16(o[4*i] * r0, o[4*i+1] * r0); q[2*i+1] = pack_bf16(o[4*i+2] * r1, o[4*i+3] * r1); }
    #pragma unroll
    for (int i = 0; i < 64; i++) o[i] = 0.f;
  }
  float m0 = -INFINITY, m1 = -INFINITY, l0 = 0.f, l1 = 0.f;
  #pragma unroll 1
  for (int n0 = 0; n0 < S_LEN; n0 += 16) {
    float s[8];
    #pragma unroll
    for (int i = 0; i < 8; i++) s[i] = 0.f;
    #pragma unroll
    for (int nb = 0; nb < 2; nb++) {
      const uint32_t* kr = (const uint32_t*)(K + (size_t)(n0 + nb * 8 + g) * DH) + qd;
      #pragma unroll
      for (int kk = 0; kk < 8; kk++) {
        uint32_t b0 = kr[kk * 8], b1 = kr[kk * 8 + 4];
        asm volatile("mma.sync.aligned.m16n8k16.row.col.f32.bf16.bf16.f32 {%0,%1,%2,%3}, {%4,%5,%6,%7}, {%8,%9}, {%0,%1,%2,%3};"
          : "+f"(s[nb*4]), "+f"(s[nb*4+1]), "+f"(s[nb*4+2]), "+f"(s[nb*4+3]) : "r"(q[kk*4]), "r"(q[kk*4+1]), "r"(q[kk*4+2]), "r"(q[kk*4+3]), "r"(b0), "r"(b1));
      }
    }
    float x0 = fmaxf(fmaxf(s[0], s[1]), fmaxf(s[4], s[5])), x1 = fmaxf(fmaxf(s[2], s[3]), fmaxf(s[6], s[7]));
    x0 = fmaxf(x0, __shfl_xor_sync(0xffffffff, x0, 1)); x1 = fmaxf(x1, __shfl_xor_sync(0xffffffff, x1, 1));
    x0 = fmaxf(x0, __shfl_xor_sync(0xffffffff, x0, 2)); x1 = fmaxf(x1, __shfl_xor_sync(0xffffffff, x1, 2));
    const float n0m = fmaxf(m0, x0), n1m = fmaxf(m1, x1);
    const float sh0 = (n0m == -INFINITY) ? 0.f : n0m, sh1 = (n1m == -INFINITY) ? 0.f : n1m;
    const float c0 = ex2(m0 - sh0), c1 = ex2(m1 - sh1);
    m0 = n0m; m1 = n1m;
    s[0] = ex2(s[0] - sh0); s[1] = ex2(s[1] - sh0); s[4] = ex2(s[4] - sh0); s[5] = ex2(s[5] - sh0);
    s[2] = ex2(s[2] - sh1); s[3] = ex2(s[3] - sh1); s[6] = ex2(s[6] - sh1); s[7] = ex2(s[7] - sh1);
    l0 = l0 * c0 + (s[0] + s[1]) + (s[4] + s[5]); l1 = l1 * c1 + (s[2] + s[3]) + (s[6] + s[7]);
    const uint32_t a0 = pack_bf16(s[0], s[1]), a1 = pack_bf16(s[2], s[3]), a2 = pack_bf16(s[4], s[5]), a3 = pack_bf16(s[6], s[7]);
    const unsigned short* vr = (const unsigned short*)(V + (size_t)(n0 + 2 * qd) * DH + g);
    #pragma unroll
    for (int nb = 0; nb < 16; nb++) {
      uint32_t b0 = (uint32_t)vr[nb * 8] | ((uint32_t)vr[nb * 8 + DH] << 16);
      uint32_t b1 = (uint32_t)vr[nb * 8 + 8 * DH] | ((uint32_t)vr[nb * 8 + 9 * DH] << 16);
      o[nb*4] *= c0; o[nb*4+1] *= c0; o[nb*4+2] *= c1; o[nb*4+3] *= c1;
      asm volatile("mma.sync.aligned.m16n8k16.row.col.f32.bf16.bf16.f32 {%0,%1,%2,%3}, {%4,%5,%6,%7}, {%8,%9}, {%0,%1,%2,%3};"
        : "+f"(o[nb*4]), "+f"(o[nb*4+1]), "+f"(o[nb*4+2]), "+f"(o[nb*4+3]) : "r"(a0), "r"(a1), "r"(a2), "r"(a3), "r"(b0), "r"(b1));
    }
  }
  l0 += __shfl_xor_sync(0xffffffff, l0, 1); l1 += __shfl_xor_sync(0xffffffff, l1, 1);
  l0 += __shfl_xor_sync(0xffffffff, l0, 2); l1 += __shfl_xor_sync(0xffffffff, l1, 2);
  i0 = rcp_approx(l0); i1 = rcp_approx(l1);
}

__device__ __forceinline__ void flag_if(uint32_t a, bool c) { asm volatile("{\n.reg .pred p;\nsetp.ne.u32 p, %1, 0;\n@p st.shared.u8 [%0], 1;\n}\n" :: "r"(a), "r"((uint32_t)c) : "memory"); }
__device__ __forceinline__ void row_scale(float& l0, float& l1, int one, uint32_t flag) {
  l0 += __shfl_xor_sync(0xffffffff, l0, one); l1 += __shfl_xor_sync(0xffffffff, l1, one);
  l0 += __shfl_xor_sync(0xffffffff, l0, 2); l1 += __shfl_xor_sync(0xffffffff, l1, 2);
  flag_if(flag, !((l0 >= 0.00390625f) && (l0 <= 1.8446744e19f) && (l1 >= 0.00390625f) && (l1 <= 1.8446744e19f)));
  l0 = rcp_fast(l0); l1 = rcp_fast(l1);
}
__device__ __forceinline__ uint32_t taint(uint32_t z, uint32_t a, uint32_t b) { asm("fma.rn.bf16x2 %0, %1, %2, %0;" : "+r"(z) : "r"(a), "r"(b)); return z; }
__device__ __forceinline__ bool tainted(uint32_t z) { return (taint(0u, z, 0u) & 0x7fff7fffu) != 0; }

__device__ __forceinline__ int kv_tile(int j) { return j < 32 ? j ^ 16 : j; }
__device__ __forceinline__ uint32_t qo_slot(int h) { return SM_QO + ((0x3102 >> (4 * h)) & 3) * 2 * U; }
__device__ __forceinline__ uint32_t o_addr(uint32_t wr, int lane) { return wr + (lane & 15) * 128 + (((lane >> 4) ^ (lane & 7)) << 4); }
template <bool CHECK> __device__ __forceinline__ uint32_t store_o(uint32_t a, const float (&o)[64], float i0, float i1) {
  uint32_t z = 0;
  #pragma unroll
  for (int i = 0; i < 8; i++) {
    const uint32_t w0 = pack_bf16(o[8*i] * i0, o[8*i+1] * i0), w1 = pack_bf16(o[8*i+2] * i1, o[8*i+3] * i1), w2 = pack_bf16(o[8*i+4] * i0, o[8*i+5] * i0), w3 = pack_bf16(o[8*i+6] * i1, o[8*i+7] * i1);
    stsm4((a ^ ((i & 3) << 5)) + (i >> 2) * U, w0, w1, w2, w3);
    if (CHECK) z = taint(taint(z, w0, w1), w2, w3);
  }
  return z;
}

__device__ __noinline__ void redo_heads(const Params& P, uint32_t sb, uint32_t bad, int row0, int head0) {
  const int lane = threadIdx.x & 31;
  const uint32_t st0 = lds32(sb + SM_STAT + ((row0 & 127) + (lane >> 2)) * 4), st1 = lds32(sb + SM_STAT + ((row0 & 127) + 8 + (lane >> 2)) * 4);
  #pragma unroll 1
  for (int h = 0; h < 4; h++) {
    if (!((bad >> (8 * h)) & 1)) continue;
    float o[64], i0, i1;
    const int head = head0 + (kv_tile(h * 16) >> 4);
    attn_slow(o, i0, i1, P.x + (size_t)row0 * DM, P.wq + head * DH, st0, st1, P.k + (size_t)head * S_LEN * DH, P.v + (size_t)head * S_LEN * DH, lane);
    store_o<false>(o_addr(sb + (row0 & 127) * 128, lane) + qo_slot(h), o, i0, i1);
  }
}

template <int K> struct IC { static constexpr int v = K; };
template <int K, int N, class F> __device__ __forceinline__ void static_for(F&& f) { if constexpr (K < N) { f(IC<K>{}); static_for<K + 1, N>(f); } }
template <uint32_t OFF, int SITE> __device__ __forceinline__ void mma_qk(float (&s)[64], const uint32_t (&q)[32], uint64_t d0) {
  wg_fence();
  static_for<0, 8>([&](auto kc) { constexpr int k = decltype(kc)::v; wgmma_rs<doff(OFF, 16) - SITE + (k / 4) * 1024 + (k % 4) * 2>(s, q[k*4], q[k*4+1], q[k*4+2], q[k*4+3], d0, k > 0); });
  wg_commit();
}
template <uint32_t OFF, int SITE> __device__ __forceinline__ void mma_pv(float (&o)[64], const uint32_t (&p)[32], uint64_t d0, bool keep) {
  wg_fence();
  static_for<0, 8>([&](auto kc) { constexpr int k = decltype(kc)::v; wgmma_rs_tb<doff(OFF, U) - SITE + k * 128>(o, p[k*4], p[k*4+1], p[k*4+2], p[k*4+3], d0, (k > 0) || keep); });
  wg_commit();
}
template <int I0, int I1>
__device__ __forceinline__ void exp_rows(float (&s)[64], float (&l)[2]) {
  #pragma unroll
  for (int i = I0; i < I1; i += 2) {
    s[i] = ex2(s[i]); s[i+1] = ex2(s[i+1]);
    l[(i >> 1) & 1] += s[i] + s[i+1];
  }
}

template <int KS, bool EDGE>
__device__ __forceinline__ void attn_step(uint32_t sb, uint32_t rb, uint32_t wr, uint32_t qa, int wg, int lane, int j, int ph, float (&s)[64], float (&o)[64], uint32_t (&p)[32], uint32_t (&q)[32],
                                          float (&l)[2], bool& ready, Scratch* g, unsigned (&tz)[3]) {
  constexpr bool FIRST = EDGE && !KS, LAST = EDGE && KS;
  TRACEF(2, wg, 32 + j);
  STALL(1);
  if (!ready) mbar_wait(sb + B_KF + KS * 8, ph);
  bar_sync(1 + wg, 256);
  mma_qk<KS * SM_K1, EDGE>(s, q, desc(sb, EDGE));
  if (!ready) mbar_wait(sb + B_KF + 24 - KS * 8, KS ? ph : ph ^ 1);
  mma_pv<SM_V + (1 - KS) * 2 * U, EDGE>(o, p, desc(sb, EDGE), !KS || LAST || ((j & 15) != 1));
  bar_arrive(1 + (wg ^ 1), 256);
  const int one = FIRST ? lds32(sb + SM_ONE) : 1;
  wg_wait<1>();
  fence_regs(s);
  release2(rb + B_KE + KS * 8, lane);
  float i0 = l[0], i1 = l[1];
  if (FIRST) { row_scale(i0, i1, one, sb + SM_BAD - 1 + ((wr - sb) >> 9) + (j >> 4)); l[0] = fminf(i0, 0.f); l[1] = fminf(i1, 0.f); }
  constexpr int DP = FIRST ? DPOSF : (LAST && DPOS < 7 * QSP ? 7 * QSP : DPOS);
  if (LAST) {
    fence_regs(q);
    const uint32_t a = qa + qo_slot(j >> 4);
    static_for<0, 8>([&](auto ic) { constexpr int i = decltype(ic)::v;
      lds128_after(q[4*i], q[4*i+1], q[4*i+2], q[4*i+3], a + (i >> 2) * U + (i & 3) * 512, l[0], l[1]);
      exp_rows<i * QSP, i < 7 ? (i + 1) * QSP : DP>(s, l);
    });
  } else exp_rows<0, DP>(s, l);
  pin_after(sb + SM_BAD, l[0], l[1]);
  exp_rows<DP, 64>(s, l);
  wg_wait<0>();
  fence_regs(o); fence_regs(p);
  release2(rb + B_KE + 24 - KS * 8, lane);
  ready = mbar_test2(sb + B_KF + 16 + KS * 8, ph, sb + B_KF + 8 - KS * 8, KS ? ph ^ 1 : ph);
  if (FIRST) {
    const int h = (j >> 4) - 1;
    store_o<false>(o_addr(wr, lane) + qo_slot(h), o, i0, i1);
    if (lane == 0) mbar_arrive(sb + B_OS + h * 8);
  }
  #pragma unroll
  for (int i = 0; i < 32; i++) p[i] = pack_bf16(s[2*i], s[2*i+1]);
}

template <int SITE> __device__ __forceinline__ void mma_c(float (&acc)[64], uint32_t sb, int slot, int h, int arrive_bar) {
  const uint64_t a = desc(sb, c_slot(slot) * 1024 + SITE), b = desc(sb, h * 2048 + SITE);
  wg_fence();
  static_for<0, 8>([&](auto kc) { constexpr int k = decltype(kc)::v;
    if (k == C_EARLY && arrive_bar) bar_arrive(arrive_bar, 256);
    wgmma_ss_ta<doff(0, 16) - SITE + k * 128, doff(SM_QO, 16) - SITE + (k >> 2) * 1024 + (k & 3) * 2>(acc, a, b, k > 0 || h > 0);
  });
  wg_commit();
}

__device__ __forceinline__ void side_cta(const Params& P, const CUtensorMap* tmX, const CUtensorMap* tmW, const CUtensorMap* tmG, const CUtensorMap* tmU,
                                         const CUtensorMap* tmD, uint32_t sb, int m) {
  const int tid = threadIdx.x, warp = __shfl_sync(0xffffffff, tid >> 5, 0), lane = tid & 31;
  const uint32_t XS = sb + 12 * U, HS = XS + 10240, BF = sb + SM_BAR, BE = BF + 96, XF = BE + 96, XE = XF + 32, BW = XE + 32, SEL = BW + 16, KEY = SEL + 64;
  Scratch* const g = P.g;
  const int nj = m < 3 ? 14 : 12, nd = m < 3 ? 4 : 3, f0 = m * 448;
  if (elect_one()) { mbar_init(BF + warp * 8, 1); mbar_init(BE + warp * 8, 4); if (warp < 9) mbar_init(XF + warp * 8, (warp & 4) ? 8 : 1); }
  if (tid == 32) sts32(SEL + 32, launch_of(atomicAdd(&g->ticket, 1ull)));
  __syncthreads();
  const uint32_t launch = lds32(SEL + 32);
  if (warp == 0) {
    if (elect_one()) {
      mbar_expect_tx(BW, 10 * U);
      #pragma unroll 1
      for (int i = 0; i < 10; i++) tma_load_2d(sb + i * U, tmW, BW, m * 1024 + (i < 5 ? 448 : 960), (i < 5 ? i : i - 5) * 128);
    }
    #pragma unroll 1
    for (int n = 0, qt = 0, c = 0; n < 160; n++) {
      const uint32_t bar = XF + (n & 3) * 8;
      mbar_wait(bar + 32, ((n >> 2) & 1) ^ 1);
      if (elect_one()) {
        mbar_expect_tx(bar, U);
        tma_load_2d(sb + (10 + (n & 3)) * U, tmX, bar, c * 64, qt * 128);
        if (c == 0 && qt < 15) l2_prefetch(P.x + (size_t)(qt * 128 + 128 + m * 32) * DM, 32 * DM * 2);
      }
      if (++c == 10) { c = 0; qt++; }
    }
  } else if (warp < 3) {
    #pragma unroll 1
    for (int qt = 0; qt < 16; qt++) {
      bar_sync(1 + warp, 160);
      if (lane == 0) flag_add_release(&g->q3_done[m].v);
      __syncwarp();
    }
  } else if (warp >= 4) {
    float acc[64], cs[32];
    mbar_wait(BW, 0);
    #pragma unroll 1
    for (int c = 0; c < 10; c++) {
      wg_fence();
      static_for<0, 4>([&](auto kc) { constexpr int k = decltype(kc)::v;
        wgmma_rs_tb<doff(0, 5 * U) + k * 128>(acc, 0x3f803f80u, 0x3f803f80u, 0x3f803f80u, 0x3f803f80u, desc(sb, c * 512), k || c); });
      wg_commit();
      wg_wait<0>();
    }
    fence_regs(acc);
    #pragma unroll
    for (int i = 0; i < 32; i++) cs[i] = -acc[(i >> 1) * 4 + (i & 1)];
    fence_regs(cs);
    #pragma unroll 1
    for (int qt = 0, n = 0; qt < 16; qt++) {
      const uint32_t* const sp = g->stat + qt * 128 + (warp - 4) * 16 + (lane >> 2);
      uint32_t st0, st1;
      #pragma unroll 1
      for (int c = 0; c < 10; c++, n++) {
        const uint64_t a = desc(sb, (n & 3) * 1024 + (warp >> 3) * 512), b = desc(sb, c * 512);
        mbar_wait(XF + (n & 3) * 8, (n >> 2) & 1);
        wg_fence();
        static_for<0, 4>([&](auto kc) { constexpr int k = decltype(kc)::v; wgmma_ss_tb<doff(10 * U, 16) + k * 2, doff(0, 5 * U) + k * 128>(acc, a, b, k || c); });
        wg_commit();
        if (c == 9) { st0 = ldg32(sp); st1 = ldg32(sp + 8); }
        wg_wait<1>();
        if (c && lane == 0) mbar_arrive(XE + ((n - 1) & 3) * 8);
      }
      #pragma unroll 1
      for (int it = 0; __any_sync(0xffffffff, tag_miss(st0, st1, launch << 31) >> 31) && it < MAXPOLL; it++) { st0 = ldg32(sp); st1 = ldg32(sp + 8); }
      st0 &= 0x7fffffffu; st1 &= 0x7fffffffu;
      const float rs[2] = {rcp_fast(bf_hi(st0)) * SCALE_LOG2E, rcp_fast(bf_hi(st1)) * SCALE_LOG2E}, nm[2] = {bf_lo(st0), bf_lo(st1)};
      wg_wait<0>();
      fence_regs(acc);
      if (lane == 0) mbar_arrive(XE + ((n - 1) & 3) * 8);
      STALL(7);
      uint4* const dst = g->q3 + (qt * 8 + m * 2) * 1024 + (warp - 4) * 128 + lane;
      #pragma unroll
      for (int e = 0; e < 8; e++) {
        uint32_t w[4];
        #pragma unroll
        for (int i = 0; i < 4; i++)
          w[i] = pack_bf16(fmaf(nm[i & 1], cs[4*e + (i & 2)], acc[8*e + 2*i]) * rs[i & 1], fmaf(nm[i & 1], cs[4*e + (i & 2) + 1], acc[8*e + 2*i + 1]) * rs[i & 1]);
        dst[(e >> 2) * 1024 + (e & 3) * 32] = make_uint4(w[0], w[1], w[2], w[3]);
      }
      bar_sync(1 + (warp >> 2), 160);
    }
  }
  if (tid == 96) flag_wait(&g->cnt_gate.v, launch * 256);
  __syncthreads();
  TRACE(0, 1);
  if (tid >= 256 && tid < 320) sts128(HS + 3072 + tid * 16, 0, 0, 0, 0);
  if (warp < 4) {
    uint4 k4[4];
    #pragma unroll
    for (int i = 0; i < 4; i++) k4[i] = ld_relaxed4(g->key + warp * 512 + i * 128 + lane * 4);
    uint32_t bound = 0;
    #pragma unroll 1
    for (int c = 0; c < TOPC; c++) {
      uint32_t b = 0;
      #pragma unroll
      for (int i = 0; i < 4; i++) b = max(max(max(b, k4[i].x - bound), k4[i].y - bound), max(k4[i].z - bound, k4[i].w - bound));
      bound += __reduce_max_sync(0xffffffff, b);
      if (lane == 0) sts32(KEY + (warp * TOPC + c) * 4, bound);
    }
    bar_sync(1, 128);
    const uint32_t v = lds32(KEY + lane * 4);
    int n = 0;
    #pragma unroll 1
    for (int j = 0; j < 32; j++) n += __shfl_sync(0xffffffff, v, j) > v;
    if (n < TOPC) sts32(SEL + n * 4, v);
  }
  __syncthreads();
  #pragma unroll 1
  for (int i = tid; i < TOPC * 80; i += 384) {
    const int row = 0xffff - (lds32(SEL + (i & 7) * 4) & 0xffff);
    const uint32_t st = ldg32(g->stat + row), m2 = __byte_perm(st, 0, 0x1010);
    const float rsd = rcp_fast(bf_hi(st & 0x7fffffffu));
    const uint4 v = ldg_nc((const uint4*)(P.x + (size_t)row * DM) + (i >> 3));
    sts128(XS + i * 16, norm2(v.x, m2, rsd), norm2(v.y, m2, rsd), norm2(v.z, m2, rsd), norm2(v.w, m2, rsd));
  }
  proxy_fence();
  __syncthreads();
  TRACE(0, 2);
  uint32_t sl = 0, ph = 0;
  if (warp == 0) {
    #pragma unroll 1
    for (int job = 0; job < nj + 10; job++) {
      const bool up = job < nj;
      #pragma unroll 1
      for (int i = 0; i < (up ? 5 : nd); i++) {
        mbar_wait(BE + sl * 8, ph ^ 1);
        if (elect_one()) {
          mbar_expect_tx(BF + sl * 8, U);
          tma_load_2d(sb + sl * U, up ? ((job & 1) ? tmU : tmG) : tmD, BF + sl * 8, up ? f0 + (job >> 1) * 64 : (job - nj) * 64, (up ? 0 : f0) + i * 128);
        }
        if (++sl == 12) { sl = 0; ph ^= 1; }
      }
    }
  } else if ((warp >> 2) == 1) {
    float gs[4];
    #pragma unroll 1
    for (int job = 0; job < nj + 10; job++) {
      const bool up = job < nj;
      if (job == nj) { proxy_fence(); bar_sync(1, 128); }
      float ac[4][4], acc[4];
      uint32_t prev = 0;
      #pragma unroll 1
      for (int i = 0; i < (up ? 5 : nd); i++) {
        const uint64_t a = desc(sb, sl * 1024 + 0x10000), b = (uint64_t)(desc_lo(up ? XS : HS, 128) + i * 128) | (8ull << 32);
        mbar_wait(BF + sl * 8, ph);
        wg_fence();
        static_for<0, 8>([&](auto kc) { constexpr int k = decltype(kc)::v; wgmma_ss_ta<k * 128, k * 16>(ac[k & 3], a, b, k > 3 || i > 0); });
        wg_commit();
        wg_wait<1>();
        if (i && lane == 0) mbar_arrive(prev);
        prev = BE + sl * 8;
        if (++sl == 12) { sl = 0; ph ^= 1; }
      }
      wg_wait<0>();
      if (lane == 0) mbar_arrive(prev);
      #pragma unroll
      for (int e = 0; e < 4; e++) fence_regs(ac[e]);
      #pragma unroll
      for (int e = 0; e < 4; e++) acc[e] = (ac[0][e] + ac[1][e]) + (ac[2][e] + ac[3][e]);
      STALL(9);
      const int f = (warp & 3) * 16 + (lane >> 2), tk = (lane & 3) * 2;
      if (!up) {
        float* y = g->ypart + (m * DM + (job - nj) * 64 + f) * TOPC + tk;
        *(float2*)y = make_float2(acc[0], acc[1]); *(float2*)(y + 8 * TOPC) = make_float2(acc[2], acc[3]);
      } else {
        #pragma unroll
        for (int e = 0; e < 4; e++) {
          const float z = rbf(acc[e]);
          if (job & 1) asm volatile("st.shared.u16 [%0], %1;" :: "r"(HS + (job >> 1) * 1024 + ((f >> 3) + (e >> 1)) * 128 + (tk + (e & 1)) * 16 + (f & 7) * 2), "h"((uint16_t)pack_bf16(gs[e] * z, 0.f)) : "memory");
          gs[e] = rbf(z * sigmoid_f(z));
        }
      }
    }
  }
  __syncthreads();
  TRACE(0, 3);
  if (tid == 0) { flag_add_release(&g->cnt_mod.v); flag_wait(&g->cnt_mod.v, launch * 4, 50); }
  __syncthreads();
  #pragma unroll 1
  for (int i = tid; i < 2 * DM; i += 384) {
    const int t = 2 * m + (i & 1), col = i >> 1;
    const uint32_t key = lds32(SEL + t * 4);
    const float* yp = g->ypart + col * TOPC + t;
    const float y = rbf((__ldcg(yp) + __ldcg(yp + TOPC * DM)) + (__ldcg(yp + 2 * TOPC * DM) + __ldcg(yp + 3 * TOPC * DM)));
    const float rs = rbf(sigmoid_f(bf_hi((key >> 31) ? key & 0x7fffffffu : ~key)));
    const uint32_t xn = lds32(XS + (col >> 3) * 128 + t * 16 + (col & 6) * 2);
    const float z = rbf(((col & 1) ? bf_hi(xn) : bf_lo(xn)) + rbf(y * rs));
    g->gate[(size_t)(0xffff - (key & 0xffff)) * DM + col] = __float2bfloat16_rn(z * sigmoid_f(z));
  }
  __syncthreads();
  if (tid == 0) flag_add_release(&g->mod_done.v);
  TRACE(0, 4);
}

__global__ void __cluster_dims__(2, 1, 1) __launch_bounds__(384, 1) fused_kernel(const __grid_constant__ CUtensorMap tmX, const __grid_constant__ CUtensorMap tmW4,
    const __grid_constant__ CUtensorMap tmW3, const __grid_constant__ CUtensorMap tmW1,
    const __grid_constant__ CUtensorMap tmK, const __grid_constant__ CUtensorMap tmV, const __grid_constant__ CUtensorMap tmWO,
    const __grid_constant__ CUtensorMap tmG, const __grid_constant__ CUtensorMap tmU, const __grid_constant__ CUtensorMap tmD,
    const __grid_constant__ CUtensorMap tmGate, const __grid_constant__ Params P) {
  extern __shared__ __align__(1024) uint8_t smem_raw[];
  const uint32_t sb = smem_u32(smem_raw);
  const int tid = threadIdx.x, lane = tid & 31;
  const int rank = blockIdx.x & 1, cl = blockIdx.x >> 1;
  if (cl >= 64) {
    side_cta(P, &tmX, &tmW1, &tmG, &tmU, &tmD, sb, blockIdx.x & 3);
    return;
  }
  const int rr = ((cl - 36) * 37) >> 8, kk = cl - 36 - rr * 7, qp = sel_lt(cl, 4, PH, sel_lt(cl, 36, (cl - 4) & 7, kk + sel_lt(kk, PH, 0, 1)));
  const int hg = sel_lt(cl, 4, cl + 4, sel_lt(cl, 36, (cl - 4) >> 3, 4 + rr)), qt = qp * 2 + rank;
  const int warp = __shfl_sync(0xffffffff, tid >> 5, 0), wgi = warp >> 2;
  Scratch* const g = P.g;
  if (elect_one()) {
    #pragma unroll
    for (int i = 0; i < 4; i++) mbar_init(sb + SM_BAR + warp * 32 + i * 8, 1 << ((0x333444000000ull >> (4 * warp)) & 7));
    if (warp == 0) {
      mbar_expect_tx(sb + B_WF, 2 * U);
      tma_load_2d(sb + 2 * U, &tmX, sb + B_WF, 0, qt * 128);
      tma_load_3d(sb + SM_W, &tmW4, sb + B_WF, 0, 0, hg * 8);
      tma_load_3d(sb + SM_W + 8192, &tmW4, sb + B_WF, 0, 16, hg * 8);
    }
    asm volatile("fence.mbarrier_init.release.cluster;" ::: "memory");
  }
  __syncwarp();
  cluster_arrive();
  unsigned long long ticket = 0;
  if (tid == 64) asm volatile("atom.relaxed.gpu.global.add.u64 %0, [%1], 1;" : "=l"(ticket) : "l"(&g->ticket) : "memory");
  cluster_wait();
  if (warp == 0 && elect_one()) {
    #pragma unroll
    for (int i = 1; i < 6; i++) {
      mbar_expect_tx(sb + B_WF + i * 8, (i & 1) ? U : 2 * U);
      tma_load_3d_mc(sb + SM_W + i * U + rank * 8192, &tmW4, sb + B_WF + i * 8, 0, i * 32 + rank * 16, hg * 8);
      if (!(i & 1)) tma_load_2d(sb + (2 + i / 2) * U, &tmX, sb + B_WF + i * 8, i * 32, qt * 128);
    }
  }
  STALL(14);
  if (wgi == 0) {
    asm volatile("setmaxnreg.dec.sync.aligned.u32 56;");
    uint32_t w0 = 0;
    if (warp == 1 || warp == 2) {
      if (warp == 2 && lane < 12) sts128(sb + SM_EXT + 1024 + (lane >= 6 ? 1024 - 96 : 0) + lane * 16, 0, 0, 0, 0);
      __syncwarp();
      if (tid == 64) { sts32(sb + SM_ONE, 1); sts32(sb + SM_EP, launch_of(ticket)); mbar_arrive(sb + B_EP); }
      __syncwarp();
      mbar_pace(sb + B_WF, 0);
      TRACEO(1);
      auto warm = [&](int ps, int i0, int i1) {
        const uint32_t o = (((qt >> 2) * 4 + (lane & 3) + (lane >> 2) * 16) * (NH * DH) + hg * 512 + ps * 256 + (qt & 3) * 64) * 2;
        #pragma unroll 1
        for (int i = i0; i < i1; i++) {
          asm volatile("prefetch.global.L2 [%0];" :: "l"(at<char>(P.wq, o + i * 256 * (NH * DH))) : "memory");
          if (ps) __nanosleep(W1SL);
        }
      };
      if (elect_one()) l2_prefetch(P.x + (size_t)(qt * 128 + hg * 16 + warp * 8 - 6) * DM, 6 * DM * 2);
      if (warp == 1) warm(0, 1, 5);
      auto publish = [&](uint32_t w) { if (!(lane & 12)) st_relaxed(at<uint32_t>(g->stat, (qt * 128 + hg * 16 + (warp - 1) * 8 + (lane & 3) * 2 + (lane >> 4)) * 4), w ^ (lds32(sb + SM_EP) << 31)); };
      mbar_wait(sb + B_EP, 0);
      publish(0x80000000u);
      const int r0 = qt * 128 + hg * 16 + (warp - 1) * 8 + (lane >> 4);
      const uint32_t e = r0 * DM * 2 + (lane & 15) * 16;
      uint4 vn[5];
      #pragma unroll
      for (int i = 0; i < 5; i++) vn[i] = ldg_nc(at<uint4>(P.x, e) + i * 16);
      #pragma unroll 1
      for (int it = 0; it < 4; it++) {
        uint4 v[5];
        #pragma unroll
        for (int i = 0; i < 5; i++) { v[i] = vn[i]; if (it < 3) vn[i] = ldg_nc(at<uint4>(P.x, e + (it + 1) * 2560) + i * 16); }
        const float x0 = bf_lo(__shfl_sync(0xffffffff, v[0].x, lane & 16));
        float m1 = 0.f, s1 = 0.f;
        #pragma unroll
        for (int i = 0; i < 5; i++) {
          const uint32_t vw[4] = {v[i].x, v[i].y, v[i].z, v[i].w};
          #pragma unroll
          for (int k = 0; k < 4; k++) { const float d0 = bf_lo(vw[k]) - x0, d1 = bf_hi(vw[k]) - x0; m1 += d0 + d1; s1 = fmaf(d0, d0, fmaf(d1, d1, s1)); }
        }
        #pragma unroll
        for (int o = 8; o; o >>= 1) { m1 += __shfl_xor_sync(0xffffffff, m1, o); s1 += __shfl_xor_sync(0xffffffff, s1, o); }
        const float md = m1 * (1.f / DM), var = fmaxf(fmaf(-md, md, s1 * (1.f / DM)), 0.f);
        if ((lane & 15) == it) w0 = pack_bf16(x0 + md, sqrt_approx(rbf(rbf(var) + 1e-5f)));
      }
      STALL(5);
      publish(w0 & 0x7fffffffu);
      TRACE1(2, 8);
      if (warp == 1 && W1SL) warm(1, 0, 5);
    }
        if (warp >= 2) {
      const int ps = 3 - warp;
      {
        const uint4* src = at<uint4>(P.wq, (((qt >> 2) * 4 + (lane >> 3)) * (NH * DH) + hg * 512 + ps * 256 + (qt & 3) * 64 + (lane & 7) * 8) * 2);
        const uint32_t mine = ((hg * 2 + ps) * 256 + qt * 16 + (lane & 7) * 2 + (lane >> 4)) * 16;
        float cs[8];
        #pragma unroll
        for (int e = 0; e < 8; e++) cs[e] = 0.f;
        #pragma unroll 1
        for (int b = 0; b < 40 / CSB; b++, src += CSB * 16 * 512) {
          uint4 w[CSB];
          #pragma unroll
          for (int i = 0; i < CSB; i++) w[i] = ldg_nc(src + i * 16 * 512);
          #pragma unroll
          for (int i = 0; i < CSB; i++) add8(cs, w[i]);
          if (b == 0) {
            mbar_wait(sb + B_EP, 0);
            if (!(lane & 8)) st_tagged(at<uint4>(g->cs, mine), ~lds32(sb + SM_EP) & 1, 0, 0, 0);
          }
        }
        #pragma unroll
        for (int e = 0; e < 4; e++) {
          cs[e] = ((lane & 16) ? cs[e + 4] : cs[e]) + __shfl_xor_sync(0xffffffff, (lane & 16) ? cs[e] : cs[e + 4], 16);
          cs[e] += __shfl_xor_sync(0xffffffff, cs[e], 8);
        }
        STALL(6);
        mbar_wait(sb + B_EP, 0);
        const uint32_t tm = 0u - (lds32(sb + SM_EP) & 1);
        const uint4* const gc = at<uint4>(g->cs, ((hg * 2 + ps) * 256 + lane) * 16);
        if (!(lane & 8)) st_tagged(at<uint4>(g->cs, mine), (__float_as_uint(cs[0]) & ~1u) | (tm & 1), __float_as_uint(cs[1]), __float_as_uint(cs[2]), __float_as_uint(cs[3]));

        uint4 v[9];
        int it = 0;
        uint32_t miss;
        do {
          #pragma unroll
          for (int i = 0; i < 8; i++) v[i] = ld_tagged(gc + i * 32);
          v[8] = ld_relaxed4(at<uint4>(g->stat, qt * 512 + lane * 16));
          miss = (tag_miss(v[8].x, v[8].y, tm) | tag_miss(v[8].z, v[8].w, tm)) >> 31;
          #pragma unroll
          for (int i = 0; i < 8; i += 2) miss |= tag_miss(v[i].x, v[i+1].x, tm);
        } while (__any_sync(0xffffffff, miss & 1) && ++it < MAXPOLL);
        #pragma unroll
        for (int i = 0; i < 2; i++) {
          auto sum = [](uint32_t a, uint32_t b, uint32_t c, uint32_t d) { return (__uint_as_float(a) + __uint_as_float(b)) + (__uint_as_float(c) + __uint_as_float(d)); };
          const float c0 = sum(v[i].x, v[i+2].x, v[i+4].x, v[i+6].x), c1 = sum(v[i].y, v[i+2].y, v[i+4].y, v[i+6].y);
          const float c2 = sum(v[i].z, v[i+2].z, v[i+4].z, v[i+6].z), c3 = sum(v[i].w, v[i+2].w, v[i+4].w, v[i+6].w);
          const uint32_t h0 = pack_bf16(c0, c1), h1 = pack_bf16(c2, c3), a = sb + SM_EXT + ps * 1024 + i * 512 + (lane >> 1) * 32 + (lane & 1) * 8;
          asm volatile("st.shared.v2.u32 [%0], {%1,%2};" :: "r"(a), "r"(h0), "r"(h1) : "memory");
          asm volatile("st.shared.v2.u32 [%0], {%1,%2};" :: "r"(a + 16), "r"(pack_bf16(c0 - bf_lo(h0), c1 - bf_hi(h0))), "r"(pack_bf16(c2 - bf_lo(h1), c3 - bf_hi(h1))) : "memory");
        }
        sts128(sb + SM_STAT + lane * 16, v[8].x & 0x7fffffffu, v[8].y & 0x7fffffffu, v[8].z & 0x7fffffffu, v[8].w & 0x7fffffffu);
        proxy_fence();
        __syncwarp();
        if (lane == 0) mbar_arrive(sb + B_EXT + ps * 8);
        TRACE1(2, 6 + ps);
        if (elect_one()) l2_prefetch(at<char>(ps ? P.v : P.k, ((hg * 4 + 1) * S_LEN + qt * (16 + 8 * KVPF)) * DH * 2), 4096 + 2048 * KVPF);
      }
    }
    if (warp == 1 || warp == 2) {
      int j = 0;
      const int r0 = qt * 128 + hg * 16 + (warp - 1) * 8 + (lane >> 4);
      uint32_t e = r0 * DM * 2 + (lane & 15) * 16;
      uint4 xn = ldg_nc(at<uint4>(P.x, e)), wn = ldg_nc(at<uint4>(P.wr, (lane & 15) * 16));
      #pragma unroll 1
      for (int it = 0; it < 4; it++) {
        const uint32_t st = __shfl_sync(0xffffffff, w0, (lane & 16) + it), m2 = __byte_perm(st, 0, 0x1010);
        const float rsd = rcp_fast(bf_hi(st));
        float a = 0.f;
        #pragma unroll 1
        for (int i = 0; i < 5; i++) {
          #pragma unroll 1
          do { mbar_pace(sb + B_KE + (j & 1) * 8, (j >> 1) & 1); j++; } while (j < 3 || (j >= 15 && j < 20));
          STALL(8);
          uint32_t z[4] = {xn.x, xn.y, xn.z, xn.w};
          const uint32_t ww[4] = {wn.x, wn.y, wn.z, wn.w}, en = e + (i < 4 ? 256 : (it < 3 ? 1536 : 0));
          xn = ldg_nc(at<uint4>(P.x, en)); wn = ldg_nc(at<uint4>(P.wr, (i < 4 ? i * 256 + 256 : 0) + (lane & 15) * 16));
          #pragma unroll
          for (int k = 0; k < 4; k++) {
            const uint32_t n = norm2(z[k], m2, rsd);
            const float lo = bf_lo(n), hi = bf_hi(n);
            a = fmaf(lo, bf_lo(ww[k]), fmaf(hi, bf_hi(ww[k]), a));
            z[k] = pack_bf16(lo * sigmoid_f(lo), hi * sigmoid_f(hi));
          }
          stg128(at<uint4>(g->gate, e), make_uint4(z[0], z[1], z[2], z[3]));
          e = en;
        }
        #pragma unroll
        for (int o = 8; o; o >>= 1) a += __shfl_xor_sync(0xffffffff, a, o);
        uint32_t u = pack_bf16(a, 0.f);
        if (u == 0x8000u) u = 0;
        u = (u & 0x8000u) ? (~u & 0xffffu) : (u | 0x8000u);
        if (!(lane & 15)) st_relaxed(at<uint32_t>(g->key, (r0 + it * 2) * 4), (u << 16) | (uint32_t)(0xffff - r0 - it * 2));
      }
      __syncwarp();
      if (lane == 0) flag_add_release(&g->cnt_gate.v);
      TRACE1(2, 9);
    }
    if (warp == 0) {
      const int row0 = hg * 4 * S_LEN;
      uint32_t s = 0, ph = 0;
      #pragma unroll 1
      for (int c = 3; c < 20; c++) {
        const int k = (c < 10 ? c : (c < 18 ? c - 8 : c - 18)) * 64, cb = hg * 8 + (c < 10 ? 0 : 4);
        const CUtensorMap* const tm = c < 10 ? &tmW4 : &tmW3;
        const uint32_t wb = c < 10 ? U : 12288;
        const bool wx = c < 10 || (c >= XRC && c < XRC + 2);
        const uint32_t bar = sb + B_WF + s * 8, dst = sb + SM_W + rank * 8192 + s * U;
        mbar_wait(bar + (B_WE - B_WF), ph);
        if (elect_one()) {
          mbar_expect_tx(bar, wx ? wb + U : wb);
          tma_load_3d_mc(dst, tm, bar, 0, k + rank * 16, cb);
          if (wx) tma_load_2d(sb + (c < 10 ? (c + 2) & 7 : c + 4 - XRC) * U, &tmX, bar, c < 10 ? k : (c - XRC) * 64, qt * 128);
        }
        mbar_wait(bar + (B_WE - B_WF) + 8, ph);
        if (elect_one()) {
          mbar_expect_tx(bar + 8, wb);
          tma_load_3d_mc(dst + U, tm, bar + 8, 0, k + 32 + rank * 16, cb);
        }
        s += 2;
        if (s == 6) { s = 0; ph ^= 1; }
      }
      #pragma unroll 1
      for (int i = 0; i < 128; i++) {
        const int isv = i < 5 ? (i >> 1) & 1 : (i < 127 ? ~i & 1 : 1), j = i < 4 ? i & 1 : (i + 1 - 2 * isv) >> 1;
        const uint32_t b = isv * 16 + (j & 1) * 8;
        STALL(11);
        if (i) mbar_wait(sb + (i < 4 ? B_WE + ((0x3150 >> (4 * i)) & 7) * 8 : B_KE + b), i < 4 ? i < 2 : (~j >> 1) & 1);
        if (elect_one()) {
          mbar_expect_tx(sb + B_KF + b, 2 * U);
          tma_load_2d_mc(sb + (isv ? SM_V + (j & 1) * 2 * U : (j & 1) * SM_K1) + rank * U, isv ? &tmV : &tmK, sb + B_KF + b, rank * 64, row0 + kv_tile(j) * 128);
          if (GSYNC && i == 125) mbar_arrive(sb + B_ANN);
        }
        if (i == 4) TRACEO(3);
      }
      s = 0; ph = 1;
      #pragma unroll 1
      for (int n = 0; n < (X_SKIP(qp) ? 2 : 40); n++) {
        const int st = n < 5 ? (n == 1) : n >> 2, h = n < 5 ? max(n - 1, 0) : n & 3;
        const int u = st < 2 ? 8 + st : ((hg + st - 1) & 7);
        STALL(12);
        mbar_wait(sb + (n < 6 ? B_KE + (n < 4 ? n >> 1 : 3) * 8 : B_CE + s * 8), ph);
        if (elect_one()) {
          mbar_expect_tx(sb + B_CF + s * 8, U);
          tma_load_2d_mc(sb + c_slot(s) * U + rank * 8192, &tmWO, sb + B_CF + s * 8, u * 64, hg * 512 + ((0x3120 >> (4 * h)) & 3) * 128 + rank * 64);
        }
        if (n == 3) TRACEO(4);
        if (++s == 6) { s = 0; ph ^= 1; }
      }
      mbar_wait(sb + B_GATE, 0);
      asm volatile("fence.proxy.async.global;" ::: "memory");
      #pragma unroll 1
      for (int n = 0; n < (X_SKIP(qp) ? 0 : 2); n++) {
        mbar_wait(sb + B_CE + 32 + n * 8, 1);
        if (elect_one()) {
          mbar_expect_tx(sb + B_CF + 32 + n * 8, U);
          tma_load_2d(sb + (10 + n) * U, n ? &tmGate : &tmX, sb + B_CF + 32 + n * 8, hg * 64, qt * 128);
        }
      }
      if (!X_SKIP(qp)) {
        const uint4* const last = g->part + (size_t)((qt * 8 + hg) * 9 + 8) * 1024;
        mbar_wait(sb + B_CE + P8, 0);
        if (elect_one()) {
          mbar_expect_tx(sb + B_CF + 8, U);
          bulk_load(sb + U, last, U, sb + B_CF + 8);
        }
      }
    } else if (warp == 2) {
      #pragma unroll 1
      for (int h = 0; h < 4; h++) {
        mbar_wait(sb + B_OS + h * 8, 0);
        STALL(13);
        #pragma unroll 1
        for (int i = 0; i < (h < 3 ? 16 : 0); i++) {
          uint32_t z = 0;
          #pragma unroll
          for (int k = 0; k < 4; k++) { const uint4 v = lds128(sb + qo_slot(h) + i * 2048 + k * 512 + lane * 16); z = taint(taint(z, v.x, v.y), v.z, v.w); }
          flag_if(sb + SM_BAD + (i & 7) * 4 + h, tainted(z));
        }
        if (GSYNC && h == 2) {
          const uint32_t launch = lds32(sb + SM_EP);
          uint32_t* const mine = at<uint32_t>(g->near, (qt * 8 + hg) * 32 + (lane & 7) * 4);
          st_relaxed(mine, launch - 1);
          mbar_wait(sb + B_ANN, 0);
          mbar_wait(sb + B_KE, 1);
          st_relaxed(mine, launch);
          #pragma unroll 1
          for (int it = 0; __any_sync(0xffffffff, ldg32(at<uint32_t>(g->near, qp * 512 + lane * 16)) != launch) && it < MAXPOLL; it++) {}
        }
        __syncwarp();
        if (h >= 2) { proxy_fence(); if (elect_one()) mbar_arrive(sb + B_OF); }
        __syncwarp();
      }
    } else if (!elect_one()) {
    } else if (warp == 1) {
      mbar_wait(sb + B_OS + 8, 0);
      flag_wait(at<unsigned>(g->q3_done, (hg >> 1) * 128), lds32(sb + SM_EP) * 32 + qt * 2 - 30);
      asm volatile("fence.proxy.async.global;" ::: "memory");
      mbar_expect_tx(sb + B_Q3, U);
      bulk_load(sb + 5 * U, g->q3 + (qt * 8 + hg) * 1024, U, sb + B_Q3);
      flag_wait(&g->mod_done.v, lds32(sb + SM_EP) * 4);
      mbar_arrive(sb + B_GATE);
    } else {
      #pragma unroll 1
      for (int j = 2; j < 64 - KVPF; j++) {
        mbar_pace(sb + B_KE + (j & 1) * 8, (~j >> 1) & 1);
        const size_t o = (size_t)(hg * 4 * S_LEN + kv_tile(j + KVPF) * 128 + qt * 8) * DH;
        if (KVPF) { l2_prefetch(P.k + o, 2048); l2_prefetch(P.v + o, 2048); }
        if (j >= 40 && j < 56) l2_prefetch(P.wo + (size_t)(hg * 512 + qt * 32 + (j - 40) * 2) * DM, 2 * DM * 2);
        if (j >= 56 && j < 60) l2_prefetch(((j & 1) ? P.x : g->gate) + (size_t)(qt * 128 + hg * 16 + (j & 2) * 4) * DM, 8 * DM * 2);
      }
    }
    __syncwarp();
    if ((warp == 1 || warp == 2) && !X_SKIP(qp)) {
      mbar_wait(sb + B_GATE, 0);
      #pragma unroll 1
      for (int i = 0; i < 4; i++) {
        const int r = warp * 8 - 8 + (i & 1) * 4 + (lane >> 3);
        const uint32_t e = ((qt * 128 + hg * 16 + r) * DM + (8 + (i >> 1)) * 64 + (lane & 7) * 8) * 2;
        if (!(i & 1)) bar_sync(8, 192);
        STALL(10);
        const uint4 xr = ldg_nc(at<uint4>(P.x, e)), gr = ld_relaxed4(at<uint4>(g->gate, e)), sv = lds128(sb + SM_BAR + 1024 + r * 128 + (((lane ^ r) & 7) << 4));
        stg128(at<uint4>(P.out, e), gated(xr, sv, gr));
        if (i == 1) bar_arrive(9, 192);
      }
    }
    cluster_arrive();
    cluster_wait();
  } else {
    const int wg = wgi - 1, t = tid & 127, cw = warp - 4;
    asm volatile("setmaxnreg.inc.sync.aligned.u32 224;");
    uint32_t q[32], p[32];
    float s[64], o[64], l[2] = {0.f, 0.f};
    const uint32_t rb = __shfl_sync(0xffffffff, map_cta(sb, lane & 1), lane), wr = sb + cw * 2048, qa = __shfl_sync(0xffffffff, wr + lane * 16, lane);
    {
      uint32_t sl = 0, ph = 0, rprev = 0;
      float acc0[128], acc1[96];
      auto pair = [&](auto& acc, int pass, int i, auto mid) {
        const uint64_t a = desc(sb, ((i + 2 + 2 * pass) & 7) * 1024 + wg * 512 + doff(0, 16)), b = desc(sb, sl * 128 + doff(SM_W, 2048));
        STALL(4);
        mbar_wait(sb + B_WF + sl, ph);
        if (i == 0) TRACE(wg, 1 + pass);
        TRACEF(1, wg, 40 + pass * 20 + 2 * i);
        wg_fence();
        wgmma_ss_tb<0, 0>(acc, a, b, i > 0);
        wgmma_ss_tb<2, 512>(acc, a, b, 1);
        wg_commit();
        mbar_wait(sb + B_WF + 8 + sl, ph);
        wg_wait<1>();
        if (i > 0) release2(rprev, lane);
        TRACEF(1, wg, 41 + pass * 20 + 2 * i);
        wg_fence();
        wgmma_ss_tb<4, 1024>(acc, a, b, 1);
        wgmma_ss_tb<6, 1536>(acc, a, b, 1);
        wg_commit();
        mid();
        rprev = rb + B_WE + 8 + sl;
        sl += 16;
        if (sl == 48) { sl = 0; ph ^= 1; }
        wg_wait<1>();
        release2(rprev - 8, lane);
      };
      if (wg == 1) bar_arrive(1, 256);
      #pragma unroll 1
      for (int i = 0; i < 10; i++) {
        if (i == SKEW0 / 2) bar_sync(1 + wg, 256);
        pair(acc0, 0, i, [] {});
      }
      mbar_wait(sb + B_EXT, 0);
      const uint32_t st0 = lds32(sb + SM_STAT + (cw * 16 + (lane >> 2)) * 4), st1 = lds32(sb + SM_STAT + (cw * 16 + 8 + (lane >> 2)) * 4);
      const uint32_t a0 = (lane & 3) ? 0u : (__byte_perm(st0, 0, 0x1010) ^ 0x80008000u), a1 = (lane & 3) ? 0u : (__byte_perm(st1, 0, 0x1010) ^ 0x80008000u);
      wg_fence();
      wgmma_rs_tb<0>(acc0, a0, a1, 0u, 0u, (uint64_t)desc_lo(sb + SM_EXT, 0) | ((uint64_t)2 << 32), 1);
      wg_commit();
      bar_arrive(1 + (wg ^ 1), 256);
      float rs[2] = {rcp_fast(bf_hi(st0)) * SCALE_LOG2E, rcp_fast(bf_hi(st1)) * SCALE_LOG2E};
      wg_wait<0>();
      fence_regs(acc0);
      release2(rprev, lane);
      #pragma unroll
      for (int i = 0; i < 32; i++) q[i] = pack_bf16(acc0[64+2*i] * rs[i & 1], acc0[64+2*i+1] * rs[i & 1]);
      fence_regs(q);
      pair(acc1, 1, 0, [&] {
        bar_sync(4 + wg, 128);
        const uint32_t one = lds32(sb + SM_ONE);
        rs[0] = __uint_as_float(__float_as_uint(rs[0]) * one); rs[1] = __uint_as_float(__float_as_uint(rs[1]) * one);
        #pragma unroll
        for (int i = 0; i < 32; i++) p[i] = pack_bf16(acc0[2*i] * rs[i & 1], acc0[2*i+1] * rs[i & 1]);
        fence_regs(p);
      });
      #pragma unroll 1
      for (int i = 1; i < 8; i++) pair(acc1, 1, i, [&] {
        #pragma unroll
        for (int e = 0; e < 8; e++) sts128_if(i == 4 + e / 2, qa + qo_slot(0) + (e >> 2) * U + (e & 3) * 512, p[4*e], p[4*e+1], p[4*e+2], p[4*e+3]);
      });
      mbar_wait(sb + B_WF, 0);
      mbar_wait(sb + B_WF + 8, 0);
      if (wg) { wg_wait<0>(); release2(rprev, lane); }
      bar_sync(1 + wg, 256);
      const uint64_t da = desc(sb, wg * 512 + 7), db = desc(sb, 7);
      static_for<0, 2>([&](auto ic) { constexpr int i = decltype(ic)::v;
        wg_fence();
        static_for<0, 4>([&](auto kc) { constexpr int k = decltype(kc)::v;
          wgmma_ss_tb<doff((4 + i) * U, 16) - 7 + k * 2, doff(SM_W + i * 2 * U, 2048) - 7 + k * 512>(acc1, da, db, 1); });
        if (i == 0) {
          wg_commit();
          mbar_wait(sb + B_WF + 16, 0);
          mbar_wait(sb + B_WF + 24, 0);
          mbar_wait(sb + B_EXT + 8, 0);
          wg_wait<1>();
          if (!wg) release2(rprev, lane);
        }
      });
      wgmma_rs_tb<0>(acc1, a0, a1, 0u, 0u, (uint64_t)desc_lo(sb + SM_EXT + 1024, 0) | ((uint64_t)2 << 32), 1);
      wg_commit();
      mbar_wait(sb + B_KF, 0);
      wg_wait<1>();
      release2(rb + B_WE + 8, lane);
      TRACE(wg, 3);
      mma_qk<0, 2>(s, q, desc(sb, 2));
      bar_arrive(1 + (wg ^ 1), 256);
      wg_wait<1>();
      fence_regs(acc1);
      release2(rb + B_WE + 24, lane);
      #pragma unroll
      for (int e = 0; e < 12; e++)
        sts128(qa + SM_QO + (e >> 2) * U + (e & 3) * 512, pack_bf16(acc1[8*e] * rs[0], acc1[8*e+1] * rs[0]), pack_bf16(acc1[8*e+2] * rs[1], acc1[8*e+3] * rs[1]),
               pack_bf16(acc1[8*e+4] * rs[0], acc1[8*e+5] * rs[0]), pack_bf16(acc1[8*e+6] * rs[1], acc1[8*e+7] * rs[1]));
      wg_wait<0>();
      fence_regs(s);
      release2(rb + B_KE, lane);
      exp_rows<0, 64>(s, l);
      #pragma unroll
      for (int i = 0; i < 32; i++) p[i] = pack_bf16(s[2*i], s[2*i+1]);
    }
    unsigned tz[3] = {0, 0, 0};
    bool ready = false;
    #pragma unroll 1
    for (int j = 1; ; j += 2) {
      int ph = 0;
      #pragma unroll 1
      do {
        attn_step<1, false>(sb, rb, wr, qa, wg, lane, j, ph, s, o, p, q, l, ready, g, tz);
        ph ^= 1; j += 2;
        if (wg < 2) attn_step<0, false>(sb, rb, wr, qa, wg, lane, j - 1, ph, s, o, p, q, l, ready, g, tz);
      } while ((j & 15) != 15);
      if (j == 47) mbar_wait(sb + B_Q3, 0);
      attn_step<1, true>(sb, rb, wr, qa, wg, lane, j, 1, s, o, p, q, l, ready, g, tz);
      if (j == 63) break;
      if (wg < 2) attn_step<0, true>(sb, rb, wr, qa, wg, lane, j + 1, 0, s, o, p, q, l, ready, g, tz);
    }
    mbar_wait(sb + B_OF, 0);
    mbar_wait(sb + B_CF + wg * 8, 0);
    mbar_wait(sb + B_KF + 24, 1);
    bar_sync(1 + wg, 256);
    TRACE(wg, 4);
    mma_pv<SM_V + 2 * U, 2>(o, p, desc(sb, 2), true);
    mma_c<3>(s, sb, wg, 0, 0);
    bar_arrive(1 + (wg ^ 1), 256);
    mbar_wait(sb + B_KE + 16, 1);
    const uint32_t tag = lds32(sb + SM_EP) & 1;
    row_scale(l[0], l[1], lds32(sb + SM_ONE), sb + SM_BAD + cw * 4 + 3);
    __syncwarp();
    const uint32_t flags = lds32(sb + SM_BAD + (lane & 7) * 4);
    wg_wait<1>();
    fence_regs(o); fence_regs(p);
    release2(rb + B_KE + 24, lane);
    const uint32_t over = tainted(store_o<true>(o_addr(wr, lane) + SM_V, o, l[0], l[1]));
    if (__builtin_expect(bar_any(4 + wg, 128, __any_sync(0xffffffff, flags | over)), 0)) {
      const uint32_t bad = __shfl_sync(0xffffffff, flags, cw) | (__any_sync(0xffffffff, over) << 24);
      wg_wait<0>();
      fence_regs(s);
      redo_heads(P, sb, bad, qt * 128 + cw * 16, hg * 4);
      #pragma unroll
      for (int i = 0; i < 64; i++) s[i] = 0.f;
      __syncwarp();
      if (lane == 0) mbar_arrive(sb + B_OS + 24);
      mbar_wait(sb + B_OF, 1);
      mma_c<4>(s, sb, wg, 0, 0);
    } else if (lane == 0) mbar_arrive(sb + B_OS + 24);
    wg_wait<0>();
    release2(rb + B_CE + wg * 8, lane);
    if (X_SKIP(qp)) { cluster_arrive(); } else {
      const uint4* in = at<uint4>(g->part, (((qt * 8 + hg) * 9 + wg) * 1024 + t) * 16);
      const uint32_t tm = 0u - tag;
      uint4 v[8];
      auto fetch = [&](auto half, const uint4* from) {
        #pragma unroll
        for (int i = decltype(half)::v * 4; i < decltype(half)::v * 4 + 4; i++) reload(v[i], from + i * 128);
      };
      auto verify = [&](auto half, const uint4* from) { verify4(v + decltype(half)::v * 4, from + decltype(half)::v * 512, tm); };
      int sp = 6, sl = 2 + 3 * wg, ph = 0;
      auto quarter = [&](auto site, int h, int arrive_bar) {
        STALL(2);
        mbar_wait(sb + B_CF + sl * 8, ph);
        if (h == 0) bar_sync(1 + wg, 256);
        mma_c<decltype(site)::v>(s, sb, sl, h, arrive_bar);
        if (h) { wg_wait<1>(); release2(rb + B_CE + sp * 8, lane); }
        sp = sl;
        if (++sl == 6) { sl = 0; ph ^= 1; }
      };
      auto send = [&](int st) {
        uint4* dst = at<uint4>(g->part, ((qt * 72 + st) * 1024 + (st < 2 ? hg * 128 : ((hg + st - 1) & 7) * 9216) + t) * 16);
        const uint32_t ds = st < 2 ? 9 * U : 2048;
        wg_wait<0>();
        fence_regs(s);
        TRACEF(4, wg, 106 + (st >> 1));
        release2(rb + B_CE + sp * 8, lane);
        STALL(3);
        #pragma unroll
        for (int i = 0; i < 8; i++, dst = at<uint4>(dst, ds))
          st_tagged(dst, (pack_bf16(s[8*i], s[8*i+1]) & ~1u) | tag, pack_bf16(s[8*i+2], s[8*i+3]), pack_bf16(s[8*i+4], s[8*i+5]), pack_bf16(s[8*i+6], s[8*i+7]));
        sl += st ? 4 : 3;
        if (sl >= 6) { sl -= 6; ph ^= 1; }
      };
      const uint32_t ta = ((lane >> 4) * 8 + (lane & 7)) * 128 + ((((cw & 3) * 2 + ((lane >> 3) & 1)) ^ (lane & 7)) << 4), ra = (t >> 3) * 128 + (((t & 7) ^ ((t >> 3) & 7)) << 4);
      float T[64];
      #pragma unroll
      for (int i = 0; i < 8; i++) asm volatile("mov.b64 {%0,%1}, 0;\nmov.b64 {%2,%3}, 0;" : "=r"(v[i].x), "=r"(v[i].y), "=r"(v[i].z), "=r"(v[i].w));
      #pragma unroll
      for (int i = 0; i < 64; i += 2) asm volatile("mov.b64 {%0,%1}, 0;" : "=f"(T[i]), "=f"(T[i+1]));
      TRACEF(4, wg, 112);
      bar_sync(1 + wg, 256);
      auto take = [&](auto half, int back, bool more) {
        verify(half, in - back * 1024);
        const uint4* const nx = in - (back - 1) * 1024;
        #pragma unroll
        for (int i = decltype(half)::v * 4; i < decltype(half)::v * 4 + 4; i++) { add8(T + 8 * i, v[i]); reload(v[i], nx + i * 128, more); }
      };
      #pragma unroll 1
      for (int st = wg; ; st += 2, in += 2048) {
        TRACEF(4, wg, 100 + (st >> 1));
        const bool odd5 = (st & 1) && st >= 5;
        quarter(IC<5>{}, 1, 0);
        if (odd5) take(IC<0>{}, 3, true);
        else if (st == 2) fetch(IC<0>{}, in - 2048);
        quarter(IC<6>{}, 2, 0);
        if (odd5) take(IC<1>{}, 3, true);
        else if (st == 2) fetch(IC<1>{}, in - 2048);
        if (st < 2) mbar_wait(sb + B_OF, 1);
        quarter(IC<7>{}, 3, st < 9 ? 2 - wg : 0);
        if (st < 9) send(st);
        if (odd5) { take(IC<0>{}, 2, st < 9); take(IC<1>{}, 2, st < 9); }
        else if (st == 3) {
          fetch(IC<0>{}, in - 1024); fetch(IC<1>{}, in - 1024);
        } else if (st == 2 || st == 4) {
          const uint4* const rows = at<uint4>(in - 3072, st == 2 ? U : 0);
          float a[8];
          #pragma unroll
          for (int i = 0; i < 8; i++) a[i] = 0.f;
          static_for<0, 2>([&](auto hf) {
            verify(hf, rows);
            #pragma unroll
            for (int i = decltype(hf)::v * 4; i < decltype(hf)::v * 4 + 4; i++) { add8(a, v[i]); reload(v[i], rows + 1024 + i * 128, st == 2); }
          });
          if (st == 4) bar_sync(9, 192);
          stsm4t(sb + SM_BAR + 1024 + ta, pack_bf16(a[0], a[1]), pack_bf16(a[2], a[3]), pack_bf16(a[4], a[5]), pack_bf16(a[6], a[7]));
          bar_arrive(8, 192);
        }
        if (st >= 8) break;
        quarter(IC<8>{}, 0, 0);
      }
      cluster_arrive();
      TRACEF(4, wg, 113);
      wg_wait<0>();
      fence_regs(s);
      if (wg == 0) {
        mbar_wait(sb + B_CF + 32, 0);
        mbar_wait(sb + B_CF + 40, 0);
        uint4* const op = at<uint4>(P.out, ((qt * 128 + (t >> 3)) * DM + hg * 64 + (t & 7) * 8) * 2);
        bar_sync(1, 256);
        uint4 xv[8];
        #pragma unroll
        for (int i = 0; i < 8; i++) { xv[i] = lds128(sb + 10 * U + i * 2048 + ra); v[i] = lds128(sb + 11 * U + i * 2048 + ra); }
        #pragma unroll
        for (int i = 0; i < 8; i++) {
          if (i % (8 / FQ) == 0) bar_sync(12 + i / (8 / FQ), 256);
          stg128(op + i * 2 * DM, gated(xv[i], lds128(sb + i * 2048 + ra), v[i]));
        }
      } else {
        TRACEF(4, wg, 110);
        #pragma unroll
        for (int i = 0; i < 64; i++) T[i] += s[i];
        fence_regs(T);
        mbar_wait(sb + B_CF + 8, 1);
        #pragma unroll
        for (int i = 0; i < 8; i++) v[i] = lds128(sb + U + i * 2048 + t * 16);
        bar_arrive(1, 256);
        static_for<0, 8>([&](auto ic) { constexpr int i = decltype(ic)::v;
          if (!(i & 3)) verify(IC<i / 4>{}, in - 1024);
          add8(T + 8 * i, v[i]);
          stsm4t(sb + i * 2048 + ta, pack_bf16(T[8*i], T[8*i+1]), pack_bf16(T[8*i+2], T[8*i+3]), pack_bf16(T[8*i+4], T[8*i+5]), pack_bf16(T[8*i+6], T[8*i+7]));
          if ((i + 1) % (8 / FQ) == 0) bar_arrive(12 + i / (8 / FQ), 256);
        });
      }
    }
    TRACE(wg, 6);
    cluster_wait();
  }
}

typedef CUresult (*EncodeFn)(CUtensorMap*, CUtensorMapDataType, cuuint32_t, void*, const cuuint64_t*, const cuuint64_t*, const cuuint32_t*, const cuuint32_t*,
                             CUtensorMapInterleave, CUtensorMapSwizzle, CUtensorMapL2promotion, CUtensorMapFloatOOBfill);
void make_map(EncodeFn enc, CUtensorMap* tm, const void* ptr, uint64_t inner, uint64_t outer, uint32_t box_outer, uint32_t blocks = 0) {
  cuuint64_t dims[3] = {blocks ? 64 : inner, outer, inner / 64}; cuuint64_t strides[2] = {inner * 2, 128};
  cuuint32_t box[3] = {64, box_outer, blocks}; cuuint32_t es[3] = {1, 1, 1};
  enc(tm, CU_TENSOR_MAP_DATA_TYPE_BFLOAT16, blocks ? 3 : 2, const_cast<void*>(ptr), dims, strides, box, es, CU_TENSOR_MAP_INTERLEAVE_NONE,
      CU_TENSOR_MAP_SWIZZLE_128B, CU_TENSOR_MAP_L2_PROMOTION_L2_256B, CU_TENSOR_MAP_FLOAT_OOB_FILL_NONE);
}

}

extern "C" void kernel_launch(void* const* d_in, const int* in_sizes, int n_in, void* d_out, int out_size) {
  (void)in_sizes; (void)n_in; (void)out_size;
  Params P;
  P.x = (const __nv_bfloat16*)d_in[0]; P.k = (const __nv_bfloat16*)d_in[1]; P.v = (const __nv_bfloat16*)d_in[2];
  P.wq = (const __nv_bfloat16*)d_in[3]; P.wo = (const __nv_bfloat16*)d_in[4]; P.wr = (const __nv_bfloat16*)d_in[6];
  P.out = (__nv_bfloat16*)d_out;
  cudaGetSymbolAddress((void**)&P.g, g_s);
  void* fn = nullptr; cudaDriverEntryPointQueryResult st;
  cudaGetDriverEntryPoint("cuTensorMapEncodeTiled", &fn, cudaEnableDefault, &st);
  EncodeFn enc = (EncodeFn)fn;
  CUtensorMap tmX, tmW4, tmW3, tmW1, tmK, tmV, tmWO, tmG, tmU, tmD, tmGate;
  make_map(enc, &tmGate, P.g->gate, DM, S_LEN, 128);
  make_map(enc, &tmX, P.x, DM, S_LEN, 128);
  make_map(enc, &tmW4, P.wq, NH * DH, DM, 16, 4);
  make_map(enc, &tmW3, P.wq, NH * DH, DM, 16, 3);
  make_map(enc, &tmW1, P.wq, NH * DH, DM, 128);
  make_map(enc, &tmK, P.k, DH, (uint64_t)NH * S_LEN, 128);
  make_map(enc, &tmV, P.v, DH, (uint64_t)NH * S_LEN, 128);
  make_map(enc, &tmWO, P.wo, DM, NH * DH, 64);
  make_map(enc, &tmG, d_in[7], FF, DM, 128);
  make_map(enc, &tmU, d_in[8], FF, DM, 128);
  make_map(enc, &tmD, d_in[9], DM, FF, 128);
  cudaFuncSetAttribute(fused_kernel, cudaFuncAttributeMaxDynamicSharedMemorySize, SMEM_BYTES);
  fused_kernel<<<132, 384, SMEM_BYTES, cudaStreamPerThread>>>(tmX, tmW4, tmW3, tmW1, tmK, tmV, tmWO, tmG, tmU, tmD, tmGate, P);
}
```

```cpp
#include <cuda_runtime.h>
#include <cuda_bf16.h>
#include <cuda.h>
#include <stdint.h>

#define MAXPOLL (1 << 22)
#define SKEW0 18
#define DPOS 44
#define DPOSF 36
#define KVPF 2
#define X_SKIP(qp) false
#define W1SL 300
#define WAITMAX (1 << 19)
#define CSB 10
#define P8 16
#define GSYNC 1
#define PH 1
#define XRC 15
#define QSP 6
namespace {

constexpr int S_LEN = 2048, DM = 640, NH = 32, DH = 128, FF = 1728, TOPC = 8;
constexpr float SCALE_LOG2E = 0.08838834764831845f * 1.4426950408889634f;

struct alignas(128) Cnt { unsigned v; unsigned pad[31]; };
struct Scratch {
  alignas(128) unsigned long long ticket;
  alignas(128)
  uint4 part[16 * 8 * 9 * 1024];
  __nv_bfloat16 gate[S_LEN * DM];
  uint32_t stat[S_LEN];
  uint4 cs[NH * DH];
  float ypart[4 * TOPC * DM];
  uint4 q3[16 * 8 * 1024];
  uint32_t key[S_LEN];
  Cnt cnt_gate, cnt_mod, mod_done, q3_done[4];
  uint32_t near[128 * 8];
};
__device__ Scratch g_s;

__device__ __forceinline__ uint32_t smem_u32(const void* p) { return (uint32_t)__cvta_generic_to_shared(p); }
template <class T> __device__ __forceinline__ T* at(const void* p, uint32_t off) { uint64_t r;
  asm("{\n.reg .u32 lo, hi;\nmov.b64 {lo, hi}, %1;\nadd.cc.u32 lo, lo, %2;\naddc.u32 hi, hi, 0;\nmov.b64 %0, {lo, hi};\n}\n" : "=l"(r) : "l"(p), "r"(off)); return (T*)r; }
__device__ __forceinline__ void mbar_init(uint32_t bar, uint32_t cnt) { asm volatile("mbarrier.init.shared::cta.b64 [%0], %1;" :: "r"(bar), "r"(cnt) : "memory"); }
__device__ __forceinline__ void mbar_expect_tx(uint32_t bar, uint32_t bytes) { asm volatile("mbarrier.arrive.expect_tx.shared::cta.b64 _, [%0], %1;" :: "r"(bar), "r"(bytes) : "memory"); }
__device__ __forceinline__ void mbar_arrive(uint32_t bar) { asm volatile("mbarrier.arrive.shared::cta.b64 _, [%0];" :: "r"(bar) : "memory"); }
__device__ __forceinline__ uint32_t map_cta(uint32_t a, uint32_t cta) { uint32_t r; asm volatile("mapa.shared::cluster.u32 %0, %1, %2;" : "=r"(r) : "r"(a), "r"(cta)); return r; }
__device__ __forceinline__ void mbar_arrive_cluster(uint32_t bar) { asm volatile("mbarrier.arrive.shared::cluster.b64 _, [%0];" :: "r"(bar) : "memory"); }
__device__ __forceinline__ void mbar_wait(uint32_t bar, uint32_t parity) {
  asm volatile("{\n.reg .pred p;\n.reg .u32 c;\nmov.u32 c, 0;\nLAB_WAIT:\nmbarrier.try_wait.parity.shared::cta.b64 p, [%0], %1;\n@p bra LAB_DONE;\n"
               "add.u32 c, c, 1;\nsetp.lt.u32 p, c, %2;\n@p bra LAB_WAIT;\ntrap;\nLAB_DONE:\n}\n" :: "r"(bar), "r"(parity), "n"(WAITMAX) : "memory"); }
__device__ __forceinline__ bool mbar_test2(uint32_t bar0, uint32_t par0, uint32_t bar1, uint32_t par1) { uint32_t r;
  asm volatile("{\n.reg .pred p, q;\nmbarrier.test_wait.parity.shared::cta.b64 p, [%1], %2;\nmbarrier.test_wait.parity.shared::cta.b64 q, [%3], %4;\nand.pred p, p, q;\nselp.u32 %0, 1, 0, p;\n}\n"
               : "=r"(r) : "r"(bar0), "r"(par0), "r"(bar1), "r"(par1) : "memory"); return r; }
__device__ __forceinline__ void mbar_pace(uint32_t bar, uint32_t parity) {
  asm volatile("{\n.reg .pred p;\n.reg .u32 c;\nmov.u32 c, 0;\nLAB_WAIT:\nmbarrier.try_wait.parity.shared::cta.b64 p, [%0], %1;\n@p bra LAB_DONE;\n"
               "add.u32 c, c, 1;\nsetp.lt.u32 p, c, 64;\n@p bra LAB_WAIT;\nLAB_DONE:\n}\n" :: "r"(bar), "r"(parity) : "memory"); }
__device__ __forceinline__ void flag_wait(const unsigned* p, unsigned target, unsigned ns = 500) {
  asm volatile("{\n.reg .pred p;\n.reg .u32 c, v;\nmov.u32 c, 0;\nLAB_WAIT:\nld.relaxed.gpu.global.u32 v, [%0];\nsub.u32 v, v, %1;\nsetp.ge.s32 p, v, 0;\n@p bra LAB_DONE;\n"
               "nanosleep.u32 %2;\nadd.u32 c, c, 1;\nsetp.lt.u32 p, c, 8388608;\n@p bra LAB_WAIT;\ntrap;\nLAB_DONE:\nld.acquire.gpu.global.u32 v, [%0];\n}\n" :: "l"(p), "r"(target), "r"(ns) : "memory"); }
__device__ __forceinline__ void flag_add_release(unsigned* p) { asm volatile("fence.acq_rel.gpu;\nred.relaxed.gpu.global.add.u32 [%0], 1;" :: "l"(p) : "memory"); }
__device__ __forceinline__ void tma_load_2d(uint32_t dst, const CUtensorMap* tm, uint32_t bar, int c0, int c1) {
  asm volatile("cp.async.bulk.tensor.2d.shared::cluster.global.mbarrier::complete_tx::bytes [%0], [%1, {%3, %4}], [%2];"
    :: "r"(dst), "l"(tm), "r"(bar), "r"(c0), "r"(c1) : "memory"); }
__device__ __forceinline__ void tma_load_2d_mc(uint32_t dst, const CUtensorMap* tm, uint32_t bar, int c0, int c1) {
  asm volatile("cp.async.bulk.tensor.2d.shared::cluster.global.mbarrier::complete_tx::bytes.multicast::cluster [%0], [%1, {%3, %4}], [%2], %5;"
    :: "r"(dst), "l"(tm), "r"(bar), "r"(c0), "r"(c1), "h"((uint16_t)3) : "memory"); }
__device__ __forceinline__ void tma_load_3d(uint32_t dst, const CUtensorMap* tm, uint32_t bar, int c0, int c1, int c2) {
  asm volatile("cp.async.bulk.tensor.3d.shared::cluster.global.mbarrier::complete_tx::bytes [%0], [%1, {%3, %4, %5}], [%2];"
    :: "r"(dst), "l"(tm), "r"(bar), "r"(c0), "r"(c1), "r"(c2) : "memory"); }
__device__ __forceinline__ void tma_load_3d_mc(uint32_t dst, const CUtensorMap* tm, uint32_t bar, int c0, int c1, int c2) {
  asm volatile("cp.async.bulk.tensor.3d.shared::cluster.global.mbarrier::complete_tx::bytes.multicast::cluster [%0], [%1, {%3, %4, %5}], [%2], %6;"
    :: "r"(dst), "l"(tm), "r"(bar), "r"(c0), "r"(c1), "r"(c2), "h"((uint16_t)3) : "memory"); }
__device__ __forceinline__ void bulk_load(uint32_t dst, const void* src, uint32_t bytes, uint32_t bar) {
  asm volatile("cp.async.bulk.shared::cluster.global.mbarrier::complete_tx::bytes [%0], [%1], %2, [%3];" :: "r"(dst), "l"(src), "r"(bytes), "r"(bar) : "memory"); }
__device__ __forceinline__ void l2_prefetch(const void* p, uint32_t bytes) { asm volatile("cp.async.bulk.prefetch.L2.global [%0], %1;" :: "l"(p), "r"(bytes) : "memory"); }
__device__ __forceinline__ void wg_fence() { asm volatile("wgmma.fence.sync.aligned;" ::: "memory"); }
__device__ __forceinline__ void wg_commit() { asm volatile("wgmma.commit_group.sync.aligned;" ::: "memory"); }
template <int N> __device__ __forceinline__ void wg_wait() { asm volatile("wgmma.wait_group.sync.aligned %0;" :: "n"(N) : "memory"); }
__device__ __forceinline__ void bar_sync(int id, int n) { asm volatile("bar.sync %0, %1;" :: "r"(id), "r"(n) : "memory"); }
__device__ __forceinline__ void bar_arrive(int id, int n) { asm volatile("bar.arrive %0, %1;" :: "r"(id), "r"(n) : "memory"); }
__device__ __forceinline__ bool bar_any(int id, int n, uint32_t v) { uint32_t r;
  asm volatile("{\n.reg .pred p;\nsetp.ne.u32 p, %3, 0;\nbar.red.or.pred p, %1, %2, p;\nselp.u32 %0, 1, 0, p;\n}\n" : "=r"(r) : "r"(id), "r"(n), "r"(v) : "memory"); return r; }
__device__ __forceinline__ int sel_lt(int a, int b, int x, int y) { int r; asm("{\n.reg .pred p;\nsetp.lt.s32 p, %1, %2;\nselp.s32 %0, %3, %4, p;\n}\n" : "=r"(r) : "r"(a), "r"(b), "r"(x), "r"(y)); return r; }
__device__ __forceinline__ bool elect_one() { uint32_t r; asm volatile("{\n.reg .pred p;\nelect.sync _|p, 0xffffffff;\nselp.u32 %0, 1, 0, p;\n}\n" : "=r"(r)); return r; }
__device__ __forceinline__ void cluster_arrive() { asm volatile("barrier.cluster.arrive.relaxed.aligned;" ::: "memory"); }
__device__ __forceinline__ void cluster_wait() { asm volatile("barrier.cluster.wait.aligned;" ::: "memory"); }
__device__ __forceinline__ void proxy_fence() { asm volatile("fence.proxy.async.shared::cta;" ::: "memory"); }
__device__ __forceinline__ uint32_t pack_bf16(float lo, float hi) { uint32_t r; asm("cvt.rn.bf16x2.f32 %0, %1, %2;" : "=r"(r) : "f"(hi), "f"(lo)); return r; }
__device__ __forceinline__ float bf_lo(uint32_t v) { return __uint_as_float(v << 16); }
__device__ __forceinline__ float bf_hi(uint32_t v) { return __uint_as_float(v & 0xffff0000u); }
__device__ __forceinline__ void add8(float* a, const uint4& w) {
  a[0] += bf_lo(w.x); a[1] += bf_hi(w.x); a[2] += bf_lo(w.y); a[3] += bf_hi(w.y); a[4] += bf_lo(w.z); a[5] += bf_hi(w.z); a[6] += bf_lo(w.w); a[7] += bf_hi(w.w); }
__device__ __forceinline__ float rbf(float x) { return __bfloat162float(__float2bfloat16_rn(x)); }
__device__ __forceinline__ float ex2(float x) { float y; asm("ex2.approx.ftz.f32 %0, %1;" : "=f"(y) : "f"(x)); return y; }
__device__ __forceinline__ uint32_t lds32(uint32_t a) { uint32_t v; asm volatile("ld.shared.u32 %0, [%1];" : "=r"(v) : "r"(a) : "memory"); return v; }
__device__ __forceinline__ void sts32(uint32_t a, uint32_t v) { asm volatile("st.shared.u32 [%0], %1;" :: "r"(a), "r"(v) : "memory"); }
__device__ __forceinline__ uint4 lds128(uint32_t a) { uint4 v; asm volatile("ld.shared.v4.u32 {%0,%1,%2,%3}, [%4];" : "=r"(v.x), "=r"(v.y), "=r"(v.z), "=r"(v.w) : "r"(a) : "memory"); return v; }
__device__ __forceinline__ void sts128(uint32_t a, uint32_t x, uint32_t y, uint32_t z, uint32_t w) { asm volatile("st.shared.v4.u32 [%0], {%1,%2,%3,%4};" :: "r"(a), "r"(x), "r"(y), "r"(z), "r"(w) : "memory"); }
__device__ __forceinline__ void sts128_if(bool c, uint32_t a, uint32_t x, uint32_t y, uint32_t z, uint32_t w) {
  asm volatile("{\n.reg .pred p;\nsetp.ne.u32 p, %5, 0;\n@p st.shared.v4.u32 [%0], {%1,%2,%3,%4};\n}\n" :: "r"(a), "r"(x), "r"(y), "r"(z), "r"(w), "r"((uint32_t)c) : "memory"); }
__device__ __forceinline__ void st_tagged(uint4* p, uint32_t x, uint32_t y, uint32_t z, uint32_t w) {
  asm volatile("st.relaxed.gpu.global.v4.u32 [%0], {%1,%2,%3,%4};" :: "l"(p), "r"(x), "r"(y), "r"(z), "r"(w) : "memory"); }
__device__ __forceinline__ uint4 ld_relaxed4(const void* p) { uint4 v;
  asm volatile("ld.relaxed.gpu.global.v4.u32 {%0,%1,%2,%3}, [%4];" : "=r"(v.x), "=r"(v.y), "=r"(v.z), "=r"(v.w) : "l"(p) : "memory"); return v; }
__device__ __forceinline__ uint4 ld_tagged(const uint4* p) { uint4 v;
  asm volatile("{\n.reg .b128 v;\nld.relaxed.gpu.global.b128 v, [%4];\nmov.b128 {%0,%1,%2,%3}, v;\n}\n" : "=r"(v.x), "=r"(v.y), "=r"(v.z), "=r"(v.w) : "l"(p) : "memory"); return v; }
__device__ __forceinline__ void reload(uint4& v, const uint4* p, bool yes = true) {
  asm volatile("{\n.reg .pred p;\nsetp.ne.u32 p, %5, 0;\n@p ld.relaxed.gpu.global.v4.u32 {%0,%1,%2,%3}, [%4];\n}\n" : "+r"(v.x), "+r"(v.y), "+r"(v.z), "+r"(v.w) : "l"(p), "r"((uint32_t)yes) : "memory"); }
#define TAG_TEST "lop3.b32 a, %0, %4, %17, 0x7E;\nlop3.b32 b, %8, %12, %17, 0x7E;\nlop3.b32 a, a, b, 1, 0xA8;\nsetp.ne.u32 p, a, 0;\nvote.sync.any.pred p, p, 0xffffffff;\n"
__device__ __forceinline__ void verify4(uint4* v, const uint4* p, uint32_t tm) {
  asm volatile("{\n.reg .pred p;\n.reg .u32 a, b, c;\n" TAG_TEST "@!p bra.uni LAB_DONE;\nmov.u32 c, 0;\nLAB_AGAIN:\n"
    "ld.relaxed.gpu.global.v4.u32 {%0,%1,%2,%3}, [%16];\nld.relaxed.gpu.global.v4.u32 {%4,%5,%6,%7}, [%16+2048];\n"
    "ld.relaxed.gpu.global.v4.u32 {%8,%9,%10,%11}, [%16+4096];\nld.relaxed.gpu.global.v4.u32 {%12,%13,%14,%15}, [%16+6144];\n"
    TAG_TEST "add.u32 c, c, 1;\nsetp.lt.and.u32 p, c, %18, p;\n@p bra.uni LAB_AGAIN;\nLAB_DONE:\n}\n"
    : "+r"(v[0].x), "+r"(v[0].y), "+r"(v[0].z), "+r"(v[0].w), "+r"(v[1].x), "+r"(v[1].y), "+r"(v[1].z), "+r"(v[1].w),
      "+r"(v[2].x), "+r"(v[2].y), "+r"(v[2].z), "+r"(v[2].w), "+r"(v[3].x), "+r"(v[3].y), "+r"(v[3].z), "+r"(v[3].w) : "l"(p), "r"(tm), "n"(MAXPOLL) : "memory"); }
__device__ __forceinline__ uint4 ldg_nc(const void* p) { uint4 v;
  asm volatile("ld.global.nc.L1::no_allocate.v4.u32 {%0,%1,%2,%3}, [%4];" : "=r"(v.x), "=r"(v.y), "=r"(v.z), "=r"(v.w) : "l"(p) : "memory"); return v; }
__device__ __forceinline__ uint32_t ldg32(const void* p) { uint32_t v; asm volatile("ld.relaxed.gpu.global.u32 %0, [%1];" : "=r"(v) : "l"(p) : "memory"); return v; }
__device__ __forceinline__ void stg128(void* p, const uint4& v) { asm volatile("st.global.v4.u32 [%0], {%1,%2,%3,%4};" :: "l"(p), "r"(v.x), "r"(v.y), "r"(v.z), "r"(v.w) : "memory"); }
__device__ __forceinline__ void st_relaxed(uint32_t* p, uint32_t v) { asm volatile("st.relaxed.gpu.global.u32 [%0], %1;" :: "l"(p), "r"(v) : "memory"); }
__device__ __forceinline__ uint32_t mul_bf2(uint32_t a, uint32_t b) { uint32_t r; asm("mul.rn.bf16x2 %0, %1, %2;" : "=r"(r) : "r"(a), "r"(b)); return r; }
__device__ __forceinline__ uint32_t add_bf2(uint32_t a, uint32_t b) { uint32_t r; asm("add.rn.bf16x2 %0, %1, %2;" : "=r"(r) : "r"(a), "r"(b)); return r; }
__device__ __forceinline__ uint32_t sub_bf2(uint32_t a, uint32_t b) { uint32_t r; asm("sub.rn.bf16x2 %0, %1, %2;" : "=r"(r) : "r"(a), "r"(b)); return r; }
__device__ __forceinline__ void stsm4(uint32_t a, uint32_t r0, uint32_t r1, uint32_t r2, uint32_t r3) {
  asm volatile("stmatrix.sync.aligned.m8n8.x4.shared.b16 [%0], {%1,%2,%3,%4};" :: "r"(a), "r"(r0), "r"(r1), "r"(r2), "r"(r3) : "memory"); }
__device__ __forceinline__ void stsm4t(uint32_t a, uint32_t r0, uint32_t r1, uint32_t r2, uint32_t r3) {
  asm volatile("stmatrix.sync.aligned.m8n8.x4.trans.shared.b16 [%0], {%1,%2,%3,%4};" :: "r"(a), "r"(r0), "r"(r1), "r"(r2), "r"(r3) : "memory"); }
__device__ __forceinline__ uint4 gated(const uint4& x, const uint4& s, const uint4& g) {
  return make_uint4(add_bf2(x.x, mul_bf2(s.x, g.x)), add_bf2(x.y, mul_bf2(s.y, g.y)), add_bf2(x.z, mul_bf2(s.z, g.z)), add_bf2(x.w, mul_bf2(s.w, g.w))); }
__device__ __forceinline__ uint32_t tag_miss(uint32_t a, uint32_t b, uint32_t tm) { uint32_t d; asm("lop3.b32 %0, %1, %2, %3, 0x7E;" : "=r"(d) : "r"(a), "r"(b), "r"(tm)); return d; }
template <int R> __device__ __forceinline__ void fence_regs(float (&d)[R]) {
  #pragma unroll
  for (int i = 0; i < R; i++) asm volatile("" : "+f"(d[i]) :: "memory"); }
template <int R> __device__ __forceinline__ void fence_regs(uint32_t (&d)[R]) {
  #pragma unroll
  for (int i = 0; i < R; i++) asm volatile("" : "+r"(d[i]) :: "memory"); }
__device__ __forceinline__ uint32_t desc_lo(uint32_t addr, uint32_t lbo_bytes) { return ((addr & 0x3FFFF) >> 4) | ((lbo_bytes >> 4) << 16); }
__device__ __forceinline__ uint64_t desc(uint32_t sb, uint32_t var = 0) {
  uint64_t d; asm("mov.b64 %0, {%1, %2};" : "=l"(d) : "r"(desc_lo(sb, 0) + var), "r"(0x40000040u)); return d; }
__host__ __device__ constexpr int doff(uint32_t off, uint32_t lbo_bytes) { return (off >> 4) | ((lbo_bytes >> 4) << 16); }
__device__ __forceinline__ float rcp_approx(float x) { float y; asm("rcp.approx.f32 %0, %1;" : "=f"(y) : "f"(x)); return y; }
__device__ __forceinline__ float rcp_fast(float x) { float y; asm("rcp.approx.ftz.f32 %0, %1;" : "=f"(y) : "f"(x)); return y; }
__device__ __forceinline__ float sqrt_approx(float x) { float y; asm("sqrt.approx.f32 %0, %1;" : "=f"(y) : "f"(x)); return y; }
__device__ __forceinline__ float sigmoid_f(float z) { return rcp_fast(1.f + ex2(z * -1.4426950408889634f)); }
__device__ __forceinline__ uint32_t norm2(uint32_t x, uint32_t mean2, float rsd) { const uint32_t d = sub_bf2(x, mean2); return pack_bf16(bf_lo(d) * rsd, bf_hi(d) * rsd); }
#define STALL(site)
#define TRACE(w, i)
#define TRACE1(w, i)
#define TRACEF(m, w, i)
#define TRACEO(i)

template <int OA, int OB> __device__ __forceinline__ void wgmma_ss_tb(float (&d)[128], uint64_t da, uint64_t db, int sd) {
  asm volatile("{\n.reg .pred p;\n.reg .b64 a, b;\nadd.s64 a, %128, %131;\nadd.s64 b, %129, %132;\nsetp.ne.b32 p, %130, 0;\n"
    "wgmma.mma_async.sync.aligned.m64n256k16.f32.bf16.bf16 {%0, %1, %2, %3, %4, %5, %6, %7, %8, %9, %10, %11, %12, %13, %14, %15, %16, %17, %18, %19, %20, %21, %22, %23, %24, %25, %26, %27, %28, %29, %30, %31, %32, %33, %34, %35, %36, %37, %38, %39, %40, %41, %42, %43, %44, %45, %46, %47, %48, %49, %50, %51, %52, %53, %54, %55, %56, %57, %58, %59, %60, %61, %62, %63, %64, %65, %66, %67, %68, %69, %70, %71, %72, %73, %74, %75, %76, %77, %78, %79, %80, %81, %82, %83, %84, %85, %86, %87, %88, %89, %90, %91, %92, %93, %94, %95, %96, %97, %98, %99, %100, %101, %102, %103, %104, %105, %106, %107, %108, %109, %110, %111, %112, %113, %114, %115, %116, %117, %118, %119, %120, %121, %122, %123, %124, %125, %126, %127}, a, b, p, 1, 1, 0, 1;\n}\n"
    : "+f"(d[0]), "+f"(d[1]), "+f"(d[2]), "+f"(d[3]), "+f"(d[4]), "+f"(d[5]), "+f"(d[6]), "+f"(d[7]), "+f"(d[8]), "+f"(d[9]), "+f"(d[10]), "+f"(d[11]), "+f"(d[12]), "+f"(d[13]), "+f"(d[14]), "+f"(d[15]), "+f"(d[16]), "+f"(d[17]), "+f"(d[18]), "+f"(d[19]), "+f"(d[20]), "+f"(d[21]), "+f"(d[22]), "+f"(d[23]), "+f"(d[24]), "+f"(d[25]), "+f"(d[26]), "+f"(d[27]), "+f"(d[28]), "+f"(d[29]), "+f"(d[30]), "+f"(d[31]), "+f"(d[32]), "+f"(d[33]), "+f"(d[34]), "+f"(d[35]), "+f"(d[36]), "+f"(d[37]), "+f"(d[38]), "+f"(d[39]), "+f"(d[40]), "+f"(d[41]), "+f"(d[42]), "+f"(d[43]), "+f"(d[44]), "+f"(d[45]), "+f"(d[46]), "+f"(d[47]), "+f"(d[48]), "+f"(d[49]), "+f"(d[50]), "+f"(d[51]), "+f"(d[52]), "+f"(d[53]), "+f"(d[54]), "+f"(d[55]), "+f"(d[56]), "+f"(d[57]), "+f"(d[58]), "+f"(d[59]), "+f"(d[60]), "+f"(d[61]), "+f"(d[62]), "+f"(d[63]), "+f"(d[64]), "+f"(d[65]), "+f"(d[66]), "+f"(d[67]), "+f"(d[68]), "+f"(d[69]), "+f"(d[70]), "+f"(d[71]), "+f"(d[72]), "+f"(d[73]), "+f"(d[74]), "+f"(d[75]), "+f"(d[76]), "+f"(d[77]), "+f"(d[78]), "+f"(d[79]), "+f"(d[80]), "+f"(d[81]), "+f"(d[82]), "+f"(d[83]), "+f"(d[84]), "+f"(d[85]), "+f"(d[86]), "+f"(d[87]), "+f"(d[88]), "+f"(d[89]), "+f"(d[90]), "+f"(d[91]), "+f"(d[92]), "+f"(d[93]), "+f"(d[94]), "+f"(d[95]), "+f"(d[96]), "+f"(d[97]), "+f"(d[98]), "+f"(d[99]), "+f"(d[100]), "+f"(d[101]), "+f"(d[102]), "+f"(d[103]), "+f"(d[104]), "+f"(d[105]), "+f"(d[106]), "+f"(d[107]), "+f"(d[108]), "+f"(d[109]), "+f"(d[110]), "+f"(d[111]), "+f"(d[112]), "+f"(d[113]), "+f"(d[114]), "+f"(d[115]), "+f"(d[116]), "+f"(d[117]), "+f"(d[118]), "+f"(d[119]), "+f"(d[120]), "+f"(d[121]), "+f"(d[122]), "+f"(d[123]), "+f"(d[124]), "+f"(d[125]), "+f"(d[126]), "+f"(d[127])
    : "l"(da), "l"(db), "r"(sd), "n"(OA), "n"(OB));
}
template <int OB> __device__ __forceinline__ void wgmma_rs_tb(float (&d)[128], uint32_t a0, uint32_t a1, uint32_t a2, uint32_t a3, uint64_t db, int sd) {
  asm volatile("{\n.reg .pred p;\n.reg .b64 b;\nadd.s64 b, %132, %134;\nsetp.ne.b32 p, %133, 0;\n"
    "wgmma.mma_async.sync.aligned.m64n256k16.f32.bf16.bf16 {%0, %1, %2, %3, %4, %5, %6, %7, %8, %9, %10, %11, %12, %13, %14, %15, %16, %17, %18, %19, %20, %21, %22, %23, %24, %25, %26, %27, %28, %29, %30, %31, %32, %33, %34, %35, %36, %37, %38, %39, %40, %41, %42, %43, %44, %45, %46, %47, %48, %49, %50, %51, %52, %53, %54, %55, %56, %57, %58, %59, %60, %61, %62, %63, %64, %65, %66, %67, %68, %69, %70, %71, %72, %73, %74, %75, %76, %77, %78, %79, %80, %81, %82, %83, %84, %85, %86, %87, %88, %89, %90, %91, %92, %93, %94, %95, %96, %97, %98, %99, %100, %101, %102, %103, %104, %105, %106, %107, %108, %109, %110, %111, %112, %113, %114, %115, %116, %117, %118, %119, %120, %121, %122, %123, %124, %125, %126, %127}, {%128, %129, %130, %131}, b, p, 1, 1, 1;\n}\n"
    : "+f"(d[0]), "+f"(d[1]), "+f"(d[2]), "+f"(d[3]), "+f"(d[4]), "+f"(d[5]), "+f"(d[6]), "+f"(d[7]), "+f"(d[8]), "+f"(d[9]), "+f"(d[10]), "+f"(d[11]), "+f"(d[12]), "+f"(d[13]), "+f"(d[14]), "+f"(d[15]), "+f"(d[16]), "+f"(d[17]), "+f"(d[18]), "+f"(d[19]), "+f"(d[20]), "+f"(d[21]), "+f"(d[22]), "+f"(d[23]), "+f"(d[24]), "+f"(d[25]), "+f"(d[26]), "+f"(d[27]), "+f"(d[28]), "+f"(d[29]), "+f"(d[30]), "+f"(d[31]), "+f"(d[32]), "+f"(d[33]), "+f"(d[34]), "+f"(d[35]), "+f"(d[36]), "+f"(d[37]), "+f"(d[38]), "+f"(d[39]), "+f"(d[40]), "+f"(d[41]), "+f"(d[42]), "+f"(d[43]), "+f"(d[44]), "+f"(d[45]), "+f"(d[46]), "+f"(d[47]), "+f"(d[48]), "+f"(d[49]), "+f"(d[50]), "+f"(d[51]), "+f"(d[52]), "+f"(d[53]), "+f"(d[54]), "+f"(d[55]), "+f"(d[56]), "+f"(d[57]), "+f"(d[58]), "+f"(d[59]), "+f"(d[60]), "+f"(d[61]), "+f"(d[62]), "+f"(d[63]), "+f"(d[64]), "+f"(d[65]), "+f"(d[66]), "+f"(d[67]), "+f"(d[68]), "+f"(d[69]), "+f"(d[70]), "+f"(d[71]), "+f"(d[72]), "+f"(d[73]), "+f"(d[74]), "+f"(d[75]), "+f"(d[76]), "+f"(d[77]), "+f"(d[78]), "+f"(d[79]), "+f"(d[80]), "+f"(d[81]), "+f"(d[82]), "+f"(d[83]), "+f"(d[84]), "+f"(d[85]), "+f"(d[86]), "+f"(d[87]), "+f"(d[88]), "+f"(d[89]), "+f"(d[90]), "+f"(d[91]), "+f"(d[92]), "+f"(d[93]), "+f"(d[94]), "+f"(d[95]), "+f"(d[96]), "+f"(d[97]), "+f"(d[98]), "+f"(d[99]), "+f"(d[100]), "+f"(d[101]), "+f"(d[102]), "+f"(d[103]), "+f"(d[104]), "+f"(d[105]), "+f"(d[106]), "+f"(d[107]), "+f"(d[108]), "+f"(d[109]), "+f"(d[110]), "+f"(d[111]), "+f"(d[112]), "+f"(d[113]), "+f"(d[114]), "+f"(d[115]), "+f"(d[116]), "+f"(d[117]), "+f"(d[118]), "+f"(d[119]), "+f"(d[120]), "+f"(d[121]), "+f"(d[122]), "+f"(d[123]), "+f"(d[124]), "+f"(d[125]), "+f"(d[126]), "+f"(d[127])
    : "r"(a0), "r"(a1), "r"(a2), "r"(a3), "l"(db), "r"(sd), "n"(OB));
}
template <int OA, int OB> __device__ __forceinline__ void wgmma_ss_tb(float (&d)[96], uint64_t da, uint64_t db, int sd) {
  asm volatile("{\n.reg .pred p;\n.reg .b64 a, b;\nadd.s64 a, %96, %99;\nadd.s64 b, %97, %100;\nsetp.ne.b32 p, %98, 0;\n"
    "wgmma.mma_async.sync.aligned.m64n192k16.f32.bf16.bf16 {%0, %1, %2, %3, %4, %5, %6, %7, %8, %9, %10, %11, %12, %13, %14, %15, %16, %17, %18, %19, %20, %21, %22, %23, %24, %25, %26, %27, %28, %29, %30, %31, %32, %33, %34, %35, %36, %37, %38, %39, %40, %41, %42, %43, %44, %45, %46, %47, %48, %49, %50, %51, %52, %53, %54, %55, %56, %57, %58, %59, %60, %61, %62, %63, %64, %65, %66, %67, %68, %69, %70, %71, %72, %73, %74, %75, %76, %77, %78, %79, %80, %81, %82, %83, %84, %85, %86, %87, %88, %89, %90, %91, %92, %93, %94, %95}, a, b, p, 1, 1, 0, 1;\n}\n"
    : "+f"(d[0]), "+f"(d[1]), "+f"(d[2]), "+f"(d[3]), "+f"(d[4]), "+f"(d[5]), "+f"(d[6]), "+f"(d[7]), "+f"(d[8]), "+f"(d[9]), "+f"(d[10]), "+f"(d[11]), "+f"(d[12]), "+f"(d[13]), "+f"(d[14]), "+f"(d[15]), "+f"(d[16]), "+f"(d[17]), "+f"(d[18]), "+f"(d[19]), "+f"(d[20]), "+f"(d[21]), "+f"(d[22]), "+f"(d[23]), "+f"(d[24]), "+f"(d[25]), "+f"(d[26]), "+f"(d[27]), "+f"(d[28]), "+f"(d[29]), "+f"(d[30]), "+f"(d[31]), "+f"(d[32]), "+f"(d[33]), "+f"(d[34]), "+f"(d[35]), "+f"(d[36]), "+f"(d[37]), "+f"(d[38]), "+f"(d[39]), "+f"(d[40]), "+f"(d[41]), "+f"(d[42]), "+f"(d[43]), "+f"(d[44]), "+f"(d[45]), "+f"(d[46]), "+f"(d[47]), "+f"(d[48]), "+f"(d[49]), "+f"(d[50]), "+f"(d[51]), "+f"(d[52]), "+f"(d[53]), "+f"(d[54]), "+f"(d[55]), "+f"(d[56]), "+f"(d[57]), "+f"(d[58]), "+f"(d[59]), "+f"(d[60]), "+f"(d[61]), "+f"(d[62]), "+f"(d[63]), "+f"(d[64]), "+f"(d[65]), "+f"(d[66]), "+f"(d[67]), "+f"(d[68]), "+f"(d[69]), "+f"(d[70]), "+f"(d[71]), "+f"(d[72]), "+f"(d[73]), "+f"(d[74]), "+f"(d[75]), "+f"(d[76]), "+f"(d[77]), "+f"(d[78]), "+f"(d[79]), "+f"(d[80]), "+f"(d[81]), "+f"(d[82]), "+f"(d[83]), "+f"(d[84]), "+f"(d[85]), "+f"(d[86]), "+f"(d[87]), "+f"(d[88]), "+f"(d[89]), "+f"(d[90]), "+f"(d[91]), "+f"(d[92]), "+f"(d[93]), "+f"(d[94]), "+f"(d[95])
    : "l"(da), "l"(db), "r"(sd), "n"(OA), "n"(OB));
}
template <int OB> __device__ __forceinline__ void wgmma_rs_tb(float (&d)[96], uint32_t a0, uint32_t a1, uint32_t a2, uint32_t a3, uint64_t db, int sd) {
  asm volatile("{\n.reg .pred p;\n.reg .b64 b;\nadd.s64 b, %100, %102;\nsetp.ne.b32 p, %101, 0;\n"
    "wgmma.mma_async.sync.aligned.m64n192k16.f32.bf16.bf16 {%0, %1, %2, %3, %4, %5, %6, %7, %8, %9, %10, %11, %12, %13, %14, %15, %16, %17, %18, %19, %20, %21, %22, %23, %24, %25, %26, %27, %28, %29, %30, %31, %32, %33, %34, %35, %36, %37, %38, %39, %40, %41, %42, %43, %44, %45, %46, %47, %48, %49, %50, %51, %52, %53, %54, %55, %56, %57, %58, %59, %60, %61, %62, %63, %64, %65, %66, %67, %68, %69, %70, %71, %72, %73, %74, %75, %76, %77, %78, %79, %80, %81, %82, %83, %84, %85, %86, %87, %88, %89, %90, %91, %92, %93, %94, %95}, {%96, %97, %98, %99}, b, p, 1, 1, 1;\n}\n"
    : "+f"(d[0]), "+f"(d[1]), "+f"(d[2]), "+f"(d[3]), "+f"(d[4]), "+f"(d[5]), "+f"(d[6]), "+f"(d[7]), "+f"(d[8]), "+f"(d[9]), "+f"(d[10]), "+f"(d[11]), "+f"(d[12]), "+f"(d[13]), "+f"(d[14]), "+f"(d[15]), "+f"(d[16]), "+f"(d[17]), "+f"(d[18]), "+f"(d[19]), "+f"(d[20]), "+f"(d[21]), "+f"(d[22]), "+f"(d[23]), "+f"(d[24]), "+f"(d[25]), "+f"(d[26]), "+f"(d[27]), "+f"(d[28]), "+f"(d[29]), "+f"(d[30]), "+f"(d[31]), "+f"(d[32]), "+f"(d[33]), "+f"(d[34]), "+f"(d[35]), "+f"(d[36]), "+f"(d[37]), "+f"(d[38]), "+f"(d[39]), "+f"(d[40]), "+f"(d[41]), "+f"(d[42]), "+f"(d[43]), "+f"(d[44]), "+f"(d[45]), "+f"(d[46]), "+f"(d[47]), "+f"(d[48]), "+f"(d[49]), "+f"(d[50]), "+f"(d[51]), "+f"(d[52]), "+f"(d[53]), "+f"(d[54]), "+f"(d[55]), "+f"(d[56]), "+f"(d[57]), "+f"(d[58]), "+f"(d[59]), "+f"(d[60]), "+f"(d[61]), "+f"(d[62]), "+f"(d[63]), "+f"(d[64]), "+f"(d[65]), "+f"(d[66]), "+f"(d[67]), "+f"(d[68]), "+f"(d[69]), "+f"(d[70]), "+f"(d[71]), "+f"(d[72]), "+f"(d[73]), "+f"(d[74]), "+f"(d[75]), "+f"(d[76]), "+f"(d[77]), "+f"(d[78]), "+f"(d[79]), "+f"(d[80]), "+f"(d[81]), "+f"(d[82]), "+f"(d[83]), "+f"(d[84]), "+f"(d[85]), "+f"(d[86]), "+f"(d[87]), "+f"(d[88]), "+f"(d[89]), "+f"(d[90]), "+f"(d[91]), "+f"(d[92]), "+f"(d[93]), "+f"(d[94]), "+f"(d[95])
    : "r"(a0), "r"(a1), "r"(a2), "r"(a3), "l"(db), "r"(sd), "n"(OB));
}
template <int OA, int OB> __device__ __forceinline__ void wgmma_ss_tb(float (&d)[64], uint64_t da, uint64_t db, int sd) {
  asm volatile("{\n.reg .pred p;\n.reg .b64 a, b;\nadd.s64 a, %64, %67;\nadd.s64 b, %65, %68;\nsetp.ne.b32 p, %66, 0;\n"
    "wgmma.mma_async.sync.aligned.m64n128k16.f32.bf16.bf16 {%0, %1, %2, %3, %4, %5, %6, %7, %8, %9, %10, %11, %12, %13, %14, %15, %16, %17, %18, %19, %20, %21, %22, %23, %24, %25, %26, %27, %28, %29, %30, %31, %32, %33, %34, %35, %36, %37, %38, %39, %40, %41, %42, %43, %44, %45, %46, %47, %48, %49, %50, %51, %52, %53, %54, %55, %56, %57, %58, %59, %60, %61, %62, %63}, a, b, p, 1, 1, 0, 1;\n}\n"
    : "+f"(d[0]), "+f"(d[1]), "+f"(d[2]), "+f"(d[3]), "+f"(d[4]), "+f"(d[5]), "+f"(d[6]), "+f"(d[7]), "+f"(d[8]), "+f"(d[9]), "+f"(d[10]), "+f"(d[11]), "+f"(d[12]), "+f"(d[13]), "+f"(d[14]), "+f"(d[15]), "+f"(d[16]), "+f"(d[17]), "+f"(d[18]), "+f"(d[19]), "+f"(d[20]), "+f"(d[21]), "+f"(d[22]), "+f"(d[23]), "+f"(d[24]), "+f"(d[25]), "+f"(d[26]), "+f"(d[27]), "+f"(d[28]), "+f"(d[29]), "+f"(d[30]), "+f"(d[31]), "+f"(d[32]), "+f"(d[33]), "+f"(d[34]), "+f"(d[35]), "+f"(d[36]), "+f"(d[37]), "+f"(d[38]), "+f"(d[39]), "+f"(d[40]), "+f"(d[41]), "+f"(d[42]), "+f"(d[43]), "+f"(d[44]), "+f"(d[45]), "+f"(d[46]), "+f"(d[47]), "+f"(d[48]), "+f"(d[49]), "+f"(d[50]), "+f"(d[51]), "+f"(d[52]), "+f"(d[53]), "+f"(d[54]), "+f"(d[55]), "+f"(d[56]), "+f"(d[57]), "+f"(d[58]), "+f"(d[59]), "+f"(d[60]), "+f"(d[61]), "+f"(d[62]), "+f"(d[63])
    : "l"(da), "l"(db), "r"(sd), "n"(OA), "n"(OB));
}
template <int OB> __device__ __forceinline__ void wgmma_rs_tb(float (&d)[64], uint32_t a0, uint32_t a1, uint32_t a2, uint32_t a3, uint64_t db, int sd) {
  asm volatile("{\n.reg .pred p;\n.reg .b64 b;\nadd.s64 b, %68, %70;\nsetp.ne.b32 p, %69, 0;\n"
    "wgmma.mma_async.sync.aligned.m64n128k16.f32.bf16.bf16 {%0, %1, %2, %3, %4, %5, %6, %7, %8, %9, %10, %11, %12, %13, %14, %15, %16, %17, %18, %19, %20, %21, %22, %23, %24, %25, %26, %27, %28, %29, %30, %31, %32, %33, %34, %35, %36, %37, %38, %39, %40, %41, %42, %43, %44, %45, %46, %47, %48, %49, %50, %51, %52, %53, %54, %55, %56, %57, %58, %59, %60, %61, %62, %63}, {%64, %65, %66, %67}, b, p, 1, 1, 1;\n}\n"
    : "+f"(d[0]), "+f"(d[1]), "+f"(d[2]), "+f"(d[3]), "+f"(d[4]), "+f"(d[5]), "+f"(d[6]), "+f"(d[7]), "+f"(d[8]), "+f"(d[9]), "+f"(d[10]), "+f"(d[11]), "+f"(d[12]), "+f"(d[13]), "+f"(d[14]), "+f"(d[15]), "+f"(d[16]), "+f"(d[17]), "+f"(d[18]), "+f"(d[19]), "+f"(d[20]), "+f"(d[21]), "+f"(d[22]), "+f"(d[23]), "+f"(d[24]), "+f"(d[25]), "+f"(d[26]), "+f"(d[27]), "+f"(d[28]), "+f"(d[29]), "+f"(d[30]), "+f"(d[31]), "+f"(d[32]), "+f"(d[33]), "+f"(d[34]), "+f"(d[35]), "+f"(d[36]), "+f"(d[37]), "+f"(d[38]), "+f"(d[39]), "+f"(d[40]), "+f"(d[41]), "+f"(d[42]), "+f"(d[43]), "+f"(d[44]), "+f"(d[45]), "+f"(d[46]), "+f"(d[47]), "+f"(d[48]), "+f"(d[49]), "+f"(d[50]), "+f"(d[51]), "+f"(d[52]), "+f"(d[53]), "+f"(d[54]), "+f"(d[55]), "+f"(d[56]), "+f"(d[57]), "+f"(d[58]), "+f"(d[59]), "+f"(d[60]), "+f"(d[61]), "+f"(d[62]), "+f"(d[63])
    : "r"(a0), "r"(a1), "r"(a2), "r"(a3), "l"(db), "r"(sd), "n"(OB));
}
template <int OA, int OB> __device__ __forceinline__ void wgmma_ss_ta(float (&d)[64], uint64_t da, uint64_t db, int sd) {
  asm volatile("{\n.reg .pred p;\n.reg .b64 a, b;\nadd.s64 a, %64, %67;\nadd.s64 b, %65, %68;\nsetp.ne.b32 p, %66, 0;\n"
    "wgmma.mma_async.sync.aligned.m64n128k16.f32.bf16.bf16 {%0, %1, %2, %3, %4, %5, %6, %7, %8, %9, %10, %11, %12, %13, %14, %15, %16, %17, %18, %19, %20, %21, %22, %23, %24, %25, %26, %27, %28, %29, %30, %31, %32, %33, %34, %35, %36, %37, %38, %39, %40, %41, %42, %43, %44, %45, %46, %47, %48, %49, %50, %51, %52, %53, %54, %55, %56, %57, %58, %59, %60, %61, %62, %63}, a, b, p, 1, 1, 1, 0;\n}\n"
    : "+f"(d[0]), "+f"(d[1]), "+f"(d[2]), "+f"(d[3]), "+f"(d[4]), "+f"(d[5]), "+f"(d[6]), "+f"(d[7]), "+f"(d[8]), "+f"(d[9]), "+f"(d[10]), "+f"(d[11]), "+f"(d[12]), "+f"(d[13]), "+f"(d[14]), "+f"(d[15]), "+f"(d[16]), "+f"(d[17]), "+f"(d[18]), "+f"(d[19]), "+f"(d[20]), "+f"(d[21]), "+f"(d[22]), "+f"(d[23]), "+f"(d[24]), "+f"(d[25]), "+f"(d[26]), "+f"(d[27]), "+f"(d[28]), "+f"(d[29]), "+f"(d[30]), "+f"(d[31]), "+f"(d[32]), "+f"(d[33]), "+f"(d[34]), "+f"(d[35]), "+f"(d[36]), "+f"(d[37]), "+f"(d[38]), "+f"(d[39]), "+f"(d[40]), "+f"(d[41]), "+f"(d[42]), "+f"(d[43]), "+f"(d[44]), "+f"(d[45]), "+f"(d[46]), "+f"(d[47]), "+f"(d[48]), "+f"(d[49]), "+f"(d[50]), "+f"(d[51]), "+f"(d[52]), "+f"(d[53]), "+f"(d[54]), "+f"(d[55]), "+f"(d[56]), "+f"(d[57]), "+f"(d[58]), "+f"(d[59]), "+f"(d[60]), "+f"(d[61]), "+f"(d[62]), "+f"(d[63])
    : "l"(da), "l"(db), "r"(sd), "n"(OA), "n"(OB));
}
template <int OB> __device__ __forceinline__ void wgmma_rs(float (&d)[64], uint32_t a0, uint32_t a1, uint32_t a2, uint32_t a3, uint64_t db, int sd) {
  asm volatile("{\n.reg .pred p;\n.reg .b64 b;\nadd.s64 b, %68, %70;\nsetp.ne.b32 p, %69, 0;\n"
    "wgmma.mma_async.sync.aligned.m64n128k16.f32.bf16.bf16 {%0, %1, %2, %3, %4, %5, %6, %7, %8, %9, %10, %11, %12, %13, %14, %15, %16, %17, %18, %19, %20, %21, %22, %23, %24, %25, %26, %27, %28, %29, %30, %31, %32, %33, %34, %35, %36, %37, %38, %39, %40, %41, %42, %43, %44, %45, %46, %47, %48, %49, %50, %51, %52, %53, %54, %55, %56, %57, %58, %59, %60, %61, %62, %63}, {%64, %65, %66, %67}, b, p, 1, 1, 0;\n}\n"
    : "+f"(d[0]), "+f"(d[1]), "+f"(d[2]), "+f"(d[3]), "+f"(d[4]), "+f"(d[5]), "+f"(d[6]), "+f"(d[7]), "+f"(d[8]), "+f"(d[9]), "+f"(d[10]), "+f"(d[11]), "+f"(d[12]), "+f"(d[13]), "+f"(d[14]), "+f"(d[15]), "+f"(d[16]), "+f"(d[17]), "+f"(d[18]), "+f"(d[19]), "+f"(d[20]), "+f"(d[21]), "+f"(d[22]), "+f"(d[23]), "+f"(d[24]), "+f"(d[25]), "+f"(d[26]), "+f"(d[27]), "+f"(d[28]), "+f"(d[29]), "+f"(d[30]), "+f"(d[31]), "+f"(d[32]), "+f"(d[33]), "+f"(d[34]), "+f"(d[35]), "+f"(d[36]), "+f"(d[37]), "+f"(d[38]), "+f"(d[39]), "+f"(d[40]), "+f"(d[41]), "+f"(d[42]), "+f"(d[43]), "+f"(d[44]), "+f"(d[45]), "+f"(d[46]), "+f"(d[47]), "+f"(d[48]), "+f"(d[49]), "+f"(d[50]), "+f"(d[51]), "+f"(d[52]), "+f"(d[53]), "+f"(d[54]), "+f"(d[55]), "+f"(d[56]), "+f"(d[57]), "+f"(d[58]), "+f"(d[59]), "+f"(d[60]), "+f"(d[61]), "+f"(d[62]), "+f"(d[63])
    : "r"(a0), "r"(a1), "r"(a2), "r"(a3), "l"(db), "r"(sd), "n"(OB));
}
template <int OA, int OB> __device__ __forceinline__ void wgmma_ss_ta(float (&d)[4], uint64_t da, uint64_t db, int sd) {
  asm volatile("{\n.reg .pred p;\n.reg .b64 a, b;\nadd.s64 a, %4, %7;\nadd.s64 b, %5, %8;\nsetp.ne.b32 p, %6, 0;\n"
    "wgmma.mma_async.sync.aligned.m64n8k16.f32.bf16.bf16 {%0, %1, %2, %3}, a, b, p, 1, 1, 1, 0;\n}\n"
    : "+f"(d[0]), "+f"(d[1]), "+f"(d[2]), "+f"(d[3])
    : "l"(da), "l"(db), "r"(sd), "n"(OA), "n"(OB));
}

constexpr uint32_t U = 16384;
constexpr uint32_t SM_QO = 2 * U, SM_W = 8 * U, SM_V = 8 * U, SM_K1 = 12 * U, SM_BAR = 14 * U;
constexpr uint32_t B_WF = SM_BAR, B_KF = SM_BAR + 48, B_CF = SM_BAR + 80, B_GATE = SM_BAR + 128, B_OF = SM_BAR + 136, B_EP = SM_BAR + 144, B_EXT = SM_BAR + 152, B_Q3 = SM_BAR + 168, B_ANN = SM_BAR + 176,
                   B_WE = SM_BAR + 192, B_KE = SM_BAR + 240, B_CE = SM_BAR + 288, B_OS = SM_BAR + 344;
constexpr uint32_t SM_EP = SM_BAR + 384;
constexpr uint32_t SM_ONE = SM_BAR + 388;
constexpr uint32_t SM_STAT = SM_BAR + 400, SM_EXT = SM_STAT + 512;
constexpr uint32_t SM_BAD = SM_EXT + 2048;
constexpr int SMEM_BYTES = SM_BAR + 3072;
__device__ __forceinline__ uint32_t c_slot(int s) { return (0xBADC10u >> (4 * s)) & 15; }

struct Params {
  const __nv_bfloat16 *x, *k, *v, *wq, *wo, *wr;
  __nv_bfloat16* out;
  Scratch* g;
};

__device__ __forceinline__ void release2(uint32_t rbar, int lane) { if (lane < 2) mbar_arrive_cluster(rbar); }
__device__ __forceinline__ void pin_after(uint32_t a, float e0, float e1) {
  asm volatile("{\n.reg .pred p;\nsetp.lt.f32 p, %1, %2;\n@p st.shared.u32 [%0], %0;\n}\n" :: "r"(a), "f"(e0), "f"(-e1) : "memory"); }
__device__ __forceinline__ void lds128_after(uint32_t& x, uint32_t& y, uint32_t& z, uint32_t& w, uint32_t a, float e0, float e1) {
  asm volatile("{\n.reg .pred p;\nsetp.geu.f32 p, %5, %6;\n@p ld.shared.v4.u32 {%0,%1,%2,%3}, [%4];\n}\n" : "+r"(x), "+r"(y), "+r"(z), "+r"(w) : "r"(a), "f"(e0), "f"(-e1) : "memory"); }
__device__ __forceinline__ uint32_t launch_of(unsigned long long ticket) { return (uint32_t)(ticket / 132) + 1; }

__device__ __forceinline__ void attn_slow(float (&o)[64], float& i0, float& i1, const __nv_bfloat16* __restrict__ X, const __nv_bfloat16* __restrict__ WQ, uint32_t st0, uint32_t st1,
                                          const __nv_bfloat16* __restrict__ K, const __nv_bfloat16* __restrict__ V, int lane) {
  uint32_t q[32];
  #pragma unroll
  for (int i = 0; i < 64; i++) o[i] = 0.f;
  const int g = lane >> 2, qd = lane & 3;
  #pragma unroll 1
  for (int k0 = 0; k0 < DM; k0 += 16) {
    uint32_t a[4];
    #pragma unroll
    for (int e = 0; e < 4; e++) {
      const uint32_t xv = *(const uint32_t*)(X + (size_t)(g + (e & 1) * 8) * DM + k0 + (e >> 1) * 8 + 2 * qd);
      const float mb = bf_lo((e & 1) ? st1 : st0);
      a[e] = pack_bf16(bf_lo(xv) - mb, bf_hi(xv) - mb);
    }
    const unsigned short* wr = (const unsigned short*)(WQ + (size_t)(k0 + 2 * qd) * (NH * DH) + g);
    #pragma unroll
    for (int nb = 0; nb < 16; nb++) {
      uint32_t b0 = (uint32_t)wr[nb * 8] | ((uint32_t)wr[nb * 8 + NH * DH] << 16);
      uint32_t b1 = (uint32_t)wr[nb * 8 + 8 * NH * DH] | ((uint32_t)wr[nb * 8 + 9 * NH * DH] << 16);
      asm volatile("mma.sync.aligned.m16n8k16.row.col.f32.bf16.bf16.f32 {%0,%1,%2,%3}, {%4,%5,%6,%7}, {%8,%9}, {%0,%1,%2,%3};"
        : "+f"(o[nb*4]), "+f"(o[nb*4+1]), "+f"(o[nb*4+2]), "+f"(o[nb*4+3]) : "r"(a[0]), "r"(a[1]), "r"(a[2]), "r"(a[3]), "r"(b0), "r"(b1));
    }
  }
  {
    const float r0 = rcp_approx(bf_hi(st0)) * SCALE_LOG2E, r1 = rcp_approx(bf_hi(st1)) * SCALE_LOG2E;
    #pragma unroll
    for (int i = 0; i < 16; i++) { q[2*i] = pack_bf16(o[4*i] * r0, o[4*i+1] * r0); q[2*i+1] = pack_bf16(o[4*i+2] * r1, o[4*i+3] * r1); }
    #pragma unroll
    for (int i = 0; i < 64; i++) o[i] = 0.f;
  }
  float m0 = -INFINITY, m1 = -INFINITY, l0 = 0.f, l1 = 0.f;
  #pragma unroll 1
  for (int n0 = 0; n0 < S_LEN; n0 += 16) {
    float s[8];
    #pragma unroll
    for (int i = 0; i < 8; i++) s[i] = 0.f;
    #pragma unroll
    for (int nb = 0; nb < 2; nb++) {
      const uint32_t* kr = (const uint32_t*)(K + (size_t)(n0 + nb * 8 + g) * DH) + qd;
      #pragma unroll
      for (int kk = 0; kk < 8; kk++) {
        uint32_t b0 = kr[kk * 8], b1 = kr[kk * 8 + 4];
        asm volatile("mma.sync.aligned.m16n8k16.row.col.f32.bf16.bf16.f32 {%0,%1,%2,%3}, {%4,%5,%6,%7}, {%8,%9}, {%0,%1,%2,%3};"
          : "+f"(s[nb*4]), "+f"(s[nb*4+1]), "+f"(s[nb*4+2]), "+f"(s[nb*4+3]) : "r"(q[kk*4]), "r"(q[kk*4+1]), "r"(q[kk*4+2]), "r"(q[kk*4+3]), "r"(b0), "r"(b1));
      }
    }
    float x0 = fmaxf(fmaxf(s[0], s[1]), fmaxf(s[4], s[5])), x1 = fmaxf(fmaxf(s[2], s[3]), fmaxf(s[6], s[7]));
    x0 = fmaxf(x0, __shfl_xor_sync(0xffffffff, x0, 1)); x1 = fmaxf(x1, __shfl_xor_sync(0xffffffff, x1, 1));
    x0 = fmaxf(x0, __shfl_xor_sync(0xffffffff, x0, 2)); x1 = fmaxf(x1, __shfl_xor_sync(0xffffffff, x1, 2));
    const float n0m = fmaxf(m0, x0), n1m = fmaxf(m1, x1);
    const float sh0 = (n0m == -INFINITY) ? 0.f : n0m, sh1 = (n1m == -INFINITY) ? 0.f : n1m;
    const float c0 = ex2(m0 - sh0), c1 = ex2(m1 - sh1);
    m0 = n0m; m1 = n1m;
    s[0] = ex2(s[0] - sh0); s[1] = ex2(s[1] - sh0); s[4] = ex2(s[4] - sh0); s[5] = ex2(s[5] - sh0);
    s[2] = ex2(s[2] - sh1); s[3] = ex2(s[3] - sh1); s[6] = ex2(s[6] - sh1); s[7] = ex2(s[7] - sh1);
    l0 = l0 * c0 + (s[0] + s[1]) + (s[4] + s[5]); l1 = l1 * c1 + (s[2] + s[3]) + (s[6] + s[7]);
    const uint32_t a0 = pack_bf16(s[0], s[1]), a1 = pack_bf16(s[2], s[3]), a2 = pack_bf16(s[4], s[5]), a3 = pack_bf16(s[6], s[7]);
    const unsigned short* vr = (const unsigned short*)(V + (size_t)(n0 + 2 * qd) * DH + g);
    #pragma unroll
    for (int nb = 0; nb < 16; nb++) {
      uint32_t b0 = (uint32_t)vr[nb * 8] | ((uint32_t)vr[nb * 8 + DH] << 16);
      uint32_t b1 = (uint32_t)vr[nb * 8 + 8 * DH] | ((uint32_t)vr[nb * 8 + 9 * DH] << 16);
      o[nb*4] *= c0; o[nb*4+1] *= c0; o[nb*4+2] *= c1; o[nb*4+3] *= c1;
      asm volatile("mma.sync.aligned.m16n8k16.row.col.f32.bf16.bf16.f32 {%0,%1,%2,%3}, {%4,%5,%6,%7}, {%8,%9}, {%0,%1,%2,%3};"
        : "+f"(o[nb*4]), "+f"(o[nb*4+1]), "+f"(o[nb*4+2]), "+f"(o[nb*4+3]) : "r"(a0), "r"(a1), "r"(a2), "r"(a3), "r"(b0), "r"(b1));
    }
  }
  l0 += __shfl_xor_sync(0xffffffff, l0, 1); l1 += __shfl_xor_sync(0xffffffff, l1, 1);
  l0 += __shfl_xor_sync(0xffffffff, l0, 2); l1 += __shfl_xor_sync(0xffffffff, l1, 2);
  i0 = rcp_approx(l0); i1 = rcp_approx(l1);
}

__device__ __forceinline__ void flag_if(uint32_t a, bool c) { asm volatile("{\n.reg .pred p;\nsetp.ne.u32 p, %1, 0;\n@p st.shared.u8 [%0], 1;\n}\n" :: "r"(a), "r"((uint32_t)c) : "memory"); }
__device__ __forceinline__ void row_scale(float& l0, float& l1, int one, uint32_t flag) {
  l0 += __shfl_xor_sync(0xffffffff, l0, one); l1 += __shfl_xor_sync(0xffffffff, l1, one);
  l0 += __shfl_xor_sync(0xffffffff, l0, 2); l1 += __shfl_xor_sync(0xffffffff, l1, 2);
  flag_if(flag, !((l0 >= 0.00390625f) && (l0 <= 1.8446744e19f) && (l1 >= 0.00390625f) && (l1 <= 1.8446744e19f)));
  l0 = rcp_fast(l0); l1 = rcp_fast(l1);
}
__device__ __forceinline__ uint32_t taint(uint32_t z, uint32_t a, uint32_t b) { asm("fma.rn.bf16x2 %0, %1, %2, %0;" : "+r"(z) : "r"(a), "r"(b)); return z; }
__device__ __forceinline__ bool tainted(uint32_t z) { return (taint(0u, z, 0u) & 0x7fff7fffu) != 0; }

__device__ __forceinline__ int kv_tile(int j) { return j < 32 ? j ^ 16 : j; }
__device__ __forceinline__ uint32_t qo_slot(int h) { return SM_QO + ((0x3102 >> (4 * h)) & 3) * 2 * U; }
__device__ __forceinline__ uint32_t o_addr(uint32_t wr, int lane) { return wr + (lane & 15) * 128 + (((lane >> 4) ^ (lane & 7)) << 4); }
template <bool CHECK> __device__ __forceinline__ uint32_t store_o(uint32_t a, const float (&o)[64], float i0, float i1) {
  uint32_t z = 0;
  #pragma unroll
  for (int i = 0; i < 8; i++) {
    const uint32_t w0 = pack_bf16(o[8*i] * i0, o[8*i+1] * i0), w1 = pack_bf16(o[8*i+2] * i1, o[8*i+3] * i1), w2 = pack_bf16(o[8*i+4] * i0, o[8*i+5] * i0), w3 = pack_bf16(o[8*i+6] * i1, o[8*i+7] * i1);
    stsm4((a ^ ((i & 3) << 5)) + (i >> 2) * U, w0, w1, w2, w3);
    if (CHECK) z = taint(taint(z, w0, w1), w2, w3);
  }
  return z;
}

__device__ __noinline__ void redo_heads(const Params& P, uint32_t sb, uint32_t bad, int row0, int head0) {
  const int lane = threadIdx.x & 31;
  const uint32_t st0 = lds32(sb + SM_STAT + ((row0 & 127) + (lane >> 2)) * 4), st1 = lds32(sb + SM_STAT + ((row0 & 127) + 8 + (lane >> 2)) * 4);
  #pragma unroll 1
  for (int h = 0; h < 4; h++) {
    if (!((bad >> (8 * h)) & 1)) continue;
    float o[64], i0, i1;
    const int head = head0 + (kv_tile(h * 16) >> 4);
    attn_slow(o, i0, i1, P.x + (size_t)row0 * DM, P.wq + head * DH, st0, st1, P.k + (size_t)head * S_LEN * DH, P.v + (size_t)head * S_LEN * DH, lane);
    store_o<false>(o_addr(sb + (row0 & 127) * 128, lane) + qo_slot(h), o, i0, i1);
  }
}

template <int K> struct IC { static constexpr int v = K; };
template <int K, int N, class F> __device__ __forceinline__ void static_for(F&& f) { if constexpr (K < N) { f(IC<K>{}); static_for<K + 1, N>(f); } }
template <uint32_t OFF, int SITE> __device__ __forceinline__ void mma_qk(float (&s)[64], const uint32_t (&q)[32], uint64_t d0) {
  wg_fence();
  static_for<0, 8>([&](auto kc) { constexpr int k = decltype(kc)::v; wgmma_rs<doff(OFF, 16) - SITE + (k / 4) * 1024 + (k % 4) * 2>(s, q[k*4], q[k*4+1], q[k*4+2], q[k*4+3], d0, k > 0); });
  wg_commit();
}
template <uint32_t OFF, int SITE> __device__ __forceinline__ void mma_pv(float (&o)[64], const uint32_t (&p)[32], uint64_t d0, bool keep) {
  wg_fence();
  static_for<0, 8>([&](auto kc) { constexpr int k = decltype(kc)::v; wgmma_rs_tb<doff(OFF, U) - SITE + k * 128>(o, p[k*4], p[k*4+1], p[k*4+2], p[k*4+3], d0, (k > 0) || keep); });
  wg_commit();
}
template <int I0, int I1>
__device__ __forceinline__ void exp_rows(float (&s)[64], float (&l)[2]) {
  #pragma unroll
  for (int i = I0; i < I1; i += 2) {
    s[i] = ex2(s[i]); s[i+1] = ex2(s[i+1]);
    l[(i >> 1) & 1] += s[i] + s[i+1];
  }
}

template <int KS, bool EDGE>
__device__ __forceinline__ void attn_step(uint32_t sb, uint32_t rb, uint32_t wr, uint32_t qa, int wg, int lane, int j, int ph, float (&s)[64], float (&o)[64], uint32_t (&p)[32], uint32_t (&q)[32],
                                          float (&l)[2], bool& ready, Scratch* g, unsigned (&tz)[3]) {
  constexpr bool FIRST = EDGE && !KS, LAST = EDGE && KS;
  TRACEF(2, wg, 32 + j);
  STALL(1);
  if (!ready) mbar_wait(sb + B_KF + KS * 8, ph);
  bar_sync(1 + wg, 256);
  mma_qk<KS * SM_K1, EDGE>(s, q, desc(sb, EDGE));
  if (!ready) mbar_wait(sb + B_KF + 24 - KS * 8, KS ? ph : ph ^ 1);
  mma_pv<SM_V + (1 - KS) * 2 * U, EDGE>(o, p, desc(sb, EDGE), !KS || LAST || ((j & 15) != 1));
  bar_arrive(1 + (wg ^ 1), 256);
  const int one = FIRST ? lds32(sb + SM_ONE) : 1;
  wg_wait<1>();
  fence_regs(s);
  release2(rb + B_KE + KS * 8, lane);
  float i0 = l[0], i1 = l[1];
  if (FIRST) { row_scale(i0, i1, one, sb + SM_BAD - 1 + ((wr - sb) >> 9) + (j >> 4)); l[0] = fminf(i0, 0.f); l[1] = fminf(i1, 0.f); }
  constexpr int DP = FIRST ? DPOSF : (LAST && DPOS < 7 * QSP ? 7 * QSP : DPOS);
  if (LAST) {
    fence_regs(q);
    const uint32_t a = qa + qo_slot(j >> 4);
    static_for<0, 8>([&](auto ic) { constexpr int i = decltype(ic)::v;
      lds128_after(q[4*i], q[4*i+1], q[4*i+2], q[4*i+3], a + (i >> 2) * U + (i & 3) * 512, l[0], l[1]);
      exp_rows<i * QSP, i < 7 ? (i + 1) * QSP : DP>(s, l);
    });
  } else exp_rows<0, DP>(s, l);
  pin_after(sb + SM_BAD, l[0], l[1]);
  exp_rows<DP, 64>(s, l);
  wg_wait<0>();
  fence_regs(o); fence_regs(p);
  release2(rb + B_KE + 24 - KS * 8, lane);
  ready = mbar_test2(sb + B_KF + 16 + KS * 8, ph, sb + B_KF + 8 - KS * 8, KS ? ph ^ 1 : ph);
  if (FIRST) {
    const int h = (j >> 4) - 1;
    store_o<false>(o_addr(wr, lane) + qo_slot(h), o, i0, i1);
    if (lane == 0) mbar_arrive(sb + B_OS + h * 8);
  }
  #pragma unroll
  for (int i = 0; i < 32; i++) p[i] = pack_bf16(s[2*i], s[2*i+1]);
}

template <int SITE> __device__ __forceinline__ void mma_c(float (&acc)[64], uint32_t sb, int slot, int h, int arrive_bar) {
  const uint64_t a = desc(sb, c_slot(slot) * 1024 + SITE), b = desc(sb, h * 2048 + SITE);
  wg_fence();
  static_for<0, 8>([&](auto kc) { constexpr int k = decltype(kc)::v;
    wgmma_ss_ta<doff(0, 16) - SITE + k * 128, doff(SM_QO, 16) - SITE + (k >> 2) * 1024 + (k & 3) * 2>(acc, a, b, k > 0 || h > 0);
  });
  wg_commit();
  if (arrive_bar) bar_arrive(arrive_bar, 256);
}

__device__ __forceinline__ void side_cta(const Params& P, const CUtensorMap* tmX, const CUtensorMap* tmW, const CUtensorMap* tmG, const CUtensorMap* tmU,
                                         const CUtensorMap* tmD, uint32_t sb, int m) {
  const int tid = threadIdx.x, warp = __shfl_sync(0xffffffff, tid >> 5, 0), lane = tid & 31;
  const uint32_t XS = sb + 12 * U, HS = XS + 10240, BF = sb + SM_BAR, BE = BF + 96, XF = BE + 96, XE = XF + 32, BW = XE + 32, SEL = BW + 16, KEY = SEL + 64;
  Scratch* const g = P.g;
  const int nj = m < 3 ? 14 : 12, nd = m < 3 ? 4 : 3, f0 = m * 448;
  if (elect_one()) { mbar_init(BF + warp * 8, 1); mbar_init(BE + warp * 8, 4); if (warp < 9) mbar_init(XF + warp * 8, (warp & 4) ? 8 : 1); }
  if (tid == 32) sts32(SEL + 32, launch_of(atomicAdd(&g->ticket, 1ull)));
  __syncthreads();
  const uint32_t launch = lds32(SEL + 32);
  if (warp == 0) {
    if (elect_one()) {
      mbar_expect_tx(BW, 10 * U);
      #pragma unroll 1
      for (int i = 0; i < 10; i++) tma_load_2d(sb + i * U, tmW, BW, m * 1024 + (i < 5 ? 448 : 960), (i < 5 ? i : i - 5) * 128);
    }
    #pragma unroll 1
    for (int n = 0, qt = 0, c = 0; n < 160; n++) {
      const uint32_t bar = XF + (n & 3) * 8;
      mbar_wait(bar + 32, ((n >> 2) & 1) ^ 1);
      if (elect_one()) {
        mbar_expect_tx(bar, U);
        tma_load_2d(sb + (10 + (n & 3)) * U, tmX, bar, c * 64, qt * 128);
        if (c == 0 && qt < 15) l2_prefetch(P.x + (size_t)(qt * 128 + 128 + m * 32) * DM, 32 * DM * 2);
      }
      if (++c == 10) { c = 0; qt++; }
    }
  } else if (warp < 3) {
    #pragma unroll 1
    for (int qt = 0; qt < 16; qt++) {
      bar_sync(1 + warp, 160);
      if (lane == 0) flag_add_release(&g->q3_done[m].v);
      __syncwarp();
    }
  } else if (warp >= 4) {
    float acc[64], cs[32];
    mbar_wait(BW, 0);
    #pragma unroll 1
    for (int c = 0; c < 10; c++) {
      wg_fence();
      static_for<0, 4>([&](auto kc) { constexpr int k = decltype(kc)::v;
        wgmma_rs_tb<doff(0, 5 * U) + k * 128>(acc, 0x3f803f80u, 0x3f803f80u, 0x3f803f80u, 0x3f803f80u, desc(sb, c * 512), k || c); });
      wg_commit();
      wg_wait<0>();
    }
    fence_regs(acc);
    #pragma unroll
    for (int i = 0; i < 32; i++) cs[i] = -acc[(i >> 1) * 4 + (i & 1)];
    fence_regs(cs);
    #pragma unroll 1
    for (int qt = 0, n = 0; qt < 16; qt++) {
      const uint32_t* const sp = g->stat + qt * 128 + (warp - 4) * 16 + (lane >> 2);
      uint32_t st0, st1;
      #pragma unroll 1
      for (int c = 0; c < 10; c++, n++) {
        const uint64_t a = desc(sb, (n & 3) * 1024 + (warp >> 3) * 512), b = desc(sb, c * 512);
        mbar_wait(XF + (n & 3) * 8, (n >> 2) & 1);
        wg_fence();
        static_for<0, 4>([&](auto kc) { constexpr int k = decltype(kc)::v; wgmma_ss_tb<doff(10 * U, 16) + k * 2, doff(0, 5 * U) + k * 128>(acc, a, b, k || c); });
        wg_commit();
        if (c == 9) { st0 = ldg32(sp); st1 = ldg32(sp + 8); }
        wg_wait<1>();
        if (c && lane == 0) mbar_arrive(XE + ((n - 1) & 3) * 8);
      }
      #pragma unroll 1
      for (int it = 0; __any_sync(0xffffffff, tag_miss(st0, st1, launch << 31) >> 31) && it < MAXPOLL; it++) { st0 = ldg32(sp); st1 = ldg32(sp + 8); }
      st0 &= 0x7fffffffu; st1 &= 0x7fffffffu;
      const float rs[2] = {rcp_fast(bf_hi(st0)) * SCALE_LOG2E, rcp_fast(bf_hi(st1)) * SCALE_LOG2E}, nm[2] = {bf_lo(st0), bf_lo(st1)};
      wg_wait<0>();
      fence_regs(acc);
      if (lane == 0) mbar_arrive(XE + ((n - 1) & 3) * 8);
      STALL(7);
      uint4* const dst = g->q3 + (qt * 8 + m * 2) * 1024 + (warp - 4) * 128 + lane;
      #pragma unroll
      for (int e = 0; e < 8; e++) {
        uint32_t w[4];
        #pragma unroll
        for (int i = 0; i < 4; i++)
          w[i] = pack_bf16(fmaf(nm[i & 1], cs[4*e + (i & 2)], acc[8*e + 2*i]) * rs[i & 1], fmaf(nm[i & 1], cs[4*e + (i & 2) + 1], acc[8*e + 2*i + 1]) * rs[i & 1]);
        dst[(e >> 2) * 1024 + (e & 3) * 32] = make_uint4(w[0], w[1], w[2], w[3]);
      }
      bar_sync(1 + (warp >> 2), 160);
    }
  }
  if (tid == 96) flag_wait(&g->cnt_gate.v, launch * 256);
  __syncthreads();
  TRACE(0, 1);
  if (tid >= 256 && tid < 320) sts128(HS + 3072 + tid * 16, 0, 0, 0, 0);
  if (warp < 4) {
    uint4 k4[4];
    #pragma unroll
    for (int i = 0; i < 4; i++) k4[i] = ld_relaxed4(g->key + warp * 512 + i * 128 + lane * 4);
    uint32_t bound = 0;
    #pragma unroll 1
    for (int c = 0; c < TOPC; c++) {
      uint32_t b = 0;
      #pragma unroll
      for (int i = 0; i < 4; i++) b = max(max(max(b, k4[i].x - bound), k4[i].y - bound), max(k4[i].z - bound, k4[i].w - bound));
      bound += __reduce_max_sync(0xffffffff, b);
      if (lane == 0) sts32(KEY + (warp * TOPC + c) * 4, bound);
    }
    bar_sync(1, 128);
    const uint32_t v = lds32(KEY + lane * 4);
    int n = 0;
    #pragma unroll 1
    for (int j = 0; j < 32; j++) n += __shfl_sync(0xffffffff, v, j) > v;
    if (n < TOPC) sts32(SEL + n * 4, v);
  }
  __syncthreads();
  #pragma unroll 1
  for (int i = tid; i < TOPC * 80; i += 384) {
    const int row = 0xffff - (lds32(SEL + (i & 7) * 4) & 0xffff);
    const uint32_t st = ldg32(g->stat + row), m2 = __byte_perm(st, 0, 0x1010);
    const float rsd = rcp_fast(bf_hi(st & 0x7fffffffu));
    const uint4 v = ldg_nc((const uint4*)(P.x + (size_t)row * DM) + (i >> 3));
    sts128(XS + i * 16, norm2(v.x, m2, rsd), norm2(v.y, m2, rsd), norm2(v.z, m2, rsd), norm2(v.w, m2, rsd));
  }
  proxy_fence();
  __syncthreads();
  TRACE(0, 2);
  uint32_t sl = 0, ph = 0;
  if (warp == 0) {
    #pragma unroll 1
    for (int job = 0; job < nj + 10; job++) {
      const bool up = job < nj;
      #pragma unroll 1
      for (int i = 0; i < (up ? 5 : nd); i++) {
        mbar_wait(BE + sl * 8, ph ^ 1);
        if (elect_one()) {
          mbar_expect_tx(BF + sl * 8, U);
          tma_load_2d(sb + sl * U, up ? ((job & 1) ? tmU : tmG) : tmD, BF + sl * 8, up ? f0 + (job >> 1) * 64 : (job - nj) * 64, (up ? 0 : f0) + i * 128);
        }
        if (++sl == 12) { sl = 0; ph ^= 1; }
      }
    }
  } else if ((warp >> 2) == 1) {
    float gs[4];
    #pragma unroll 1
    for (int job = 0; job < nj + 10; job++) {
      const bool up = job < nj;
      if (job == nj) { proxy_fence(); bar_sync(1, 128); }
      float ac[4][4], acc[4];
      uint32_t prev = 0;
      #pragma unroll 1
      for (int i = 0; i < (up ? 5 : nd); i++) {
        const uint64_t a = desc(sb, sl * 1024 + 0x10000), b = (uint64_t)(desc_lo(up ? XS : HS, 128) + i * 128) | (8ull << 32);
        mbar_wait(BF + sl * 8, ph);
        wg_fence();
        static_for<0, 8>([&](auto kc) { constexpr int k = decltype(kc)::v; wgmma_ss_ta<k * 128, k * 16>(ac[k & 3], a, b, k > 3 || i > 0); });
        wg_commit();
        wg_wait<1>();
        if (i && lane == 0) mbar_arrive(prev);
        prev = BE + sl * 8;
        if (++sl == 12) { sl = 0; ph ^= 1; }
      }
      wg_wait<0>();
      if (lane == 0) mbar_arrive(prev);
      #pragma unroll
      for (int e = 0; e < 4; e++) fence_regs(ac[e]);
      #pragma unroll
      for (int e = 0; e < 4; e++) acc[e] = (ac[0][e] + ac[1][e]) + (ac[2][e] + ac[3][e]);
      STALL(9);
      const int f = (warp & 3) * 16 + (lane >> 2), tk = (lane & 3) * 2;
      if (!up) {
        float* y = g->ypart + (m * DM + (job - nj) * 64 + f) * TOPC + tk;
        *(float2*)y = make_float2(acc[0], acc[1]); *(float2*)(y + 8 * TOPC) = make_float2(acc[2], acc[3]);
      } else {
        #pragma unroll
        for (int e = 0; e < 4; e++) {
          const float z = rbf(acc[e]);
          if (job & 1) asm volatile("st.shared.u16 [%0], %1;" :: "r"(HS + (job >> 1) * 1024 + ((f >> 3) + (e >> 1)) * 128 + (tk + (e & 1)) * 16 + (f & 7) * 2), "h"((uint16_t)pack_bf16(gs[e] * z, 0.f)) : "memory");
          gs[e] = rbf(z * sigmoid_f(z));
        }
      }
    }
  }
  __syncthreads();
  TRACE(0, 3);
  if (tid == 0) { flag_add_release(&g->cnt_mod.v); flag_wait(&g->cnt_mod.v, launch * 4, 50); }
  __syncthreads();
  #pragma unroll 1
  for (int i = tid; i < 2 * DM; i += 384) {
    const int t = 2 * m + (i & 1), col = i >> 1;
    const uint32_t key = lds32(SEL + t * 4);
    const float* yp = g->ypart + col * TOPC + t;
    const float y = rbf((__ldcg(yp) + __ldcg(yp + TOPC * DM)) + (__ldcg(yp + 2 * TOPC * DM) + __ldcg(yp + 3 * TOPC * DM)));
    const float rs = rbf(sigmoid_f(bf_hi((key >> 31) ? key & 0x7fffffffu : ~key)));
    const uint32_t xn = lds32(XS + (col >> 3) * 128 + t * 16 + (col & 6) * 2);
    const float z = rbf(((col & 1) ? bf_hi(xn) : bf_lo(xn)) + rbf(y * rs));
    g->gate[(size_t)(0xffff - (key & 0xffff)) * DM + col] = __float2bfloat16_rn(z * sigmoid_f(z));
  }
  __syncthreads();
  if (tid == 0) flag_add_release(&g->mod_done.v);
  TRACE(0, 4);
}

__global__ void __cluster_dims__(2, 1, 1) __launch_bounds__(384, 1) fused_kernel(const __grid_constant__ CUtensorMap tmX, const __grid_constant__ CUtensorMap tmW4,
    const __grid_constant__ CUtensorMap tmW3, const __grid_constant__ CUtensorMap tmW1,
    const __grid_constant__ CUtensorMap tmK, const __grid_constant__ CUtensorMap tmV, const __grid_constant__ CUtensorMap tmWO,
    const __grid_constant__ CUtensorMap tmG, const __grid_constant__ CUtensorMap tmU, const __grid_constant__ CUtensorMap tmD,
    const __grid_constant__ CUtensorMap tmGate, const __grid_constant__ Params P) {
  extern __shared__ __align__(1024) uint8_t smem_raw[];
  const uint32_t sb = smem_u32(smem_raw);
  const int tid = threadIdx.x, lane = tid & 31;
  const int rank = blockIdx.x & 1, cl = blockIdx.x >> 1;
  if (cl >= 64) {
    side_cta(P, &tmX, &tmW1, &tmG, &tmU, &tmD, sb, blockIdx.x & 3);
    return;
  }
  const int rr = ((cl - 36) * 37) >> 8, kk = cl - 36 - rr * 7, qp = sel_lt(cl, 4, PH, sel_lt(cl, 36, (cl - 4) & 7, kk + sel_lt(kk, PH, 0, 1)));
  const int hg = sel_lt(cl, 4, cl + 4, sel_lt(cl, 36, (cl - 4) >> 3, 4 + rr)), qt = qp * 2 + rank;
  const int warp = __shfl_sync(0xffffffff, tid >> 5, 0), wgi = warp >> 2;
  Scratch* const g = P.g;
  if (elect_one()) {
    #pragma unroll
    for (int i = 0; i < 4; i++) mbar_init(sb + SM_BAR + warp * 32 + i * 8, 1 << ((0x333444000000ull >> (4 * warp)) & 7));
    if (warp == 0) {
      mbar_expect_tx(sb + B_WF, 2 * U);
      tma_load_2d(sb + 2 * U, &tmX, sb + B_WF, 0, qt * 128);
      tma_load_3d(sb + SM_W, &tmW4, sb + B_WF, 0, 0, hg * 8);
      tma_load_3d(sb + SM_W + 8192, &tmW4, sb + B_WF, 0, 16, hg * 8);
    }
    asm volatile("fence.mbarrier_init.release.cluster;" ::: "memory");
  }
  __syncwarp();
  cluster_arrive();
  unsigned long long ticket = 0;
  if (tid == 64) asm volatile("atom.relaxed.gpu.global.add.u64 %0, [%1], 1;" : "=l"(ticket) : "l"(&g->ticket) : "memory");
  cluster_wait();
  if (warp == 0 && elect_one()) {
    #pragma unroll
    for (int i = 1; i < 6; i++) {
      mbar_expect_tx(sb + B_WF + i * 8, (i & 1) ? U : 2 * U);
      tma_load_3d_mc(sb + SM_W + i * U + rank * 8192, &tmW4, sb + B_WF + i * 8, 0, i * 32 + rank * 16, hg * 8);
      if (!(i & 1)) tma_load_2d(sb + (2 + i / 2) * U, &tmX, sb + B_WF + i * 8, i * 32, qt * 128);
    }
  }
  STALL(14);
  if (wgi == 0) {
    asm volatile("setmaxnreg.dec.sync.aligned.u32 56;");
    uint32_t w0 = 0;
    if (warp == 1 || warp == 2) {
      if (warp == 2 && lane < 12) sts128(sb + SM_EXT + 1024 + (lane >= 6 ? 1024 - 96 : 0) + lane * 16, 0, 0, 0, 0);
      __syncwarp();
      if (tid == 64) { sts32(sb + SM_ONE, 1); sts32(sb + SM_EP, launch_of(ticket)); mbar_arrive(sb + B_EP); }
      __syncwarp();
      mbar_pace(sb + B_WF, 0);
      TRACEO(1);
      auto warm = [&](int ps, int i0, int i1) {
        const uint32_t o = (((qt >> 2) * 4 + (lane & 3) + (lane >> 2) * 16) * (NH * DH) + hg * 512 + ps * 256 + (qt & 3) * 64) * 2;
        #pragma unroll 1
        for (int i = i0; i < i1; i++) {
          asm volatile("prefetch.global.L2 [%0];" :: "l"(at<char>(P.wq, o + i * 256 * (NH * DH))) : "memory");
          if (ps) __nanosleep(W1SL);
        }
      };
      if (elect_one()) l2_prefetch(P.x + (size_t)(qt * 128 + hg * 16 + warp * 8 - 6) * DM, 6 * DM * 2);
      if (warp == 1) warm(0, 1, 5);
      auto publish = [&](uint32_t w) { if (!(lane & 12)) st_relaxed(at<uint32_t>(g->stat, (qt * 128 + hg * 16 + (warp - 1) * 8 + (lane & 3) * 2 + (lane >> 4)) * 4), w ^ (lds32(sb + SM_EP) << 31)); };
      mbar_wait(sb + B_EP, 0);
      publish(0x80000000u);
      const int r0 = qt * 128 + hg * 16 + (warp - 1) * 8 + (lane >> 4);
      const uint32_t e = r0 * DM * 2 + (lane & 15) * 16;
      uint4 vn[5];
      #pragma unroll
      for (int i = 0; i < 5; i++) vn[i] = ldg_nc(at<uint4>(P.x, e) + i * 16);
      #pragma unroll 1
      for (int it = 0; it < 4; it++) {
        uint4 v[5];
        #pragma unroll
        for (int i = 0; i < 5; i++) { v[i] = vn[i]; if (it < 3) vn[i] = ldg_nc(at<uint4>(P.x, e + (it + 1) * 2560) + i * 16); }
        const float x0 = bf_lo(__shfl_sync(0xffffffff, v[0].x, lane & 16));
        float m1 = 0.f, s1 = 0.f;
        #pragma unroll
        for (int i = 0; i < 5; i++) {
          const uint32_t vw[4] = {v[i].x, v[i].y, v[i].z, v[i].w};
          #pragma unroll
          for (int k = 0; k < 4; k++) { const float d0 = bf_lo(vw[k]) - x0, d1 = bf_hi(vw[k]) - x0; m1 += d0 + d1; s1 = fmaf(d0, d0, fmaf(d1, d1, s1)); }
        }
        #pragma unroll
        for (int o = 8; o; o >>= 1) { m1 += __shfl_xor_sync(0xffffffff, m1, o); s1 += __shfl_xor_sync(0xffffffff, s1, o); }
        const float md = m1 * (1.f / DM), var = fmaxf(fmaf(-md, md, s1 * (1.f / DM)), 0.f);
        if ((lane & 15) == it) w0 = pack_bf16(x0 + md, sqrt_approx(rbf(rbf(var) + 1e-5f)));
      }
      STALL(5);
      publish(w0 & 0x7fffffffu);
      TRACE1(2, 8);
      if (warp == 1 && W1SL) warm(1, 0, 5);
    }
        if (warp >= 2) {
      const int ps = 3 - warp;
      {
        const uint4* src = at<uint4>(P.wq, (((qt >> 2) * 4 + (lane >> 3)) * (NH * DH) + hg * 512 + ps * 256 + (qt & 3) * 64 + (lane & 7) * 8) * 2);
        const uint32_t mine = ((hg * 2 + ps) * 256 + qt * 16 + (lane & 7) * 2 + (lane >> 4)) * 16;
        float cs[8];
        #pragma unroll
        for (int e = 0; e < 8; e++) cs[e] = 0.f;
        #pragma unroll 1
        for (int b = 0; b < 40 / CSB; b++, src += CSB * 16 * 512) {
          uint4 w[CSB];
          #pragma unroll
          for (int i = 0; i < CSB; i++) w[i] = ldg_nc(src + i * 16 * 512);
          #pragma unroll
          for (int i = 0; i < CSB; i++) add8(cs, w[i]);
          if (b == 0) {
            mbar_wait(sb + B_EP, 0);
            if (!(lane & 8)) st_tagged(at<uint4>(g->cs, mine), ~lds32(sb + SM_EP) & 1, 0, 0, 0);
          }
        }
        #pragma unroll
        for (int e = 0; e < 4; e++) {
          cs[e] = ((lane & 16) ? cs[e + 4] : cs[e]) + __shfl_xor_sync(0xffffffff, (lane & 16) ? cs[e] : cs[e + 4], 16);
          cs[e] += __shfl_xor_sync(0xffffffff, cs[e], 8);
        }
        STALL(6);
        mbar_wait(sb + B_EP, 0);
        const uint32_t tm = 0u - (lds32(sb + SM_EP) & 1);
        const uint4* const gc = at<uint4>(g->cs, ((hg * 2 + ps) * 256 + lane) * 16);
        if (!(lane & 8)) st_tagged(at<uint4>(g->cs, mine), (__float_as_uint(cs[0]) & ~1u) | (tm & 1), __float_as_uint(cs[1]), __float_as_uint(cs[2]), __float_as_uint(cs[3]));

        uint4 v[9];
        int it = 0;
        uint32_t miss;
        do {
          #pragma unroll
          for (int i = 0; i < 8; i++) v[i] = ld_tagged(gc + i * 32);
          v[8] = ld_relaxed4(at<uint4>(g->stat, qt * 512 + lane * 16));
          miss = (tag_miss(v[8].x, v[8].y, tm) | tag_miss(v[8].z, v[8].w, tm)) >> 31;
          #pragma unroll
          for (int i = 0; i < 8; i += 2) miss |= tag_miss(v[i].x, v[i+1].x, tm);
        } while (__any_sync(0xffffffff, miss & 1) && ++it < MAXPOLL);
        #pragma unroll
        for (int i = 0; i < 2; i++) {
          auto sum = [](uint32_t a, uint32_t b, uint32_t c, uint32_t d) { return (__uint_as_float(a) + __uint_as_float(b)) + (__uint_as_float(c) + __uint_as_float(d)); };
          const float c0 = sum(v[i].x, v[i+2].x, v[i+4].x, v[i+6].x), c1 = sum(v[i].y, v[i+2].y, v[i+4].y, v[i+6].y);
          const float c2 = sum(v[i].z, v[i+2].z, v[i+4].z, v[i+6].z), c3 = sum(v[i].w, v[i+2].w, v[i+4].w, v[i+6].w);
          const uint32_t h0 = pack_bf16(c0, c1), h1 = pack_bf16(c2, c3), a = sb + SM_EXT + ps * 1024 + i * 512 + (lane >> 1) * 32 + (lane & 1) * 8;
          asm volatile("st.shared.v2.u32 [%0], {%1,%2};" :: "r"(a), "r"(h0), "r"(h1) : "memory");
          asm volatile("st.shared.v2.u32 [%0], {%1,%2};" :: "r"(a + 16), "r"(pack_bf16(c0 - bf_lo(h0), c1 - bf_hi(h0))), "r"(pack_bf16(c2 - bf_lo(h1), c3 - bf_hi(h1))) : "memory");
        }
        sts128(sb + SM_STAT + lane * 16, v[8].x & 0x7fffffffu, v[8].y & 0x7fffffffu, v[8].z & 0x7fffffffu, v[8].w & 0x7fffffffu);
        proxy_fence();
        __syncwarp();
        if (lane == 0) mbar_arrive(sb + B_EXT + ps * 8);
        TRACE1(2, 6 + ps);
        if (elect_one()) l2_prefetch(at<char>(ps ? P.v : P.k, ((hg * 4 + 1) * S_LEN + qt * (16 + 8 * KVPF)) * DH * 2), 4096 + 2048 * KVPF);
      }
    }
    if (warp == 1 || warp == 2) {
      int j = 0;
      const int r0 = qt * 128 + hg * 16 + (warp - 1) * 8 + (lane >> 4);
      uint32_t e = r0 * DM * 2 + (lane & 15) * 16;
      uint4 xn = ldg_nc(at<uint4>(P.x, e)), wn = ldg_nc(at<uint4>(P.wr, (lane & 15) * 16));
      #pragma unroll 1
      for (int it = 0; it < 4; it++) {
        const uint32_t st = __shfl_sync(0xffffffff, w0, (lane & 16) + it), m2 = __byte_perm(st, 0, 0x1010);
        const float rsd = rcp_fast(bf_hi(st));
        float a = 0.f;
        #pragma unroll 1
        for (int i = 0; i < 5; i++) {
          #pragma unroll 1
          do { mbar_pace(sb + B_KE + (j & 1) * 8, (j >> 1) & 1); j++; } while (j < 3 || (j >= 15 && j < 20));
          STALL(8);
          uint32_t z[4] = {xn.x, xn.y, xn.z, xn.w};
          const uint32_t ww[4] = {wn.x, wn.y, wn.z, wn.w}, en = e + (i < 4 ? 256 : (it < 3 ? 1536 : 0));
          xn = ldg_nc(at<uint4>(P.x, en)); wn = ldg_nc(at<uint4>(P.wr, (i < 4 ? i * 256 + 256 : 0) + (lane & 15) * 16));
          #pragma unroll
          for (int k = 0; k < 4; k++) {
            const uint32_t n = norm2(z[k], m2, rsd);
            const float lo = bf_lo(n), hi = bf_hi(n);
            a = fmaf(lo, bf_lo(ww[k]), fmaf(hi, bf_hi(ww[k]), a));
            z[k] = pack_bf16(lo * sigmoid_f(lo), hi * sigmoid_f(hi));
          }
          stg128(at<uint4>(g->gate, e), make_uint4(z[0], z[1], z[2], z[3]));
          e = en;
        }
        #pragma unroll
        for (int o = 8; o; o >>= 1) a += __shfl_xor_sync(0xffffffff, a, o);
        uint32_t u = pack_bf16(a, 0.f);
        if (u == 0x8000u) u = 0;
        u = (u & 0x8000u) ? (~u & 0xffffu) : (u | 0x8000u);
        if (!(lane & 15)) st_relaxed(at<uint32_t>(g->key, (r0 + it * 2) * 4), (u << 16) | (uint32_t)(0xffff - r0 - it * 2));
      }
      __syncwarp();
      if (lane == 0) flag_add_release(&g->cnt_gate.v);
      TRACE1(2, 9);
    }
    if (warp == 0) {
      const int row0 = hg * 4 * S_LEN;
      uint32_t s = 0, ph = 0;
      #pragma unroll 1
      for (int c = 3; c < 20; c++) {
        const int k = (c < 10 ? c : (c < 18 ? c - 8 : c - 18)) * 64, cb = hg * 8 + (c < 10 ? 0 : 4);
        const CUtensorMap* const tm = c < 10 ? &tmW4 : &tmW3;
        const uint32_t wb = c < 10 ? U : 12288;
        const bool wx = c < 10 || (c >= XRC && c < XRC + 2);
        const uint32_t bar = sb + B_WF + s * 8, dst = sb + SM_W + rank * 8192 + s * U;
        mbar_wait(bar + (B_WE - B_WF), ph);
        if (elect_one()) {
          mbar_expect_tx(bar, wx ? wb + U : wb);
          tma_load_3d_mc(dst, tm, bar, 0, k + rank * 16, cb);
          if (wx) tma_load_2d(sb + (c < 10 ? (c + 2) & 7 : c + 4 - XRC) * U, &tmX, bar, c < 10 ? k : (c - XRC) * 64, qt * 128);
        }
        mbar_wait(bar + (B_WE - B_WF) + 8, ph);
        if (elect_one()) {
          mbar_expect_tx(bar + 8, wb);
          tma_load_3d_mc(dst + U, tm, bar + 8, 0, k + 32 + rank * 16, cb);
        }
        s += 2;
        if (s == 6) { s = 0; ph ^= 1; }
      }
      #pragma unroll 1
      for (int i = 0; i < 128; i++) {
        const int isv = i < 5 ? (i >> 1) & 1 : (i < 127 ? ~i & 1 : 1), j = i < 4 ? i & 1 : (i + 1 - 2 * isv) >> 1;
        const uint32_t b = isv * 16 + (j & 1) * 8;
        STALL(11);
        if (i) mbar_wait(sb + (i < 4 ? B_WE + ((0x3150 >> (4 * i)) & 7) * 8 : B_KE + b), i < 4 ? i < 2 : (~j >> 1) & 1);
        if (elect_one()) {
          mbar_expect_tx(sb + B_KF + b, 2 * U);
          tma_load_2d_mc(sb + (isv ? SM_V + (j & 1) * 2 * U : (j & 1) * SM_K1) + rank * U, isv ? &tmV : &tmK, sb + B_KF + b, rank * 64, row0 + kv_tile(j) * 128);
          if (GSYNC && i == 125) mbar_arrive(sb + B_ANN);
        }
        if (i == 4) TRACEO(3);
      }
      s = 0; ph = 1;
      #pragma unroll 1
      for (int n = 0; n < (X_SKIP(qp) ? 2 : 40); n++) {
        const int st = n < 5 ? (n == 1) : n >> 2, h = n < 5 ? max(n - 1, 0) : n & 3;
        const int u = st < 2 ? 8 + st : ((hg + st - 1) & 7);
        STALL(12);
        mbar_wait(sb + (n < 6 ? B_KE + (n < 4 ? n >> 1 : 3) * 8 : B_CE + s * 8), ph);
        if (elect_one()) {
          mbar_expect_tx(sb + B_CF + s * 8, U);
          tma_load_2d_mc(sb + c_slot(s) * U + rank * 8192, &tmWO, sb + B_CF + s * 8, u * 64, hg * 512 + ((0x3120 >> (4 * h)) & 3) * 128 + rank * 64);
        }
        if (n == 3) TRACEO(4);
        if (++s == 6) { s = 0; ph ^= 1; }
      }
      mbar_wait(sb + B_GATE, 0);
      asm volatile("fence.proxy.async.global;" ::: "memory");
      #pragma unroll 1
      for (int n = 0; n < (X_SKIP(qp) ? 0 : 2); n++) {
        mbar_wait(sb + B_CE + 32 + n * 8, 1);
        if (elect_one()) {
          mbar_expect_tx(sb + B_CF + 32 + n * 8, U);
          tma_load_2d(sb + (10 + n) * U, n ? &tmGate : &tmX, sb + B_CF + 32 + n * 8, hg * 64, qt * 128);
        }
      }
      if (!X_SKIP(qp)) {
        const uint4* const last = g->part + (size_t)((qt * 8 + hg) * 9 + 8) * 1024;
        mbar_wait(sb + B_CE + P8, 0);
        if (elect_one()) {
          mbar_expect_tx(sb + B_CF + 8, U);
          bulk_load(sb + U, last, U, sb + B_CF + 8);
        }
      }
    } else if (warp == 2) {
      #pragma unroll 1
      for (int h = 0; h < 4; h++) {
        mbar_wait(sb + B_OS + h * 8, 0);
        STALL(13);
        #pragma unroll 1
        for (int i = 0; i < (h < 3 ? 16 : 0); i++) {
          uint32_t z = 0;
          #pragma unroll
          for (int k = 0; k < 4; k++) { const uint4 v = lds128(sb + qo_slot(h) + i * 2048 + k * 512 + lane * 16); z = taint(taint(z, v.x, v.y), v.z, v.w); }
          flag_if(sb + SM_BAD + (i & 7) * 4 + h, tainted(z));
        }
        if (GSYNC && h == 2) {
          const uint32_t launch = lds32(sb + SM_EP);
          uint32_t* const mine = at<uint32_t>(g->near, (qt * 8 + hg) * 32 + (lane & 7) * 4);
          st_relaxed(mine, launch - 1);
          mbar_wait(sb + B_ANN, 0);
          mbar_wait(sb + B_KE, 1);
          st_relaxed(mine, launch);
          #pragma unroll 1
          for (int it = 0; __any_sync(0xffffffff, ldg32(at<uint32_t>(g->near, qp * 512 + lane * 16)) != launch) && it < MAXPOLL; it++) {}
        }
        __syncwarp();
        if (h >= 2) { proxy_fence(); if (elect_one()) mbar_arrive(sb + B_OF); }
        __syncwarp();
      }
    } else if (!elect_one()) {
    } else if (warp == 1) {
      mbar_wait(sb + B_OS + 8, 0);
      flag_wait(at<unsigned>(g->q3_done, (hg >> 1) * 128), lds32(sb + SM_EP) * 32 + qt * 2 - 30);
      asm volatile("fence.proxy.async.global;" ::: "memory");
      mbar_expect_tx(sb + B_Q3, U);
      bulk_load(sb + 5 * U, g->q3 + (qt * 8 + hg) * 1024, U, sb + B_Q3);
      flag_wait(&g->mod_done.v, lds32(sb + SM_EP) * 4);
      mbar_arrive(sb + B_GATE);
    } else {
      #pragma unroll 1
      for (int j = 2; j < 64 - KVPF; j++) {
        mbar_pace(sb + B_KE + (j & 1) * 8, (~j >> 1) & 1);
        const size_t o = (size_t)(hg * 4 * S_LEN + kv_tile(j + KVPF) * 128 + qt * 8) * DH;
        if (KVPF) { l2_prefetch(P.k + o, 2048); l2_prefetch(P.v + o, 2048); }
        if (j >= 40 && j < 56) l2_prefetch(P.wo + (size_t)(hg * 512 + qt * 32 + (j - 40) * 2) * DM, 2 * DM * 2);
        if (j >= 56 && j < 60) l2_prefetch(((j & 1) ? P.x : g->gate) + (size_t)(qt * 128 + hg * 16 + (j & 2) * 4) * DM, 8 * DM * 2);
      }
    }
    __syncwarp();
    if ((warp == 1 || warp == 2) && !X_SKIP(qp)) {
      mbar_wait(sb + B_GATE, 0);
      #pragma unroll 1
      for (int i = 0; i < 4; i++) {
        const int r = warp * 8 - 8 + (i & 1) * 4 + (lane >> 3);
        const uint32_t e = ((qt * 128 + hg * 16 + r) * DM + (8 + (i >> 1)) * 64 + (lane & 7) * 8) * 2;
        if (!(i & 1)) bar_sync(8, 192);
        STALL(10);
        const uint4 xr = ldg_nc(at<uint4>(P.x, e)), gr = ld_relaxed4(at<uint4>(g->gate, e)), sv = lds128(sb + SM_BAR + 1024 + r * 128 + (((lane ^ r) & 7) << 4));
        stg128(at<uint4>(P.out, e), gated(xr, sv, gr));
        if (i == 1) bar_arrive(9, 192);
      }
    }
    cluster_arrive();
    cluster_wait();
  } else {
    const int wg = wgi - 1, t = tid & 127, cw = warp - 4;
    asm volatile("setmaxnreg.inc.sync.aligned.u32 224;");
    uint32_t q[32], p[32];
    float s[64], o[64], l[2] = {0.f, 0.f};
    const uint32_t rb = __shfl_sync(0xffffffff, map_cta(sb, lane & 1), lane), wr = sb + cw * 2048, qa = __shfl_sync(0xffffffff, wr + lane * 16, lane);
    {
      uint32_t sl = 0, ph = 0, rprev = 0;
      float acc0[128], acc1[96];
      auto pair = [&](auto& acc, int pass, int i, auto mid) {
        const uint64_t a = desc(sb, ((i + 2 + 2 * pass) & 7) * 1024 + wg * 512 + doff(0, 16)), b = desc(sb, sl * 128 + doff(SM_W, 2048));
        STALL(4);
        mbar_wait(sb + B_WF + sl, ph);
        if (i == 0) TRACE(wg, 1 + pass);
        TRACEF(1, wg, 40 + pass * 20 + 2 * i);
        wg_fence();
        wgmma_ss_tb<0, 0>(acc, a, b, i > 0);
        wgmma_ss_tb<2, 512>(acc, a, b, 1);
        wg_commit();
        mbar_wait(sb + B_WF + 8 + sl, ph);
        wg_wait<1>();
        if (i > 0) release2(rprev, lane);
        TRACEF(1, wg, 41 + pass * 20 + 2 * i);
        wg_fence();
        wgmma_ss_tb<4, 1024>(acc, a, b, 1);
        wgmma_ss_tb<6, 1536>(acc, a, b, 1);
        wg_commit();
        mid();
        rprev = rb + B_WE + 8 + sl;
        sl += 16;
        if (sl == 48) { sl = 0; ph ^= 1; }
        wg_wait<1>();
        release2(rprev - 8, lane);
      };
      if (wg == 1) bar_arrive(1, 256);
      #pragma unroll 1
      for (int i = 0; i < 10; i++) {
        if (i == SKEW0 / 2) bar_sync(1 + wg, 256);
        pair(acc0, 0, i, [] {});
      }
      mbar_wait(sb + B_EXT, 0);
      const uint32_t st0 = lds32(sb + SM_STAT + (cw * 16 + (lane >> 2)) * 4), st1 = lds32(sb + SM_STAT + (cw * 16 + 8 + (lane >> 2)) * 4);
      const uint32_t a0 = (lane & 3) ? 0u : (__byte_perm(st0, 0, 0x1010) ^ 0x80008000u), a1 = (lane & 3) ? 0u : (__byte_perm(st1, 0, 0x1010) ^ 0x80008000u);
      wg_fence();
      wgmma_rs_tb<0>(acc0, a0, a1, 0u, 0u, (uint64_t)desc_lo(sb + SM_EXT, 0) | ((uint64_t)2 << 32), 1);
      wg_commit();
      bar_arrive(1 + (wg ^ 1), 256);
      float rs[2] = {rcp_fast(bf_hi(st0)) * SCALE_LOG2E, rcp_fast(bf_hi(st1)) * SCALE_LOG2E};
      wg_wait<0>();
      fence_regs(acc0);
      release2(rprev, lane);
      #pragma unroll
      for (int i = 0; i < 32; i++) q[i] = pack_bf16(acc0[64+2*i] * rs[i & 1], acc0[64+2*i+1] * rs[i & 1]);
      fence_regs(q);
      pair(acc1, 1, 0, [&] {
        bar_sync(4 + wg, 128);
        const uint32_t one = lds32(sb + SM_ONE);
        rs[0] = __uint_as_float(__float_as_uint(rs[0]) * one); rs[1] = __uint_as_float(__float_as_uint(rs[1]) * one);
        #pragma unroll
        for (int i = 0; i < 32; i++) p[i] = pack_bf16(acc0[2*i] * rs[i & 1], acc0[2*i+1] * rs[i & 1]);
        fence_regs(p);
      });
      #pragma unroll 1
      for (int i = 1; i < 8; i++) pair(acc1, 1, i, [&] {
        #pragma unroll
        for (int e = 0; e < 8; e++) sts128_if(i == 4 + e / 2, qa + qo_slot(0) + (e >> 2) * U + (e & 3) * 512, p[4*e], p[4*e+1], p[4*e+2], p[4*e+3]);
      });
      mbar_wait(sb + B_WF, 0);
      mbar_wait(sb + B_WF + 8, 0);
      if (wg) { wg_wait<0>(); release2(rprev, lane); }
      bar_sync(1 + wg, 256);
      const uint64_t da = desc(sb, wg * 512 + 7), db = desc(sb, 7);
      static_for<0, 2>([&](auto ic) { constexpr int i = decltype(ic)::v;
        wg_fence();
        static_for<0, 4>([&](auto kc) { constexpr int k = decltype(kc)::v;
          wgmma_ss_tb<doff((4 + i) * U, 16) - 7 + k * 2, doff(SM_W + i * 2 * U, 2048) - 7 + k * 512>(acc1, da, db, 1); });
        if (i == 0) {
          wg_commit();
          mbar_wait(sb + B_WF + 16, 0);
          mbar_wait(sb + B_WF + 24, 0);
          mbar_wait(sb + B_EXT + 8, 0);
          wg_wait<1>();
          if (!wg) release2(rprev, lane);
        }
      });
      wgmma_rs_tb<0>(acc1, a0, a1, 0u, 0u, (uint64_t)desc_lo(sb + SM_EXT + 1024, 0) | ((uint64_t)2 << 32), 1);
      wg_commit();
      mbar_wait(sb + B_KF, 0);
      wg_wait<1>();
      release2(rb + B_WE + 8, lane);
      TRACE(wg, 3);
      mma_qk<0, 2>(s, q, desc(sb, 2));
      bar_arrive(1 + (wg ^ 1), 256);
      wg_wait<1>();
      fence_regs(acc1);
      release2(rb + B_WE + 24, lane);
      #pragma unroll
      for (int e = 0; e < 12; e++)
        sts128(qa + SM_QO + (e >> 2) * U + (e & 3) * 512, pack_bf16(acc1[8*e] * rs[0], acc1[8*e+1] * rs[0]), pack_bf16(acc1[8*e+2] * rs[1], acc1[8*e+3] * rs[1]),
               pack_bf16(acc1[8*e+4] * rs[0], acc1[8*e+5] * rs[0]), pack_bf16(acc1[8*e+6] * rs[1], acc1[8*e+7] * rs[1]));
      wg_wait<0>();
      fence_regs(s);
      release2(rb + B_KE, lane);
      exp_rows<0, 64>(s, l);
      #pragma unroll
      for (int i = 0; i < 32; i++) p[i] = pack_bf16(s[2*i], s[2*i+1]);
    }
    unsigned tz[3] = {0, 0, 0};
    bool ready = false;
    #pragma unroll 1
    for (int j = 1; ; j += 2) {
      int ph = 0;
      #pragma unroll 1
      do {
        attn_step<1, false>(sb, rb, wr, qa, wg, lane, j, ph, s, o, p, q, l, ready, g, tz);
        ph ^= 1; j += 2;
        if (wg < 2) attn_step<0, false>(sb, rb, wr, qa, wg, lane, j - 1, ph, s, o, p, q, l, ready, g, tz);
      } while ((j & 15) != 15);
      if (j == 47) mbar_wait(sb + B_Q3, 0);
      attn_step<1, true>(sb, rb, wr, qa, wg, lane, j, 1, s, o, p, q, l, ready, g, tz);
      if (j == 63) break;
      if (wg < 2) attn_step<0, true>(sb, rb, wr, qa, wg, lane, j + 1, 0, s, o, p, q, l, ready, g, tz);
    }
    mbar_wait(sb + B_OF, 0);
    mbar_wait(sb + B_CF + wg * 8, 0);
    mbar_wait(sb + B_KF + 24, 1);
    bar_sync(1 + wg, 256);
    TRACE(wg, 4);
    mma_pv<SM_V + 2 * U, 2>(o, p, desc(sb, 2), true);
    mma_c<3>(s, sb, wg, 0, 0);
    bar_arrive(1 + (wg ^ 1), 256);
    mbar_wait(sb + B_KE + 16, 1);
    const uint32_t tag = lds32(sb + SM_EP) & 1;
    row_scale(l[0], l[1], lds32(sb + SM_ONE), sb + SM_BAD + cw * 4 + 3);
    __syncwarp();
    const uint32_t flags = lds32(sb + SM_BAD + (lane & 7) * 4);
    wg_wait<1>();
    fence_regs(o); fence_regs(p);
    release2(rb + B_KE + 24, lane);
    const uint32_t over = tainted(store_o<true>(o_addr(wr, lane) + SM_V, o, l[0], l[1]));
    if (__builtin_expect(bar_any(4 + wg, 128, __any_sync(0xffffffff, flags | over)), 0)) {
      const uint32_t bad = __shfl_sync(0xffffffff, flags, cw) | (__any_sync(0xffffffff, over) << 24);
      wg_wait<0>();
      fence_regs(s);
      redo_heads(P, sb, bad, qt * 128 + cw * 16, hg * 4);
      #pragma unroll
      for (int i = 0; i < 64; i++) s[i] = 0.f;
      __syncwarp();
      if (lane == 0) mbar_arrive(sb + B_OS + 24);
      mbar_wait(sb + B_OF, 1);
      mma_c<4>(s, sb, wg, 0, 0);
    } else if (lane == 0) mbar_arrive(sb + B_OS + 24);
    wg_wait<0>();
    release2(rb + B_CE + wg * 8, lane);
    if (X_SKIP(qp)) { cluster_arrive(); } else {
      const uint4* in = at<uint4>(g->part, (((qt * 8 + hg) * 9 + wg) * 1024 + t) * 16);
      const uint32_t tm = 0u - tag;
      uint4 v[8];
      auto fetch = [&](auto half, const uint4* from) {
        #pragma unroll
        for (int i = decltype(half)::v * 4; i < decltype(half)::v * 4 + 4; i++) reload(v[i], from + i * 128);
      };
      auto verify = [&](auto half, const uint4* from) { verify4(v + decltype(half)::v * 4, from + decltype(half)::v * 512, tm); };
      int sp = 6, sl = 2 + 3 * wg, ph = 0;
      auto quarter = [&](auto site, int h, int arrive_bar) {
        STALL(2);
        mbar_wait(sb + B_CF + sl * 8, ph);
        if (h == 0) bar_sync(1 + wg, 256);
        mma_c<decltype(site)::v>(s, sb, sl, h, arrive_bar);
        if (h) { wg_wait<1>(); release2(rb + B_CE + sp * 8, lane); }
        sp = sl;
        if (++sl == 6) { sl = 0; ph ^= 1; }
      };
      auto send = [&](int st) {
        uint4* dst = at<uint4>(g->part, ((qt * 72 + st) * 1024 + (st < 2 ? hg * 128 : ((hg + st - 1) & 7) * 9216) + t) * 16);
        const uint32_t ds = st < 2 ? 9 * U : 2048;
        wg_wait<0>();
        fence_regs(s);
        TRACEF(4, wg, 106 + (st >> 1));
        release2(rb + B_CE + sp * 8, lane);
        STALL(3);
        #pragma unroll
        for (int i = 0; i < 8; i++, dst = at<uint4>(dst, ds))
          st_tagged(dst, (pack_bf16(s[8*i], s[8*i+1]) & ~1u) | tag, pack_bf16(s[8*i+2], s[8*i+3]), pack_bf16(s[8*i+4], s[8*i+5]), pack_bf16(s[8*i+6], s[8*i+7]));
        sl += st ? 4 : 3;
        if (sl >= 6) { sl -= 6; ph ^= 1; }
      };
      const uint32_t ta = ((lane >> 4) * 8 + (lane & 7)) * 128 + ((((cw & 3) * 2 + ((lane >> 3) & 1)) ^ (lane & 7)) << 4), ra = (t >> 3) * 128 + (((t & 7) ^ ((t >> 3) & 7)) << 4);
      float T[64];
      #pragma unroll
      for (int i = 0; i < 8; i++) asm volatile("mov.b64 {%0,%1}, 0;\nmov.b64 {%2,%3}, 0;" : "=r"(v[i].x), "=r"(v[i].y), "=r"(v[i].z), "=r"(v[i].w));
      TRACEF(4, wg, 112);
      bar_sync(1 + wg, 256);
      auto take = [&](auto half, int back, bool more) {
        verify(half, in - back * 1024);
        const uint4* const nx = in - (back - 1) * 1024;
        #pragma unroll
        for (int i = decltype(half)::v * 4; i < decltype(half)::v * 4 + 4; i++) { add8(T + 8 * i, v[i]); reload(v[i], nx + i * 128, more); }
      };
      #pragma unroll 1
      for (int st = wg; ; st += 2, in += 2048) {
        TRACEF(4, wg, 100 + (st >> 1));
        const bool odd5 = (st & 1) && st >= 5;
        quarter(IC<5>{}, 1, 0);
        if (odd5) take(IC<0>{}, 3, true);
        else if (st == 2) fetch(IC<0>{}, in - 2048);
        quarter(IC<6>{}, 2, 0);
        if (odd5) take(IC<1>{}, 3, true);
        else if (st == 2) fetch(IC<1>{}, in - 2048);
        if (st < 2) mbar_wait(sb + B_OF, 1);
        quarter(IC<7>{}, 3, st < 9 ? 2 - wg : 0);
        if (st < 9) send(st);
        if (odd5) {
          take(IC<0>{}, 2, st < 9);
          if (st == 9) bar_arrive(1, 256);
          take(IC<1>{}, 2, st < 9);
        }
        else if (st == 3) {
          fetch(IC<0>{}, in - 1024); fetch(IC<1>{}, in - 1024);
          #pragma unroll
          for (int i = 0; i < 64; i++) asm volatile("mov.b32 %0, 0;" : "+f"(T[i]));
        } else if (st == 2 || st == 4) {
          const uint4* const rows = at<uint4>(in - 3072, st == 2 ? U : 0);
          float a[8];
          #pragma unroll
          for (int i = 0; i < 8; i++) a[i] = 0.f;
          static_for<0, 2>([&](auto hf) {
            verify(hf, rows);
            #pragma unroll
            for (int i = decltype(hf)::v * 4; i < decltype(hf)::v * 4 + 4; i++) { add8(a, v[i]); reload(v[i], rows + 1024 + i * 128, st == 2); }
          });
          if (st == 4) bar_sync(9, 192);
          stsm4t(sb + SM_BAR + 1024 + ta, pack_bf16(a[0], a[1]), pack_bf16(a[2], a[3]), pack_bf16(a[4], a[5]), pack_bf16(a[6], a[7]));
          bar_arrive(8, 192);
        }
        if (st >= 8) break;
        quarter(IC<8>{}, 0, 0);
      }
      cluster_arrive();
      TRACEF(4, wg, 113);
      wg_wait<0>();
      fence_regs(s);
      if (wg == 0) {
        mbar_wait(sb + B_CF + 32, 0);
        mbar_wait(sb + B_CF + 40, 0);
        uint4* const op = at<uint4>(P.out, ((qt * 128 + (t >> 3)) * DM + hg * 64 + (t & 7) * 8) * 2);
        bar_sync(1, 256);
        uint4 xv[8];
        #pragma unroll
        for (int i = 0; i < 8; i++) { xv[i] = lds128(sb + 10 * U + i * 2048 + ra); v[i] = lds128(sb + 11 * U + i * 2048 + ra); }
        #pragma unroll
        for (int i = 0; i < 8; i++) {
          if (!(i & 3)) bar_sync(12 + (i >> 2), 256);
          stg128(op + i * 2 * DM, gated(xv[i], lds128(sb + i * 2048 + ra), v[i]));
        }
      } else {
        TRACEF(4, wg, 110);
        mbar_wait(sb + B_CF + 8, 1);
        #pragma unroll
        for (int i = 0; i < 8; i++) v[i] = lds128(sb + U + i * 2048 + t * 16);
        #pragma unroll
        for (int i = 0; i < 64; i++) T[i] += s[i];
        fence_regs(T);
        static_for<0, 8>([&](auto ic) { constexpr int i = decltype(ic)::v;
          if (!(i & 3)) verify(IC<i / 4>{}, in - 1024);
          add8(T + 8 * i, v[i]);
          stsm4t(sb + i * 2048 + ta, pack_bf16(T[8*i], T[8*i+1]), pack_bf16(T[8*i+2], T[8*i+3]), pack_bf16(T[8*i+4], T[8*i+5]), pack_bf16(T[8*i+6], T[8*i+7]));
          if ((i & 3) == 3) bar_arrive(12 + (i >> 2), 256);
        });
      }
    }
    TRACE(wg, 6);
    cluster_wait();
  }
}

typedef CUresult (*EncodeFn)(CUtensorMap*, CUtensorMapDataType, cuuint32_t, void*, const cuuint64_t*, const cuuint64_t*, const cuuint32_t*, const cuuint32_t*,
                             CUtensorMapInterleave, CUtensorMapSwizzle, CUtensorMapL2promotion, CUtensorMapFloatOOBfill);
void make_map(EncodeFn enc, CUtensorMap* tm, const void* ptr, uint64_t inner, uint64_t outer, uint32_t box_outer, uint32_t blocks = 0) {
  cuuint64_t dims[3] = {blocks ? 64 : inner, outer, inner / 64}; cuuint64_t strides[2] = {inner * 2, 128};
  cuuint32_t box[3] = {64, box_outer, blocks}; cuuint32_t es[3] = {1, 1, 1};
  enc(tm, CU_TENSOR_MAP_DATA_TYPE_BFLOAT16, blocks ? 3 : 2, const_cast<void*>(ptr), dims, strides, box, es, CU_TENSOR_MAP_INTERLEAVE_NONE,
      CU_TENSOR_MAP_SWIZZLE_128B, CU_TENSOR_MAP_L2_PROMOTION_L2_256B, CU_TENSOR_MAP_FLOAT_OOB_FILL_NONE);
}

}

extern "C" void kernel_launch(void* const* d_in, const int* in_sizes, int n_in, void* d_out, int out_size) {
  (void)in_sizes; (void)n_in; (void)out_size;
  Params P;
  P.x = (const __nv_bfloat16*)d_in[0]; P.k = (const __nv_bfloat16*)d_in[1]; P.v = (const __nv_bfloat16*)d_in[2];
  P.wq = (const __nv_bfloat16*)d_in[3]; P.wo = (const __nv_bfloat16*)d_in[4]; P.wr = (const __nv_bfloat16*)d_in[6];
  P.out = (__nv_bfloat16*)d_out;
  cudaGetSymbolAddress((void**)&P.g, g_s);
  void* fn = nullptr; cudaDriverEntryPointQueryResult st;
  cudaGetDriverEntryPoint("cuTensorMapEncodeTiled", &fn, cudaEnableDefault, &st);
  EncodeFn enc = (EncodeFn)fn;
  CUtensorMap tmX, tmW4, tmW3, tmW1, tmK, tmV, tmWO, tmG, tmU, tmD, tmGate;
  make_map(enc, &tmGate, P.g->gate, DM, S_LEN, 128);
  make_map(enc, &tmX, P.x, DM, S_LEN, 128);
  make_map(enc, &tmW4, P.wq, NH * DH, DM, 16, 4);
  make_map(enc, &tmW3, P.wq, NH * DH, DM, 16, 3);
  make_map(enc, &tmW1, P.wq, NH * DH, DM, 128);
  make_map(enc, &tmK, P.k, DH, (uint64_t)NH * S_LEN, 128);
  make_map(enc, &tmV, P.v, DH, (uint64_t)NH * S_LEN, 128);
  make_map(enc, &tmWO, P.wo, DM, NH * DH, 64);
  make_map(enc, &tmG, d_in[7], FF, DM, 128);
  make_map(enc, &tmU, d_in[8], FF, DM, 128);
  make_map(enc, &tmD, d_in[9], DM, FF, 128);
  cudaFuncSetAttribute(fused_kernel, cudaFuncAttributeMaxDynamicSharedMemorySize, SMEM_BYTES);
  fused_kernel<<<132, 384, SMEM_BYTES, cudaStreamPerThread>>>(tmX, tmW4, tmW3, tmW1, tmK, tmV, tmWO, tmG, tmU, tmD, tmGate, P);
}
```

```cpp
#include <cuda_runtime.h>
#include <cuda_bf16.h>
#include <cuda.h>
#include <stdint.h>

#define MAXPOLL (1 << 22)
#define DPOS 44
#define DPOSF 36
#define KVPF 2
#define X_SKIP(qp) false
#define W1SL 300
#define WAITMAX (1 << 19)
#define CSB 8
#define P8 16
#define GSYNC 1
#define PH 1
#define XRC 15
#define QSP 6
namespace {

constexpr int S_LEN = 2048, DM = 640, NH = 32, DH = 128, FF = 1728, TOPC = 8;
constexpr float SCALE_LOG2E = 0.08838834764831845f * 1.4426950408889634f;

struct alignas(128) Cnt { unsigned v; unsigned pad[31]; };
struct Scratch {
  alignas(128) unsigned long long ticket;
  alignas(128)
  uint4 part[16 * 8 * 9 * 1024];
  __nv_bfloat16 gate[S_LEN * DM];
  uint32_t stat[S_LEN];
  uint4 cs[NH * DH];
  float ypart[4 * TOPC * DM];
  uint4 q3[16 * 8 * 1024];
  uint32_t key[S_LEN];
  Cnt cnt_gate, cnt_mod, mod_done, q3_done[4];
  uint32_t near[128 * 8];
};
__device__ Scratch g_s;

__device__ __forceinline__ uint32_t smem_u32(const void* p) { return (uint32_t)__cvta_generic_to_shared(p); }
template <class T> __device__ __forceinline__ T* at(const void* p, uint32_t off) { uint64_t r;
  asm("{\n.reg .u32 lo, hi;\nmov.b64 {lo, hi}, %1;\nadd.cc.u32 lo, lo, %2;\naddc.u32 hi, hi, 0;\nmov.b64 %0, {lo, hi};\n}\n" : "=l"(r) : "l"(p), "r"(off)); return (T*)r; }
__device__ __forceinline__ void mbar_init(uint32_t bar, uint32_t cnt) { asm volatile("mbarrier.init.shared::cta.b64 [%0], %1;" :: "r"(bar), "r"(cnt) : "memory"); }
__device__ __forceinline__ void mbar_expect_tx(uint32_t bar, uint32_t bytes) { asm volatile("mbarrier.arrive.expect_tx.shared::cta.b64 _, [%0], %1;" :: "r"(bar), "r"(bytes) : "memory"); }
__device__ __forceinline__ void mbar_arrive(uint32_t bar) { asm volatile("mbarrier.arrive.shared::cta.b64 _, [%0];" :: "r"(bar) : "memory"); }
__device__ __forceinline__ uint32_t map_cta(uint32_t a, uint32_t cta) { uint32_t r; asm volatile("mapa.shared::cluster.u32 %0, %1, %2;" : "=r"(r) : "r"(a), "r"(cta)); return r; }
__device__ __forceinline__ void mbar_arrive_cluster(uint32_t bar) { asm volatile("mbarrier.arrive.shared::cluster.b64 _, [%0];" :: "r"(bar) : "memory"); }
__device__ __forceinline__ void mbar_wait(uint32_t bar, uint32_t parity) {
  asm volatile("{\n.reg .pred p;\n.reg .u32 c;\nmov.u32 c, 0;\nLAB_WAIT:\nmbarrier.try_wait.parity.shared::cta.b64 p, [%0], %1;\n@p bra LAB_DONE;\n"
               "add.u32 c, c, 1;\nsetp.lt.u32 p, c, %2;\n@p bra LAB_WAIT;\ntrap;\nLAB_DONE:\n}\n" :: "r"(bar), "r"(parity), "n"(WAITMAX) : "memory"); }
__device__ __forceinline__ bool mbar_test2(uint32_t bar0, uint32_t par0, uint32_t bar1, uint32_t par1) { uint32_t r;
  asm volatile("{\n.reg .pred p, q;\nmbarrier.test_wait.parity.shared::cta.b64 p, [%1], %2;\nmbarrier.test_wait.parity.shared::cta.b64 q, [%3], %4;\nand.pred p, p, q;\nselp.u32 %0, 1, 0, p;\n}\n"
               : "=r"(r) : "r"(bar0), "r"(par0), "r"(bar1), "r"(par1) : "memory"); return r; }
__device__ __forceinline__ void mbar_pace(uint32_t bar, uint32_t parity) {
  asm volatile("{\n.reg .pred p;\n.reg .u32 c;\nmov.u32 c, 0;\nLAB_WAIT:\nmbarrier.try_wait.parity.shared::cta.b64 p, [%0], %1;\n@p bra LAB_DONE;\n"
               "add.u32 c, c, 1;\nsetp.lt.u32 p, c, 64;\n@p bra LAB_WAIT;\nLAB_DONE:\n}\n" :: "r"(bar), "r"(parity) : "memory"); }
__device__ __forceinline__ void flag_wait(const unsigned* p, unsigned target, unsigned ns = 500) {
  asm volatile("{\n.reg .pred p;\n.reg .u32 c, v;\nmov.u32 c, 0;\nLAB_WAIT:\nld.relaxed.gpu.global.u32 v, [%0];\nsub.u32 v, v, %1;\nsetp.ge.s32 p, v, 0;\n@p bra LAB_DONE;\n"
               "nanosleep.u32 %2;\nadd.u32 c, c, 1;\nsetp.lt.u32 p, c, 8388608;\n@p bra LAB_WAIT;\ntrap;\nLAB_DONE:\nld.acquire.gpu.global.u32 v, [%0];\n}\n" :: "l"(p), "r"(target), "r"(ns) : "memory"); }
__device__ __forceinline__ void flag_add_release(unsigned* p) { asm volatile("fence.acq_rel.gpu;\nred.relaxed.gpu.global.add.u32 [%0], 1;" :: "l"(p) : "memory"); }
__device__ __forceinline__ void tma_load_2d(uint32_t dst, const CUtensorMap* tm, uint32_t bar, int c0, int c1) {
  asm volatile("cp.async.bulk.tensor.2d.shared::cluster.global.mbarrier::complete_tx::bytes [%0], [%1, {%3, %4}], [%2];"
    :: "r"(dst), "l"(tm), "r"(bar), "r"(c0), "r"(c1) : "memory"); }
__device__ __forceinline__ void tma_load_2d_mc(uint32_t dst, const CUtensorMap* tm, uint32_t bar, int c0, int c1) {
  asm volatile("cp.async.bulk.tensor.2d.shared::cluster.global.mbarrier::complete_tx::bytes.multicast::cluster [%0], [%1, {%3, %4}], [%2], %5;"
    :: "r"(dst), "l"(tm), "r"(bar), "r"(c0), "r"(c1), "h"((uint16_t)3) : "memory"); }
__device__ __forceinline__ void tma_load_3d(uint32_t dst, const CUtensorMap* tm, uint32_t bar, int c0, int c1, int c2) {
  asm volatile("cp.async.bulk.tensor.3d.shared::cluster.global.mbarrier::complete_tx::bytes [%0], [%1, {%3, %4, %5}], [%2];"
    :: "r"(dst), "l"(tm), "r"(bar), "r"(c0), "r"(c1), "r"(c2) : "memory"); }
__device__ __forceinline__ void tma_load_3d_mc(uint32_t dst, const CUtensorMap* tm, uint32_t bar, int c0, int c1, int c2) {
  asm volatile("cp.async.bulk.tensor.3d.shared::cluster.global.mbarrier::complete_tx::bytes.multicast::cluster [%0], [%1, {%3, %4, %5}], [%2], %6;"
    :: "r"(dst), "l"(tm), "r"(bar), "r"(c0), "r"(c1), "r"(c2), "h"((uint16_t)3) : "memory"); }
__device__ __forceinline__ void bulk_load(uint32_t dst, const void* src, uint32_t bytes, uint32_t bar) {
  asm volatile("cp.async.bulk.shared::cluster.global.mbarrier::complete_tx::bytes [%0], [%1], %2, [%3];" :: "r"(dst), "l"(src), "r"(bytes), "r"(bar) : "memory"); }
__device__ __forceinline__ void l2_prefetch(const void* p, uint32_t bytes) { asm volatile("cp.async.bulk.prefetch.L2.global [%0], %1;" :: "l"(p), "r"(bytes) : "memory"); }
__device__ __forceinline__ void wg_fence() { asm volatile("wgmma.fence.sync.aligned;" ::: "memory"); }
__device__ __forceinline__ void wg_commit() { asm volatile("wgmma.commit_group.sync.aligned;" ::: "memory"); }
template <int N> __device__ __forceinline__ void wg_wait() { asm volatile("wgmma.wait_group.sync.aligned %0;" :: "n"(N) : "memory"); }
__device__ __forceinline__ void bar_sync(int id, int n) { asm volatile("bar.sync %0, %1;" :: "r"(id), "r"(n) : "memory"); }
__device__ __forceinline__ void bar_arrive(int id, int n) { asm volatile("bar.arrive %0, %1;" :: "r"(id), "r"(n) : "memory"); }
__device__ __forceinline__ bool bar_any(int id, int n, uint32_t v) { uint32_t r;
  asm volatile("{\n.reg .pred p;\nsetp.ne.u32 p, %3, 0;\nbar.red.or.pred p, %1, %2, p;\nselp.u32 %0, 1, 0, p;\n}\n" : "=r"(r) : "r"(id), "r"(n), "r"(v) : "memory"); return r; }
__device__ __forceinline__ int sel_lt(int a, int b, int x, int y) { int r; asm("{\n.reg .pred p;\nsetp.lt.s32 p, %1, %2;\nselp.s32 %0, %3, %4, p;\n}\n" : "=r"(r) : "r"(a), "r"(b), "r"(x), "r"(y)); return r; }
__device__ __forceinline__ bool elect_one() { uint32_t r; asm volatile("{\n.reg .pred p;\nelect.sync _|p, 0xffffffff;\nselp.u32 %0, 1, 0, p;\n}\n" : "=r"(r)); return r; }
__device__ __forceinline__ void cluster_arrive() { asm volatile("barrier.cluster.arrive.relaxed.aligned;" ::: "memory"); }
__device__ __forceinline__ void cluster_wait() { asm volatile("barrier.cluster.wait.aligned;" ::: "memory"); }
__device__ __forceinline__ void proxy_fence() { asm volatile("fence.proxy.async.shared::cta;" ::: "memory"); }
__device__ __forceinline__ uint32_t pack_bf16(float lo, float hi) { uint32_t r; asm("cvt.rn.bf16x2.f32 %0, %1, %2;" : "=r"(r) : "f"(hi), "f"(lo)); return r; }
__device__ __forceinline__ float bf_lo(uint32_t v) { return __uint_as_float(v << 16); }
__device__ __forceinline__ float bf_hi(uint32_t v) { return __uint_as_float(v & 0xffff0000u); }
__device__ __forceinline__ void add8(float* a, const uint4& w) {
  a[0] += bf_lo(w.x); a[1] += bf_hi(w.x); a[2] += bf_lo(w.y); a[3] += bf_hi(w.y); a[4] += bf_lo(w.z); a[5] += bf_hi(w.z); a[6] += bf_lo(w.w); a[7] += bf_hi(w.w); }
__device__ __forceinline__ float rbf(float x) { return __bfloat162float(__float2bfloat16_rn(x)); }
__device__ __forceinline__ float ex2(float x) { float y; asm("ex2.approx.ftz.f32 %0, %1;" : "=f"(y) : "f"(x)); return y; }
__device__ __forceinline__ uint32_t lds32(uint32_t a) { uint32_t v; asm volatile("ld.shared.u32 %0, [%1];" : "=r"(v) : "r"(a) : "memory"); return v; }
__device__ __forceinline__ void sts32(uint32_t a, uint32_t v) { asm volatile("st.shared.u32 [%0], %1;" :: "r"(a), "r"(v) : "memory"); }
__device__ __forceinline__ uint4 lds128(uint32_t a) { uint4 v; asm volatile("ld.shared.v4.u32 {%0,%1,%2,%3}, [%4];" : "=r"(v.x), "=r"(v.y), "=r"(v.z), "=r"(v.w) : "r"(a) : "memory"); return v; }
__device__ __forceinline__ void sts128(uint32_t a, uint32_t x, uint32_t y, uint32_t z, uint32_t w) { asm volatile("st.shared.v4.u32 [%0], {%1,%2,%3,%4};" :: "r"(a), "r"(x), "r"(y), "r"(z), "r"(w) : "memory"); }
__device__ __forceinline__ void sts128_if(bool c, uint32_t a, uint32_t x, uint32_t y, uint32_t z, uint32_t w) {
  asm volatile("{\n.reg .pred p;\nsetp.ne.u32 p, %5, 0;\n@p st.shared.v4.u32 [%0], {%1,%2,%3,%4};\n}\n" :: "r"(a), "r"(x), "r"(y), "r"(z), "r"(w), "r"((uint32_t)c) : "memory"); }
__device__ __forceinline__ void st_tagged(uint4* p, uint32_t x, uint32_t y, uint32_t z, uint32_t w) {
  asm volatile("st.relaxed.gpu.global.v4.u32 [%0], {%1,%2,%3,%4};" :: "l"(p), "r"(x), "r"(y), "r"(z), "r"(w) : "memory"); }
__device__ __forceinline__ uint4 ld_relaxed4(const void* p) { uint4 v;
  asm volatile("ld.relaxed.gpu.global.v4.u32 {%0,%1,%2,%3}, [%4];" : "=r"(v.x), "=r"(v.y), "=r"(v.z), "=r"(v.w) : "l"(p) : "memory"); return v; }
__device__ __forceinline__ uint4 ld_tagged(const uint4* p) { uint4 v;
  asm volatile("{\n.reg .b128 v;\nld.relaxed.gpu.global.b128 v, [%4];\nmov.b128 {%0,%1,%2,%3}, v;\n}\n" : "=r"(v.x), "=r"(v.y), "=r"(v.z), "=r"(v.w) : "l"(p) : "memory"); return v; }
__device__ __forceinline__ void reload(uint4& v, const uint4* p, bool yes = true) {
  asm volatile("{\n.reg .pred p;\nsetp.ne.u32 p, %5, 0;\n@p ld.relaxed.gpu.global.v4.u32 {%0,%1,%2,%3}, [%4];\n}\n" : "+r"(v.x), "+r"(v.y), "+r"(v.z), "+r"(v.w) : "l"(p), "r"((uint32_t)yes) : "memory"); }
#define TAG_TEST "lop3.b32 a, %0, %4, %17, 0x7E;\nlop3.b32 b, %8, %12, %17, 0x7E;\nlop3.b32 a, a, b, 1, 0xA8;\nsetp.ne.u32 p, a, 0;\nvote.sync.any.pred p, p, 0xffffffff;\n"
__device__ __forceinline__ void verify4(uint4* v, const uint4* p, uint32_t tm) {
  asm volatile("{\n.reg .pred p;\n.reg .u32 a, b, c;\n" TAG_TEST "@!p bra.uni LAB_DONE;\nmov.u32 c, 0;\nLAB_AGAIN:\n"
    "ld.relaxed.gpu.global.v4.u32 {%0,%1,%2,%3}, [%16];\nld.relaxed.gpu.global.v4.u32 {%4,%5,%6,%7}, [%16+2048];\n"
    "ld.relaxed.gpu.global.v4.u32 {%8,%9,%10,%11}, [%16+4096];\nld.relaxed.gpu.global.v4.u32 {%12,%13,%14,%15}, [%16+6144];\n"
    TAG_TEST "add.u32 c, c, 1;\nsetp.lt.and.u32 p, c, %18, p;\n@p bra.uni LAB_AGAIN;\nLAB_DONE:\n}\n"
    : "+r"(v[0].x), "+r"(v[0].y), "+r"(v[0].z), "+r"(v[0].w), "+r"(v[1].x), "+r"(v[1].y), "+r"(v[1].z), "+r"(v[1].w),
      "+r"(v[2].x), "+r"(v[2].y), "+r"(v[2].z), "+r"(v[2].w), "+r"(v[3].x), "+r"(v[3].y), "+r"(v[3].z), "+r"(v[3].w) : "l"(p), "r"(tm), "n"(MAXPOLL) : "memory"); }
__device__ __forceinline__ uint4 ldg_nc(const void* p) { uint4 v;
  asm volatile("ld.global.nc.L1::no_allocate.v4.u32 {%0,%1,%2,%3}, [%4];" : "=r"(v.x), "=r"(v.y), "=r"(v.z), "=r"(v.w) : "l"(p) : "memory"); return v; }
__device__ __forceinline__ uint32_t ldg32(const void* p) { uint32_t v; asm volatile("ld.relaxed.gpu.global.u32 %0, [%1];" : "=r"(v) : "l"(p) : "memory"); return v; }
__device__ __forceinline__ void stg128(void* p, const uint4& v) { asm volatile("st.global.v4.u32 [%0], {%1,%2,%3,%4};" :: "l"(p), "r"(v.x), "r"(v.y), "r"(v.z), "r"(v.w) : "memory"); }
__device__ __forceinline__ void st_relaxed(uint32_t* p, uint32_t v) { asm volatile("st.relaxed.gpu.global.u32 [%0], %1;" :: "l"(p), "r"(v) : "memory"); }
__device__ __forceinline__ uint32_t mul_bf2(uint32_t a, uint32_t b) { uint32_t r; asm("mul.rn.bf16x2 %0, %1, %2;" : "=r"(r) : "r"(a), "r"(b)); return r; }
__device__ __forceinline__ uint32_t add_bf2(uint32_t a, uint32_t b) { uint32_t r; asm("add.rn.bf16x2 %0, %1, %2;" : "=r"(r) : "r"(a), "r"(b)); return r; }
__device__ __forceinline__ uint32_t sub_bf2(uint32_t a, uint32_t b) { uint32_t r; asm("sub.rn.bf16x2 %0, %1, %2;" : "=r"(r) : "r"(a), "r"(b)); return r; }
__device__ __forceinline__ void stsm4(uint32_t a, uint32_t r0, uint32_t r1, uint32_t r2, uint32_t r3) {
  asm volatile("stmatrix.sync.aligned.m8n8.x4.shared.b16 [%0], {%1,%2,%3,%4};" :: "r"(a), "r"(r0), "r"(r1), "r"(r2), "r"(r3) : "memory"); }
__device__ __forceinline__ void stsm4t(uint32_t a, uint32_t r0, uint32_t r1, uint32_t r2, uint32_t r3) {
  asm volatile("stmatrix.sync.aligned.m8n8.x4.trans.shared.b16 [%0], {%1,%2,%3,%4};" :: "r"(a), "r"(r0), "r"(r1), "r"(r2), "r"(r3) : "memory"); }
__device__ __forceinline__ uint4 gated(const uint4& x, const uint4& s, const uint4& g) {
  return make_uint4(add_bf2(x.x, mul_bf2(s.x, g.x)), add_bf2(x.y, mul_bf2(s.y, g.y)), add_bf2(x.z, mul_bf2(s.z, g.z)), add_bf2(x.w, mul_bf2(s.w, g.w))); }
__device__ __forceinline__ uint32_t tag_miss(uint32_t a, uint32_t b, uint32_t tm) { uint32_t d; asm("lop3.b32 %0, %1, %2, %3, 0x7E;" : "=r"(d) : "r"(a), "r"(b), "r"(tm)); return d; }
template <int R> __device__ __forceinline__ void fence_regs(float (&d)[R]) {
  #pragma unroll
  for (int i = 0; i < R; i++) asm volatile("" : "+f"(d[i]) :: "memory"); }
template <int R> __device__ __forceinline__ void fence_regs(uint32_t (&d)[R]) {
  #pragma unroll
  for (int i = 0; i < R; i++) asm volatile("" : "+r"(d[i]) :: "memory"); }
__device__ __forceinline__ uint32_t desc_lo(uint32_t addr, uint32_t lbo_bytes) { return ((addr & 0x3FFFF) >> 4) | ((lbo_bytes >> 4) << 16); }
__device__ __forceinline__ uint64_t desc(uint32_t sb, uint32_t var = 0) {
  uint64_t d; asm("mov.b64 %0, {%1, %2};" : "=l"(d) : "r"(desc_lo(sb, 0) + var), "r"(0x40000040u)); return d; }
__host__ __device__ constexpr int doff(uint32_t off, uint32_t lbo_bytes) { return (off >> 4) | ((lbo_bytes >> 4) << 16); }
__device__ __forceinline__ float rcp_approx(float x) { float y; asm("rcp.approx.f32 %0, %1;" : "=f"(y) : "f"(x)); return y; }
__device__ __forceinline__ float rcp_fast(float x) { float y; asm("rcp.approx.ftz.f32 %0, %1;" : "=f"(y) : "f"(x)); return y; }
__device__ __forceinline__ float sqrt_approx(float x) { float y; asm("sqrt.approx.f32 %0, %1;" : "=f"(y) : "f"(x)); return y; }
__device__ __forceinline__ float sigmoid_f(float z) { return rcp_fast(1.f + ex2(z * -1.4426950408889634f)); }
__device__ __forceinline__ uint32_t norm2(uint32_t x, uint32_t mean2, float rsd) { const uint32_t d = sub_bf2(x, mean2); return pack_bf16(bf_lo(d) * rsd, bf_hi(d) * rsd); }
#define STALL(site)
#define TRACE(w, i)
#define TRACE1(w, i)
#define TRACEF(m, w, i)
#define TRACEO(i)

template <int OA, int OB> __device__ __forceinline__ void wgmma_ss_tb(float (&d)[128], uint64_t da, uint64_t db, int sd) {
  asm volatile("{\n.reg .pred p;\n.reg .b64 a, b;\nadd.s64 a, %128, %131;\nadd.s64 b, %129, %132;\nsetp.ne.b32 p, %130, 0;\n"
    "wgmma.mma_async.sync.aligned.m64n256k16.f32.bf16.bf16 {%0, %1, %2, %3, %4, %5, %6, %7, %8, %9, %10, %11, %12, %13, %14, %15, %16, %17, %18, %19, %20, %21, %22, %23, %24, %25, %26, %27, %28, %29, %30, %31, %32, %33, %34, %35, %36, %37, %38, %39, %40, %41, %42, %43, %44, %45, %46, %47, %48, %49, %50, %51, %52, %53, %54, %55, %56, %57, %58, %59, %60, %61, %62, %63, %64, %65, %66, %67, %68, %69, %70, %71, %72, %73, %74, %75, %76, %77, %78, %79, %80, %81, %82, %83, %84, %85, %86, %87, %88, %89, %90, %91, %92, %93, %94, %95, %96, %97, %98, %99, %100, %101, %102, %103, %104, %105, %106, %107, %108, %109, %110, %111, %112, %113, %114, %115, %116, %117, %118, %119, %120, %121, %122, %123, %124, %125, %126, %127}, a, b, p, 1, 1, 0, 1;\n}\n"
    : "+f"(d[0]), "+f"(d[1]), "+f"(d[2]), "+f"(d[3]), "+f"(d[4]), "+f"(d[5]), "+f"(d[6]), "+f"(d[7]), "+f"(d[8]), "+f"(d[9]), "+f"(d[10]), "+f"(d[11]), "+f"(d[12]), "+f"(d[13]), "+f"(d[14]), "+f"(d[15]), "+f"(d[16]), "+f"(d[17]), "+f"(d[18]), "+f"(d[19]), "+f"(d[20]), "+f"(d[21]), "+f"(d[22]), "+f"(d[23]), "+f"(d[24]), "+f"(d[25]), "+f"(d[26]), "+f"(d[27]), "+f"(d[28]), "+f"(d[29]), "+f"(d[30]), "+f"(d[31]), "+f"(d[32]), "+f"(d[33]), "+f"(d[34]), "+f"(d[35]), "+f"(d[36]), "+f"(d[37]), "+f"(d[38]), "+f"(d[39]), "+f"(d[40]), "+f"(d[41]), "+f"(d[42]), "+f"(d[43]), "+f"(d[44]), "+f"(d[45]), "+f"(d[46]), "+f"(d[47]), "+f"(d[48]), "+f"(d[49]), "+f"(d[50]), "+f"(d[51]), "+f"(d[52]), "+f"(d[53]), "+f"(d[54]), "+f"(d[55]), "+f"(d[56]), "+f"(d[57]), "+f"(d[58]), "+f"(d[59]), "+f"(d[60]), "+f"(d[61]), "+f"(d[62]), "+f"(d[63]), "+f"(d[64]), "+f"(d[65]), "+f"(d[66]), "+f"(d[67]), "+f"(d[68]), "+f"(d[69]), "+f"(d[70]), "+f"(d[71]), "+f"(d[72]), "+f"(d[73]), "+f"(d[74]), "+f"(d[75]), "+f"(d[76]), "+f"(d[77]), "+f"(d[78]), "+f"(d[79]), "+f"(d[80]), "+f"(d[81]), "+f"(d[82]), "+f"(d[83]), "+f"(d[84]), "+f"(d[85]), "+f"(d[86]), "+f"(d[87]), "+f"(d[88]), "+f"(d[89]), "+f"(d[90]), "+f"(d[91]), "+f"(d[92]), "+f"(d[93]), "+f"(d[94]), "+f"(d[95]), "+f"(d[96]), "+f"(d[97]), "+f"(d[98]), "+f"(d[99]), "+f"(d[100]), "+f"(d[101]), "+f"(d[102]), "+f"(d[103]), "+f"(d[104]), "+f"(d[105]), "+f"(d[106]), "+f"(d[107]), "+f"(d[108]), "+f"(d[109]), "+f"(d[110]), "+f"(d[111]), "+f"(d[112]), "+f"(d[113]), "+f"(d[114]), "+f"(d[115]), "+f"(d[116]), "+f"(d[117]), "+f"(d[118]), "+f"(d[119]), "+f"(d[120]), "+f"(d[121]), "+f"(d[122]), "+f"(d[123]), "+f"(d[124]), "+f"(d[125]), "+f"(d[126]), "+f"(d[127])
    : "l"(da), "l"(db), "r"(sd), "n"(OA), "n"(OB));
}
template <int OB> __device__ __forceinline__ void wgmma_rs_tb(float (&d)[128], uint32_t a0, uint32_t a1, uint32_t a2, uint32_t a3, uint64_t db, int sd) {
  asm volatile("{\n.reg .pred p;\n.reg .b64 b;\nadd.s64 b, %132, %134;\nsetp.ne.b32 p, %133, 0;\n"
    "wgmma.mma_async.sync.aligned.m64n256k16.f32.bf16.bf16 {%0, %1, %2, %3, %4, %5, %6, %7, %8, %9, %10, %11, %12, %13, %14, %15, %16, %17, %18, %19, %20, %21, %22, %23, %24, %25, %26, %27, %28, %29, %30, %31, %32, %33, %34, %35, %36, %37, %38, %39, %40, %41, %42, %43, %44, %45, %46, %47, %48, %49, %50, %51, %52, %53, %54, %55, %56, %57, %58, %59, %60, %61, %62, %63, %64, %65, %66, %67, %68, %69, %70, %71, %72, %73, %74, %75, %76, %77, %78, %79, %80, %81, %82, %83, %84, %85, %86, %87, %88, %89, %90, %91, %92, %93, %94, %95, %96, %97, %98, %99, %100, %101, %102, %103, %104, %105, %106, %107, %108, %109, %110, %111, %112, %113, %114, %115, %116, %117, %118, %119, %120, %121, %122, %123, %124, %125, %126, %127}, {%128, %129, %130, %131}, b, p, 1, 1, 1;\n}\n"
    : "+f"(d[0]), "+f"(d[1]), "+f"(d[2]), "+f"(d[3]), "+f"(d[4]), "+f"(d[5]), "+f"(d[6]), "+f"(d[7]), "+f"(d[8]), "+f"(d[9]), "+f"(d[10]), "+f"(d[11]), "+f"(d[12]), "+f"(d[13]), "+f"(d[14]), "+f"(d[15]), "+f"(d[16]), "+f"(d[17]), "+f"(d[18]), "+f"(d[19]), "+f"(d[20]), "+f"(d[21]), "+f"(d[22]), "+f"(d[23]), "+f"(d[24]), "+f"(d[25]), "+f"(d[26]), "+f"(d[27]), "+f"(d[28]), "+f"(d[29]), "+f"(d[30]), "+f"(d[31]), "+f"(d[32]), "+f"(d[33]), "+f"(d[34]), "+f"(d[35]), "+f"(d[36]), "+f"(d[37]), "+f"(d[38]), "+f"(d[39]), "+f"(d[40]), "+f"(d[41]), "+f"(d[42]), "+f"(d[43]), "+f"(d[44]), "+f"(d[45]), "+f"(d[46]), "+f"(d[47]), "+f"(d[48]), "+f"(d[49]), "+f"(d[50]), "+f"(d[51]), "+f"(d[52]), "+f"(d[53]), "+f"(d[54]), "+f"(d[55]), "+f"(d[56]), "+f"(d[57]), "+f"(d[58]), "+f"(d[59]), "+f"(d[60]), "+f"(d[61]), "+f"(d[62]), "+f"(d[63]), "+f"(d[64]), "+f"(d[65]), "+f"(d[66]), "+f"(d[67]), "+f"(d[68]), "+f"(d[69]), "+f"(d[70]), "+f"(d[71]), "+f"(d[72]), "+f"(d[73]), "+f"(d[74]), "+f"(d[75]), "+f"(d[76]), "+f"(d[77]), "+f"(d[78]), "+f"(d[79]), "+f"(d[80]), "+f"(d[81]), "+f"(d[82]), "+f"(d[83]), "+f"(d[84]), "+f"(d[85]), "+f"(d[86]), "+f"(d[87]), "+f"(d[88]), "+f"(d[89]), "+f"(d[90]), "+f"(d[91]), "+f"(d[92]), "+f"(d[93]), "+f"(d[94]), "+f"(d[95]), "+f"(d[96]), "+f"(d[97]), "+f"(d[98]), "+f"(d[99]), "+f"(d[100]), "+f"(d[101]), "+f"(d[102]), "+f"(d[103]), "+f"(d[104]), "+f"(d[105]), "+f"(d[106]), "+f"(d[107]), "+f"(d[108]), "+f"(d[109]), "+f"(d[110]), "+f"(d[111]), "+f"(d[112]), "+f"(d[113]), "+f"(d[114]), "+f"(d[115]), "+f"(d[116]), "+f"(d[117]), "+f"(d[118]), "+f"(d[119]), "+f"(d[120]), "+f"(d[121]), "+f"(d[122]), "+f"(d[123]), "+f"(d[124]), "+f"(d[125]), "+f"(d[126]), "+f"(d[127])
    : "r"(a0), "r"(a1), "r"(a2), "r"(a3), "l"(db), "r"(sd), "n"(OB));
}
template <int OA, int OB> __device__ __forceinline__ void wgmma_ss_tb(float (&d)[96], uint64_t da, uint64_t db, int sd) {
  asm volatile("{\n.reg .pred p;\n.reg .b64 a, b;\nadd.s64 a, %96, %99;\nadd.s64 b, %97, %100;\nsetp.ne.b32 p, %98, 0;\n"
    "wgmma.mma_async.sync.aligned.m64n192k16.f32.bf16.bf16 {%0, %1, %2, %3, %4, %5, %6, %7, %8, %9, %10, %11, %12, %13, %14, %15, %16, %17, %18, %19, %20, %21, %22, %23, %24, %25, %26, %27, %28, %29, %30, %31, %32, %33, %34, %35, %36, %37, %38, %39, %40, %41, %42, %43, %44, %45, %46, %47, %48, %49, %50, %51, %52, %53, %54, %55, %56, %57, %58, %59, %60, %61, %62, %63, %64, %65, %66, %67, %68, %69, %70, %71, %72, %73, %74, %75, %76, %77, %78, %79, %80, %81, %82, %83, %84, %85, %86, %87, %88, %89, %90, %91, %92, %93, %94, %95}, a, b, p, 1, 1, 0, 1;\n}\n"
    : "+f"(d[0]), "+f"(d[1]), "+f"(d[2]), "+f"(d[3]), "+f"(d[4]), "+f"(d[5]), "+f"(d[6]), "+f"(d[7]), "+f"(d[8]), "+f"(d[9]), "+f"(d[10]), "+f"(d[11]), "+f"(d[12]), "+f"(d[13]), "+f"(d[14]), "+f"(d[15]), "+f"(d[16]), "+f"(d[17]), "+f"(d[18]), "+f"(d[19]), "+f"(d[20]), "+f"(d[21]), "+f"(d[22]), "+f"(d[23]), "+f"(d[24]), "+f"(d[25]), "+f"(d[26]), "+f"(d[27]), "+f"(d[28]), "+f"(d[29]), "+f"(d[30]), "+f"(d[31]), "+f"(d[32]), "+f"(d[33]), "+f"(d[34]), "+f"(d[35]), "+f"(d[36]), "+f"(d[37]), "+f"(d[38]), "+f"(d[39]), "+f"(d[40]), "+f"(d[41]), "+f"(d[42]), "+f"(d[43]), "+f"(d[44]), "+f"(d[45]), "+f"(d[46]), "+f"(d[47]), "+f"(d[48]), "+f"(d[49]), "+f"(d[50]), "+f"(d[51]), "+f"(d[52]), "+f"(d[53]), "+f"(d[54]), "+f"(d[55]), "+f"(d[56]), "+f"(d[57]), "+f"(d[58]), "+f"(d[59]), "+f"(d[60]), "+f"(d[61]), "+f"(d[62]), "+f"(d[63]), "+f"(d[64]), "+f"(d[65]), "+f"(d[66]), "+f"(d[67]), "+f"(d[68]), "+f"(d[69]), "+f"(d[70]), "+f"(d[71]), "+f"(d[72]), "+f"(d[73]), "+f"(d[74]), "+f"(d[75]), "+f"(d[76]), "+f"(d[77]), "+f"(d[78]), "+f"(d[79]), "+f"(d[80]), "+f"(d[81]), "+f"(d[82]), "+f"(d[83]), "+f"(d[84]), "+f"(d[85]), "+f"(d[86]), "+f"(d[87]), "+f"(d[88]), "+f"(d[89]), "+f"(d[90]), "+f"(d[91]), "+f"(d[92]), "+f"(d[93]), "+f"(d[94]), "+f"(d[95])
    : "l"(da), "l"(db), "r"(sd), "n"(OA), "n"(OB));
}
template <int OB> __device__ __forceinline__ void wgmma_rs_tb(float (&d)[96], uint32_t a0, uint32_t a1, uint32_t a2, uint32_t a3, uint64_t db, int sd) {
  asm volatile("{\n.reg .pred p;\n.reg .b64 b;\nadd.s64 b, %100, %102;\nsetp.ne.b32 p, %101, 0;\n"
    "wgmma.mma_async.sync.aligned.m64n192k16.f32.bf16.bf16 {%0, %1, %2, %3, %4, %5, %6, %7, %8, %9, %10, %11, %12, %13, %14, %15, %16, %17, %18, %19, %20, %21, %22, %23, %24, %25, %26, %27, %28, %29, %30, %31, %32, %33, %34, %35, %36, %37, %38, %39, %40, %41, %42, %43, %44, %45, %46, %47, %48, %49, %50, %51, %52, %53, %54, %55, %56, %57, %58, %59, %60, %61, %62, %63, %64, %65, %66, %67, %68, %69, %70, %71, %72, %73, %74, %75, %76, %77, %78, %79, %80, %81, %82, %83, %84, %85, %86, %87, %88, %89, %90, %91, %92, %93, %94, %95}, {%96, %97, %98, %99}, b, p, 1, 1, 1;\n}\n"
    : "+f"(d[0]), "+f"(d[1]), "+f"(d[2]), "+f"(d[3]), "+f"(d[4]), "+f"(d[5]), "+f"(d[6]), "+f"(d[7]), "+f"(d[8]), "+f"(d[9]), "+f"(d[10]), "+f"(d[11]), "+f"(d[12]), "+f"(d[13]), "+f"(d[14]), "+f"(d[15]), "+f"(d[16]), "+f"(d[17]), "+f"(d[18]), "+f"(d[19]), "+f"(d[20]), "+f"(d[21]), "+f"(d[22]), "+f"(d[23]), "+f"(d[24]), "+f"(d[25]), "+f"(d[26]), "+f"(d[27]), "+f"(d[28]), "+f"(d[29]), "+f"(d[30]), "+f"(d[31]), "+f"(d[32]), "+f"(d[33]), "+f"(d[34]), "+f"(d[35]), "+f"(d[36]), "+f"(d[37]), "+f"(d[38]), "+f"(d[39]), "+f"(d[40]), "+f"(d[41]), "+f"(d[42]), "+f"(d[43]), "+f"(d[44]), "+f"(d[45]), "+f"(d[46]), "+f"(d[47]), "+f"(d[48]), "+f"(d[49]), "+f"(d[50]), "+f"(d[51]), "+f"(d[52]), "+f"(d[53]), "+f"(d[54]), "+f"(d[55]), "+f"(d[56]), "+f"(d[57]), "+f"(d[58]), "+f"(d[59]), "+f"(d[60]), "+f"(d[61]), "+f"(d[62]), "+f"(d[63]), "+f"(d[64]), "+f"(d[65]), "+f"(d[66]), "+f"(d[67]), "+f"(d[68]), "+f"(d[69]), "+f"(d[70]), "+f"(d[71]), "+f"(d[72]), "+f"(d[73]), "+f"(d[74]), "+f"(d[75]), "+f"(d[76]), "+f"(d[77]), "+f"(d[78]), "+f"(d[79]), "+f"(d[80]), "+f"(d[81]), "+f"(d[82]), "+f"(d[83]), "+f"(d[84]), "+f"(d[85]), "+f"(d[86]), "+f"(d[87]), "+f"(d[88]), "+f"(d[89]), "+f"(d[90]), "+f"(d[91]), "+f"(d[92]), "+f"(d[93]), "+f"(d[94]), "+f"(d[95])
    : "r"(a0), "r"(a1), "r"(a2), "r"(a3), "l"(db), "r"(sd), "n"(OB));
}
template <int OA, int OB> __device__ __forceinline__ void wgmma_ss_tb(float (&d)[64], uint64_t da, uint64_t db, int sd) {
  asm volatile("{\n.reg .pred p;\n.reg .b64 a, b;\nadd.s64 a, %64, %67;\nadd.s64 b, %65, %68;\nsetp.ne.b32 p, %66, 0;\n"
    "wgmma.mma_async.sync.aligned.m64n128k16.f32.bf16.bf16 {%0, %1, %2, %3, %4, %5, %6, %7, %8, %9, %10, %11, %12, %13, %14, %15, %16, %17, %18, %19, %20, %21, %22, %23, %24, %25, %26, %27, %28, %29, %30, %31, %32, %33, %34, %35, %36, %37, %38, %39, %40, %41, %42, %43, %44, %45, %46, %47, %48, %49, %50, %51, %52, %53, %54, %55, %56, %57, %58, %59, %60, %61, %62, %63}, a, b, p, 1, 1, 0, 1;\n}\n"
    : "+f"(d[0]), "+f"(d[1]), "+f"(d[2]), "+f"(d[3]), "+f"(d[4]), "+f"(d[5]), "+f"(d[6]), "+f"(d[7]), "+f"(d[8]), "+f"(d[9]), "+f"(d[10]), "+f"(d[11]), "+f"(d[12]), "+f"(d[13]), "+f"(d[14]), "+f"(d[15]), "+f"(d[16]), "+f"(d[17]), "+f"(d[18]), "+f"(d[19]), "+f"(d[20]), "+f"(d[21]), "+f"(d[22]), "+f"(d[23]), "+f"(d[24]), "+f"(d[25]), "+f"(d[26]), "+f"(d[27]), "+f"(d[28]), "+f"(d[29]), "+f"(d[30]), "+f"(d[31]), "+f"(d[32]), "+f"(d[33]), "+f"(d[34]), "+f"(d[35]), "+f"(d[36]), "+f"(d[37]), "+f"(d[38]), "+f"(d[39]), "+f"(d[40]), "+f"(d[41]), "+f"(d[42]), "+f"(d[43]), "+f"(d[44]), "+f"(d[45]), "+f"(d[46]), "+f"(d[47]), "+f"(d[48]), "+f"(d[49]), "+f"(d[50]), "+f"(d[51]), "+f"(d[52]), "+f"(d[53]), "+f"(d[54]), "+f"(d[55]), "+f"(d[56]), "+f"(d[57]), "+f"(d[58]), "+f"(d[59]), "+f"(d[60]), "+f"(d[61]), "+f"(d[62]), "+f"(d[63])
    : "l"(da), "l"(db), "r"(sd), "n"(OA), "n"(OB));
}
template <int OB> __device__ __forceinline__ void wgmma_rs_tb(float (&d)[64], uint32_t a0, uint32_t a1, uint32_t a2, uint32_t a3, uint64_t db, int sd) {
  asm volatile("{\n.reg .pred p;\n.reg .b64 b;\nadd.s64 b, %68, %70;\nsetp.ne.b32 p, %69, 0;\n"
    "wgmma.mma_async.sync.aligned.m64n128k16.f32.bf16.bf16 {%0, %1, %2, %3, %4, %5, %6, %7, %8, %9, %10, %11, %12, %13, %14, %15, %16, %17, %18, %19, %20, %21, %22, %23, %24, %25, %26, %27, %28, %29, %30, %31, %32, %33, %34, %35, %36, %37, %38, %39, %40, %41, %42, %43, %44, %45, %46, %47, %48, %49, %50, %51, %52, %53, %54, %55, %56, %57, %58, %59, %60, %61, %62, %63}, {%64, %65, %66, %67}, b, p, 1, 1, 1;\n}\n"
    : "+f"(d[0]), "+f"(d[1]), "+f"(d[2]), "+f"(d[3]), "+f"(d[4]), "+f"(d[5]), "+f"(d[6]), "+f"(d[7]), "+f"(d[8]), "+f"(d[9]), "+f"(d[10]), "+f"(d[11]), "+f"(d[12]), "+f"(d[13]), "+f"(d[14]), "+f"(d[15]), "+f"(d[16]), "+f"(d[17]), "+f"(d[18]), "+f"(d[19]), "+f"(d[20]), "+f"(d[21]), "+f"(d[22]), "+f"(d[23]), "+f"(d[24]), "+f"(d[25]), "+f"(d[26]), "+f"(d[27]), "+f"(d[28]), "+f"(d[29]), "+f"(d[30]), "+f"(d[31]), "+f"(d[32]), "+f"(d[33]), "+f"(d[34]), "+f"(d[35]), "+f"(d[36]), "+f"(d[37]), "+f"(d[38]), "+f"(d[39]), "+f"(d[40]), "+f"(d[41]), "+f"(d[42]), "+f"(d[43]), "+f"(d[44]), "+f"(d[45]), "+f"(d[46]), "+f"(d[47]), "+f"(d[48]), "+f"(d[49]), "+f"(d[50]), "+f"(d[51]), "+f"(d[52]), "+f"(d[53]), "+f"(d[54]), "+f"(d[55]), "+f"(d[56]), "+f"(d[57]), "+f"(d[58]), "+f"(d[59]), "+f"(d[60]), "+f"(d[61]), "+f"(d[62]), "+f"(d[63])
    : "r"(a0), "r"(a1), "r"(a2), "r"(a3), "l"(db), "r"(sd), "n"(OB));
}
template <int OA, int OB> __device__ __forceinline__ void wgmma_ss_ta(float (&d)[64], uint64_t da, uint64_t db, int sd) {
  asm volatile("{\n.reg .pred p;\n.reg .b64 a, b;\nadd.s64 a, %64, %67;\nadd.s64 b, %65, %68;\nsetp.ne.b32 p, %66, 0;\n"
    "wgmma.mma_async.sync.aligned.m64n128k16.f32.bf16.bf16 {%0, %1, %2, %3, %4, %5, %6, %7, %8, %9, %10, %11, %12, %13, %14, %15, %16, %17, %18, %19, %20, %21, %22, %23, %24, %25, %26, %27, %28, %29, %30, %31, %32, %33, %34, %35, %36, %37, %38, %39, %40, %41, %42, %43, %44, %45, %46, %47, %48, %49, %50, %51, %52, %53, %54, %55, %56, %57, %58, %59, %60, %61, %62, %63}, a, b, p, 1, 1, 1, 0;\n}\n"
    : "+f"(d[0]), "+f"(d[1]), "+f"(d[2]), "+f"(d[3]), "+f"(d[4]), "+f"(d[5]), "+f"(d[6]), "+f"(d[7]), "+f"(d[8]), "+f"(d[9]), "+f"(d[10]), "+f"(d[11]), "+f"(d[12]), "+f"(d[13]), "+f"(d[14]), "+f"(d[15]), "+f"(d[16]), "+f"(d[17]), "+f"(d[18]), "+f"(d[19]), "+f"(d[20]), "+f"(d[21]), "+f"(d[22]), "+f"(d[23]), "+f"(d[24]), "+f"(d[25]), "+f"(d[26]), "+f"(d[27]), "+f"(d[28]), "+f"(d[29]), "+f"(d[30]), "+f"(d[31]), "+f"(d[32]), "+f"(d[33]), "+f"(d[34]), "+f"(d[35]), "+f"(d[36]), "+f"(d[37]), "+f"(d[38]), "+f"(d[39]), "+f"(d[40]), "+f"(d[41]), "+f"(d[42]), "+f"(d[43]), "+f"(d[44]), "+f"(d[45]), "+f"(d[46]), "+f"(d[47]), "+f"(d[48]), "+f"(d[49]), "+f"(d[50]), "+f"(d[51]), "+f"(d[52]), "+f"(d[53]), "+f"(d[54]), "+f"(d[55]), "+f"(d[56]), "+f"(d[57]), "+f"(d[58]), "+f"(d[59]), "+f"(d[60]), "+f"(d[61]), "+f"(d[62]), "+f"(d[63])
    : "l"(da), "l"(db), "r"(sd), "n"(OA), "n"(OB));
}
template <int OB> __device__ __forceinline__ void wgmma_rs(float (&d)[64], uint32_t a0, uint32_t a1, uint32_t a2, uint32_t a3, uint64_t db, int sd) {
  asm volatile("{\n.reg .pred p;\n.reg .b64 b;\nadd.s64 b, %68, %70;\nsetp.ne.b32 p, %69, 0;\n"
    "wgmma.mma_async.sync.aligned.m64n128k16.f32.bf16.bf16 {%0, %1, %2, %3, %4, %5, %6, %7, %8, %9, %10, %11, %12, %13, %14, %15, %16, %17, %18, %19, %20, %21, %22, %23, %24, %25, %26, %27, %28, %29, %30, %31, %32, %33, %34, %35, %36, %37, %38, %39, %40, %41, %42, %43, %44, %45, %46, %47, %48, %49, %50, %51, %52, %53, %54, %55, %56, %57, %58, %59, %60, %61, %62, %63}, {%64, %65, %66, %67}, b, p, 1, 1, 0;\n}\n"
    : "+f"(d[0]), "+f"(d[1]), "+f"(d[2]), "+f"(d[3]), "+f"(d[4]), "+f"(d[5]), "+f"(d[6]), "+f"(d[7]), "+f"(d[8]), "+f"(d[9]), "+f"(d[10]), "+f"(d[11]), "+f"(d[12]), "+f"(d[13]), "+f"(d[14]), "+f"(d[15]), "+f"(d[16]), "+f"(d[17]), "+f"(d[18]), "+f"(d[19]), "+f"(d[20]), "+f"(d[21]), "+f"(d[22]), "+f"(d[23]), "+f"(d[24]), "+f"(d[25]), "+f"(d[26]), "+f"(d[27]), "+f"(d[28]), "+f"(d[29]), "+f"(d[30]), "+f"(d[31]), "+f"(d[32]), "+f"(d[33]), "+f"(d[34]), "+f"(d[35]), "+f"(d[36]), "+f"(d[37]), "+f"(d[38]), "+f"(d[39]), "+f"(d[40]), "+f"(d[41]), "+f"(d[42]), "+f"(d[43]), "+f"(d[44]), "+f"(d[45]), "+f"(d[46]), "+f"(d[47]), "+f"(d[48]), "+f"(d[49]), "+f"(d[50]), "+f"(d[51]), "+f"(d[52]), "+f"(d[53]), "+f"(d[54]), "+f"(d[55]), "+f"(d[56]), "+f"(d[57]), "+f"(d[58]), "+f"(d[59]), "+f"(d[60]), "+f"(d[61]), "+f"(d[62]), "+f"(d[63])
    : "r"(a0), "r"(a1), "r"(a2), "r"(a3), "l"(db), "r"(sd), "n"(OB));
}
template <int OA, int OB> __device__ __forceinline__ void wgmma_ss_ta(float (&d)[4], uint64_t da, uint64_t db, int sd) {
  asm volatile("{\n.reg .pred p;\n.reg .b64 a, b;\nadd.s64 a, %4, %7;\nadd.s64 b, %5, %8;\nsetp.ne.b32 p, %6, 0;\n"
    "wgmma.mma_async.sync.aligned.m64n8k16.f32.bf16.bf16 {%0, %1, %2, %3}, a, b, p, 1, 1, 1, 0;\n}\n"
    : "+f"(d[0]), "+f"(d[1]), "+f"(d[2]), "+f"(d[3])
    : "l"(da), "l"(db), "r"(sd), "n"(OA), "n"(OB));
}

constexpr uint32_t U = 16384;
constexpr uint32_t SM_QO = 2 * U, SM_W = 8 * U, SM_V = 8 * U, SM_K1 = 12 * U, SM_BAR = 14 * U;
constexpr uint32_t B_WF = SM_BAR, B_KF = SM_BAR + 48, B_CF = SM_BAR + 80, B_GATE = SM_BAR + 128, B_OF = SM_BAR + 136, B_EP = SM_BAR + 144, B_EXT = SM_BAR + 152, B_Q3 = SM_BAR + 168, B_ANN = SM_BAR + 176,
                   B_WE = SM_BAR + 192, B_KE = SM_BAR + 240, B_CE = SM_BAR + 288, B_OS = SM_BAR + 344;
constexpr uint32_t SM_EP = SM_BAR + 384;
constexpr uint32_t SM_ONE = SM_BAR + 388;
constexpr uint32_t SM_STAT = SM_BAR + 400, SM_EXT = SM_STAT + 512;
constexpr uint32_t SM_BAD = SM_EXT + 2048;
constexpr int SMEM_BYTES = SM_BAR + 3072;
__device__ __forceinline__ uint32_t c_slot(int s) { return (0xBADC10u >> (4 * s)) & 15; }

struct Params {
  const __nv_bfloat16 *x, *k, *v, *wq, *wo, *wr;
  __nv_bfloat16* out;
  Scratch* g;
};

__device__ __forceinline__ void release2(uint32_t rbar, int lane) { if (lane < 2) mbar_arrive_cluster(rbar); }
__device__ __forceinline__ void pin_after(uint32_t a, float e0, float e1) {
  asm volatile("{\n.reg .pred p;\nsetp.lt.f32 p, %1, %2;\n@p st.shared.u32 [%0], %0;\n}\n" :: "r"(a), "f"(e0), "f"(-e1) : "memory"); }
__device__ __forceinline__ void lds128_after(uint32_t& x, uint32_t& y, uint32_t& z, uint32_t& w, uint32_t a, float e0, float e1) {
  asm volatile("{\n.reg .pred p;\nsetp.geu.f32 p, %5, %6;\n@p ld.shared.v4.u32 {%0,%1,%2,%3}, [%4];\n}\n" : "+r"(x), "+r"(y), "+r"(z), "+r"(w) : "r"(a), "f"(e0), "f"(-e1) : "memory"); }
__device__ __forceinline__ uint32_t launch_of(unsigned long long ticket) { return (uint32_t)(ticket / 132) + 1; }

__device__ __forceinline__ void attn_slow(float (&o)[64], float& i0, float& i1, const __nv_bfloat16* __restrict__ X, const __nv_bfloat16* __restrict__ WQ, uint32_t st0, uint32_t st1,
                                          const __nv_bfloat16* __restrict__ K, const __nv_bfloat16* __restrict__ V, int lane) {
  uint32_t q[32];
  #pragma unroll
  for (int i = 0; i < 64; i++) o[i] = 0.f;
  const int g = lane >> 2, qd = lane & 3;
  #pragma unroll 1
  for (int k0 = 0; k0 < DM; k0 += 16) {
    uint32_t a[4];
    #pragma unroll
    for (int e = 0; e < 4; e++) {
      const uint32_t xv = *(const uint32_t*)(X + (size_t)(g + (e & 1) * 8) * DM + k0 + (e >> 1) * 8 + 2 * qd);
      const float mb = bf_lo((e & 1) ? st1 : st0);
      a[e] = pack_bf16(bf_lo(xv) - mb, bf_hi(xv) - mb);
    }
    const unsigned short* wr = (const unsigned short*)(WQ + (size_t)(k0 + 2 * qd) * (NH * DH) + g);
    #pragma unroll
    for (int nb = 0; nb < 16; nb++) {
      uint32_t b0 = (uint32_t)wr[nb * 8] | ((uint32_t)wr[nb * 8 + NH * DH] << 16);
      uint32_t b1 = (uint32_t)wr[nb * 8 + 8 * NH * DH] | ((uint32_t)wr[nb * 8 + 9 * NH * DH] << 16);
      asm volatile("mma.sync.aligned.m16n8k16.row.col.f32.bf16.bf16.f32 {%0,%1,%2,%3}, {%4,%5,%6,%7}, {%8,%9}, {%0,%1,%2,%3};"
        : "+f"(o[nb*4]), "+f"(o[nb*4+1]), "+f"(o[nb*4+2]), "+f"(o[nb*4+3]) : "r"(a[0]), "r"(a[1]), "r"(a[2]), "r"(a[3]), "r"(b0), "r"(b1));
    }
  }
  {
    const float r0 = rcp_approx(bf_hi(st0)) * SCALE_LOG2E, r1 = rcp_approx(bf_hi(st1)) * SCALE_LOG2E;
    #pragma unroll
    for (int i = 0; i < 16; i++) { q[2*i] = pack_bf16(o[4*i] * r0, o[4*i+1] * r0); q[2*i+1] = pack_bf16(o[4*i+2] * r1, o[4*i+3] * r1); }
    #pragma unroll
    for (int i = 0; i < 64; i++) o[i] = 0.f;
  }
  float m0 = -INFINITY, m1 = -INFINITY, l0 = 0.f, l1 = 0.f;
  #pragma unroll 1
  for (int n0 = 0; n0 < S_LEN; n0 += 16) {
    float s[8];
    #pragma unroll
    for (int i = 0; i < 8; i++) s[i] = 0.f;
    #pragma unroll
    for (int nb = 0; nb < 2; nb++) {
      const uint32_t* kr = (const uint32_t*)(K + (size_t)(n0 + nb * 8 + g) * DH) + qd;
      #pragma unroll
      for (int kk = 0; kk < 8; kk++) {
        uint32_t b0 = kr[kk * 8], b1 = kr[kk * 8 + 4];
        asm volatile("mma.sync.aligned.m16n8k16.row.col.f32.bf16.bf16.f32 {%0,%1,%2,%3}, {%4,%5,%6,%7}, {%8,%9}, {%0,%1,%2,%3};"
          : "+f"(s[nb*4]), "+f"(s[nb*4+1]), "+f"(s[nb*4+2]), "+f"(s[nb*4+3]) : "r"(q[kk*4]), "r"(q[kk*4+1]), "r"(q[kk*4+2]), "r"(q[kk*4+3]), "r"(b0), "r"(b1));
      }
    }
    float x0 = fmaxf(fmaxf(s[0], s[1]), fmaxf(s[4], s[5])), x1 = fmaxf(fmaxf(s[2], s[3]), fmaxf(s[6], s[7]));
    x0 = fmaxf(x0, __shfl_xor_sync(0xffffffff, x0, 1)); x1 = fmaxf(x1, __shfl_xor_sync(0xffffffff, x1, 1));
    x0 = fmaxf(x0, __shfl_xor_sync(0xffffffff, x0, 2)); x1 = fmaxf(x1, __shfl_xor_sync(0xffffffff, x1, 2));
    const float n0m = fmaxf(m0, x0), n1m = fmaxf(m1, x1);
    const float sh0 = (n0m == -INFINITY) ? 0.f : n0m, sh1 = (n1m == -INFINITY) ? 0.f : n1m;
    const float c0 = ex2(m0 - sh0), c1 = ex2(m1 - sh1);
    m0 = n0m; m1 = n1m;
    s[0] = ex2(s[0] - sh0); s[1] = ex2(s[1] - sh0); s[4] = ex2(s[4] - sh0); s[5] = ex2(s[5] - sh0);
    s[2] = ex2(s[2] - sh1); s[3] = ex2(s[3] - sh1); s[6] = ex2(s[6] - sh1); s[7] = ex2(s[7] - sh1);
    l0 = l0 * c0 + (s[0] + s[1]) + (s[4] + s[5]); l1 = l1 * c1 + (s[2] + s[3]) + (s[6] + s[7]);
    const uint32_t a0 = pack_bf16(s[0], s[1]), a1 = pack_bf16(s[2], s[3]), a2 = pack_bf16(s[4], s[5]), a3 = pack_bf16(s[6], s[7]);
    const unsigned short* vr = (const unsigned short*)(V + (size_t)(n0 + 2 * qd) * DH + g);
    #pragma unroll
    for (int nb = 0; nb < 16; nb++) {
      uint32_t b0 = (uint32_t)vr[nb * 8] | ((uint32_t)vr[nb * 8 + DH] << 16);
      uint32_t b1 = (uint32_t)vr[nb * 8 + 8 * DH] | ((uint32_t)vr[nb * 8 + 9 * DH] << 16);
      o[nb*4] *= c0; o[nb*4+1] *= c0; o[nb*4+2] *= c1; o[nb*4+3] *= c1;
      asm volatile("mma.sync.aligned.m16n8k16.row.col.f32.bf16.bf16.f32 {%0,%1,%2,%3}, {%4,%5,%6,%7}, {%8,%9}, {%0,%1,%2,%3};"
        : "+f"(o[nb*4]), "+f"(o[nb*4+1]), "+f"(o[nb*4+2]), "+f"(o[nb*4+3]) : "r"(a0), "r"(a1), "r"(a2), "r"(a3), "r"(b0), "r"(b1));
    }
  }
  l0 += __shfl_xor_sync(0xffffffff, l0, 1); l1 += __shfl_xor_sync(0xffffffff, l1, 1);
  l0 += __shfl_xor_sync(0xffffffff, l0, 2); l1 += __shfl_xor_sync(0xffffffff, l1, 2);
  i0 = rcp_approx(l0); i1 = rcp_approx(l1);
}

__device__ __forceinline__ void flag_if(uint32_t a, bool c) { asm volatile("{\n.reg .pred p;\nsetp.ne.u32 p, %1, 0;\n@p st.shared.u8 [%0], 1;\n}\n" :: "r"(a), "r"((uint32_t)c) : "memory"); }
__device__ __forceinline__ void row_scale(float& l0, float& l1, int one, uint32_t flag) {
  l0 += __shfl_xor_sync(0xffffffff, l0, one); l1 += __shfl_xor_sync(0xffffffff, l1, one);
  l0 += __shfl_xor_sync(0xffffffff, l0, 2); l1 += __shfl_xor_sync(0xffffffff, l1, 2);
  flag_if(flag, !((l0 >= 0.00390625f) && (l0 <= 1.8446744e19f) && (l1 >= 0.00390625f) && (l1 <= 1.8446744e19f)));
  l0 = rcp_fast(l0); l1 = rcp_fast(l1);
}
__device__ __forceinline__ uint32_t taint(uint32_t z, uint32_t a, uint32_t b) { asm("fma.rn.bf16x2 %0, %1, %2, %0;" : "+r"(z) : "r"(a), "r"(b)); return z; }
__device__ __forceinline__ bool tainted(uint32_t z) { return (taint(0u, z, 0u) & 0x7fff7fffu) != 0; }

__device__ __forceinline__ int kv_tile(int j) { return j < 32 ? j ^ 16 : j; }
__device__ __forceinline__ uint32_t qo_slot(int h) { return SM_QO + ((0x3102 >> (4 * h)) & 3) * 2 * U; }
__device__ __forceinline__ uint32_t o_addr(uint32_t wr, int lane) { return wr + (lane & 15) * 128 + (((lane >> 4) ^ (lane & 7)) << 4); }
template <bool CHECK> __device__ __forceinline__ uint32_t store_o(uint32_t a, const float (&o)[64], float i0, float i1) {
  uint32_t z = 0;
  #pragma unroll
  for (int i = 0; i < 8; i++) {
    const uint32_t w0 = pack_bf16(o[8*i] * i0, o[8*i+1] * i0), w1 = pack_bf16(o[8*i+2] * i1, o[8*i+3] * i1), w2 = pack_bf16(o[8*i+4] * i0, o[8*i+5] * i0), w3 = pack_bf16(o[8*i+6] * i1, o[8*i+7] * i1);
    stsm4((a ^ ((i & 3) << 5)) + (i >> 2) * U, w0, w1, w2, w3);
    if (CHECK) z = taint(taint(z, w0, w1), w2, w3);
  }
  return z;
}

__device__ __noinline__ void redo_heads(const Params& P, uint32_t sb, uint32_t bad, int row0, int head0) {
  const int lane = threadIdx.x & 31;
  const uint32_t st0 = lds32(sb + SM_STAT + ((row0 & 127) + (lane >> 2)) * 4), st1 = lds32(sb + SM_STAT + ((row0 & 127) + 8 + (lane >> 2)) * 4);
  #pragma unroll 1
  for (int h = 0; h < 4; h++) {
    if (!((bad >> (8 * h)) & 1)) continue;
    float o[64], i0, i1;
    const int head = head0 + (kv_tile(h * 16) >> 4);
    attn_slow(o, i0, i1, P.x + (size_t)row0 * DM, P.wq + head * DH, st0, st1, P.k + (size_t)head * S_LEN * DH, P.v + (size_t)head * S_LEN * DH, lane);
    store_o<false>(o_addr(sb + (row0 & 127) * 128, lane) + qo_slot(h), o, i0, i1);
  }
}

template <int K> struct IC { static constexpr int v = K; };
template <int K, int N, class F> __device__ __forceinline__ void static_for(F&& f) { if constexpr (K < N) { f(IC<K>{}); static_for<K + 1, N>(f); } }
template <uint32_t OFF, int SITE> __device__ __forceinline__ void mma_qk(float (&s)[64], const uint32_t (&q)[32], uint64_t d0) {
  wg_fence();
  static_for<0, 8>([&](auto kc) { constexpr int k = decltype(kc)::v; wgmma_rs<doff(OFF, 16) - SITE + (k / 4) * 1024 + (k % 4) * 2>(s, q[k*4], q[k*4+1], q[k*4+2], q[k*4+3], d0, k > 0); });
  wg_commit();
}
template <uint32_t OFF, int SITE> __device__ __forceinline__ void mma_pv(float (&o)[64], const uint32_t (&p)[32], uint64_t d0, bool keep) {
  wg_fence();
  static_for<0, 8>([&](auto kc) { constexpr int k = decltype(kc)::v; wgmma_rs_tb<doff(OFF, U) - SITE + k * 128>(o, p[k*4], p[k*4+1], p[k*4+2], p[k*4+3], d0, (k > 0) || keep); });
  wg_commit();
}
template <int I0, int I1>
__device__ __forceinline__ void exp_rows(float (&s)[64], float (&l)[2]) {
  #pragma unroll
  for (int i = I0; i < I1; i += 2) {
    s[i] = ex2(s[i]); s[i+1] = ex2(s[i+1]);
    l[(i >> 1) & 1] += s[i] + s[i+1];
  }
}

template <int KS, bool EDGE>
__device__ __forceinline__ void attn_step(uint32_t sb, uint32_t rb, uint32_t wr, uint32_t qa, int wg, int lane, int j, int ph, float (&s)[64], float (&o)[64], uint32_t (&p)[32], uint32_t (&q)[32],
                                          float (&l)[2], bool& ready, Scratch* g, unsigned (&tz)[3]) {
  constexpr bool FIRST = EDGE && !KS, LAST = EDGE && KS;
  TRACEF(2, wg, 32 + j);
  STALL(1);
  if (!ready) mbar_wait(sb + B_KF + KS * 8, ph);
  bar_sync(1 + wg, 256);
  mma_qk<KS * SM_K1, EDGE>(s, q, desc(sb, EDGE));
  if (!ready) mbar_wait(sb + B_KF + 24 - KS * 8, KS ? ph : ph ^ 1);
  mma_pv<SM_V + (1 - KS) * 2 * U, EDGE>(o, p, desc(sb, EDGE), !KS || LAST || ((j & 15) != 1));
  bar_arrive(1 + (wg ^ 1), 256);
  const int one = FIRST ? lds32(sb + SM_ONE) : 1;
  wg_wait<1>();
  fence_regs(s);
  release2(rb + B_KE + KS * 8, lane);
  float i0 = l[0], i1 = l[1];
  if (FIRST) { row_scale(i0, i1, one, sb + SM_BAD - 1 + ((wr - sb) >> 9) + (j >> 4)); l[0] = fminf(i0, 0.f); l[1] = fminf(i1, 0.f); }
  constexpr int DP = FIRST ? DPOSF : (LAST && DPOS < 7 * QSP ? 7 * QSP : DPOS);
  if (LAST) {
    fence_regs(q);
    const uint32_t a = qa + qo_slot(j >> 4);
    static_for<0, 8>([&](auto ic) { constexpr int i = decltype(ic)::v;
      lds128_after(q[4*i], q[4*i+1], q[4*i+2], q[4*i+3], a + (i >> 2) * U + (i & 3) * 512, l[0], l[1]);
      exp_rows<i * QSP, i < 7 ? (i + 1) * QSP : DP>(s, l);
    });
  } else exp_rows<0, DP>(s, l);
  pin_after(sb + SM_BAD, l[0], l[1]);
  exp_rows<DP, 64>(s, l);
  wg_wait<0>();
  fence_regs(o); fence_regs(p);
  release2(rb + B_KE + 24 - KS * 8, lane);
  ready = mbar_test2(sb + B_KF + 16 + KS * 8, ph, sb + B_KF + 8 - KS * 8, KS ? ph ^ 1 : ph);
  if (FIRST) {
    const int h = (j >> 4) - 1;
    store_o<false>(o_addr(wr, lane) + qo_slot(h), o, i0, i1);
    if (lane == 0) mbar_arrive(sb + B_OS + h * 8);
  }
  #pragma unroll
  for (int i = 0; i < 32; i++) p[i] = pack_bf16(s[2*i], s[2*i+1]);
}

template <int SITE> __device__ __forceinline__ void mma_c(float (&acc)[64], uint32_t sb, int slot, int h, int arrive_bar) {
  const uint64_t a = desc(sb, c_slot(slot) * 1024 + SITE), b = desc(sb, h * 2048 + SITE);
  wg_fence();
  static_for<0, 8>([&](auto kc) { constexpr int k = decltype(kc)::v;
    wgmma_ss_ta<doff(0, 16) - SITE + k * 128, doff(SM_QO, 16) - SITE + (k >> 2) * 1024 + (k & 3) * 2>(acc, a, b, k > 0 || h > 0);
  });
  wg_commit();
  if (arrive_bar) bar_arrive(arrive_bar, 256);
}

__device__ __forceinline__ void side_cta(const Params& P, const CUtensorMap* tmX, const CUtensorMap* tmW, const CUtensorMap* tmG, const CUtensorMap* tmU,
                                         const CUtensorMap* tmD, uint32_t sb, int m) {
  const int tid = threadIdx.x, warp = __shfl_sync(0xffffffff, tid >> 5, 0), lane = tid & 31;
  const uint32_t XS = sb + 12 * U, HS = XS + 10240, BF = sb + SM_BAR, BE = BF + 96, XF = BE + 96, XE = XF + 32, BW = XE + 32, SEL = BW + 16, KEY = SEL + 64;
  Scratch* const g = P.g;
  const int nj = m < 3 ? 14 : 12, nd = m < 3 ? 4 : 3, f0 = m * 448;
  if (elect_one()) { mbar_init(BF + warp * 8, 1); mbar_init(BE + warp * 8, 4); if (warp < 9) mbar_init(XF + warp * 8, (warp & 4) ? 8 : 1); }
  if (tid == 32) sts32(SEL + 32, launch_of(atomicAdd(&g->ticket, 1ull)));
  __syncthreads();
  const uint32_t launch = lds32(SEL + 32);
  if (warp == 0) {
    if (elect_one()) {
      mbar_expect_tx(BW, 10 * U);
      #pragma unroll 1
      for (int i = 0; i < 10; i++) tma_load_2d(sb + i * U, tmW, BW, m * 1024 + (i < 5 ? 448 : 960), (i < 5 ? i : i - 5) * 128);
    }
    #pragma unroll 1
    for (int n = 0, qt = 0, c = 0; n < 160; n++) {
      const uint32_t bar = XF + (n & 3) * 8;
      mbar_wait(bar + 32, ((n >> 2) & 1) ^ 1);
      if (elect_one()) {
        mbar_expect_tx(bar, U);
        tma_load_2d(sb + (10 + (n & 3)) * U, tmX, bar, c * 64, qt * 128);
        if (c == 0 && qt < 15) l2_prefetch(P.x + (size_t)(qt * 128 + 128 + m * 32) * DM, 32 * DM * 2);
      }
      if (++c == 10) { c = 0; qt++; }
    }
  } else if (warp < 3) {
    #pragma unroll 1
    for (int qt = 0; qt < 16; qt++) {
      bar_sync(1 + warp, 160);
      if (lane == 0) flag_add_release(&g->q3_done[m].v);
      __syncwarp();
    }
  } else if (warp >= 4) {
    float acc[64], cs[32];
    mbar_wait(BW, 0);
    #pragma unroll 1
    for (int c = 0; c < 10; c++) {
      wg_fence();
      static_for<0, 4>([&](auto kc) { constexpr int k = decltype(kc)::v;
        wgmma_rs_tb<doff(0, 5 * U) + k * 128>(acc, 0x3f803f80u, 0x3f803f80u, 0x3f803f80u, 0x3f803f80u, desc(sb, c * 512), k || c); });
      wg_commit();
      wg_wait<0>();
    }
    fence_regs(acc);
    #pragma unroll
    for (int i = 0; i < 32; i++) cs[i] = -acc[(i >> 1) * 4 + (i & 1)];
    fence_regs(cs);
    #pragma unroll 1
    for (int qt = 0, n = 0; qt < 16; qt++) {
      const uint32_t* const sp = g->stat + qt * 128 + (warp - 4) * 16 + (lane >> 2);
      uint32_t st0, st1;
      #pragma unroll 1
      for (int c = 0; c < 10; c++, n++) {
        const uint64_t a = desc(sb, (n & 3) * 1024 + (warp >> 3) * 512), b = desc(sb, c * 512);
        mbar_wait(XF + (n & 3) * 8, (n >> 2) & 1);
        wg_fence();
        static_for<0, 4>([&](auto kc) { constexpr int k = decltype(kc)::v; wgmma_ss_tb<doff(10 * U, 16) + k * 2, doff(0, 5 * U) + k * 128>(acc, a, b, k || c); });
        wg_commit();
        if (c == 9) { st0 = ldg32(sp); st1 = ldg32(sp + 8); }
        wg_wait<1>();
        if (c && lane == 0) mbar_arrive(XE + ((n - 1) & 3) * 8);
      }
      #pragma unroll 1
      for (int it = 0; __any_sync(0xffffffff, tag_miss(st0, st1, launch << 31) >> 31) && it < MAXPOLL; it++) { st0 = ldg32(sp); st1 = ldg32(sp + 8); }
      st0 &= 0x7fffffffu; st1 &= 0x7fffffffu;
      const float rs[2] = {rcp_fast(bf_hi(st0)) * SCALE_LOG2E, rcp_fast(bf_hi(st1)) * SCALE_LOG2E}, nm[2] = {bf_lo(st0), bf_lo(st1)};
      wg_wait<0>();
      fence_regs(acc);
      if (lane == 0) mbar_arrive(XE + ((n - 1) & 3) * 8);
      STALL(7);
      uint4* const dst = g->q3 + (qt * 8 + m * 2) * 1024 + (warp - 4) * 128 + lane;
      #pragma unroll
      for (int e = 0; e < 8; e++) {
        uint32_t w[4];
        #pragma unroll
        for (int i = 0; i < 4; i++)
          w[i] = pack_bf16(fmaf(nm[i & 1], cs[4*e + (i & 2)], acc[8*e + 2*i]) * rs[i & 1], fmaf(nm[i & 1], cs[4*e + (i & 2) + 1], acc[8*e + 2*i + 1]) * rs[i & 1]);
        dst[(e >> 2) * 1024 + (e & 3) * 32] = make_uint4(w[0], w[1], w[2], w[3]);
      }
      bar_sync(1 + (warp >> 2), 160);
    }
  }
  if (tid == 96) flag_wait(&g->cnt_gate.v, launch * 256);
  __syncthreads();
  TRACE(0, 1);
  if (tid >= 256 && tid < 320) sts128(HS + 3072 + tid * 16, 0, 0, 0, 0);
  if (warp < 4) {
    uint4 k4[4];
    #pragma unroll
    for (int i = 0; i < 4; i++) k4[i] = ld_relaxed4(g->key + warp * 512 + i * 128 + lane * 4);
    uint32_t bound = 0;
    #pragma unroll 1
    for (int c = 0; c < TOPC; c++) {
      uint32_t b = 0;
      #pragma unroll
      for (int i = 0; i < 4; i++) b = max(max(max(b, k4[i].x - bound), k4[i].y - bound), max(k4[i].z - bound, k4[i].w - bound));
      bound += __reduce_max_sync(0xffffffff, b);
      if (lane == 0) sts32(KEY + (warp * TOPC + c) * 4, bound);
    }
    bar_sync(1, 128);
    const uint32_t v = lds32(KEY + lane * 4);
    int n = 0;
    #pragma unroll 1
    for (int j = 0; j < 32; j++) n += __shfl_sync(0xffffffff, v, j) > v;
    if (n < TOPC) sts32(SEL + n * 4, v);
  }
  __syncthreads();
  #pragma unroll 1
  for (int i = tid; i < TOPC * 80; i += 384) {
    const int row = 0xffff - (lds32(SEL + (i & 7) * 4) & 0xffff);
    const uint32_t st = ldg32(g->stat + row), m2 = __byte_perm(st, 0, 0x1010);
    const float rsd = rcp_fast(bf_hi(st & 0x7fffffffu));
    const uint4 v = ldg_nc((const uint4*)(P.x + (size_t)row * DM) + (i >> 3));
    sts128(XS + i * 16, norm2(v.x, m2, rsd), norm2(v.y, m2, rsd), norm2(v.z, m2, rsd), norm2(v.w, m2, rsd));
  }
  proxy_fence();
  __syncthreads();
  TRACE(0, 2);
  uint32_t sl = 0, ph = 0;
  if (warp == 0) {
    #pragma unroll 1
    for (int job = 0; job < nj + 10; job++) {
      const bool up = job < nj;
      #pragma unroll 1
      for (int i = 0; i < (up ? 5 : nd); i++) {
        mbar_wait(BE + sl * 8, ph ^ 1);
        if (elect_one()) {
          mbar_expect_tx(BF + sl * 8, U);
          tma_load_2d(sb + sl * U, up ? ((job & 1) ? tmU : tmG) : tmD, BF + sl * 8, up ? f0 + (job >> 1) * 64 : (job - nj) * 64, (up ? 0 : f0) + i * 128);
        }
        if (++sl == 12) { sl = 0; ph ^= 1; }
      }
    }
  } else if ((warp >> 2) == 1) {
    float gs[4];
    #pragma unroll 1
    for (int job = 0; job < nj + 10; job++) {
      const bool up = job < nj;
      if (job == nj) { proxy_fence(); bar_sync(1, 128); }
      float ac[4][4], acc[4];
      uint32_t prev = 0;
      #pragma unroll 1
      for (int i = 0; i < (up ? 5 : nd); i++) {
        const uint64_t a = desc(sb, sl * 1024 + 0x10000), b = (uint64_t)(desc_lo(up ? XS : HS, 128) + i * 128) | (8ull << 32);
        mbar_wait(BF + sl * 8, ph);
        wg_fence();
        static_for<0, 8>([&](auto kc) { constexpr int k = decltype(kc)::v; wgmma_ss_ta<k * 128, k * 16>(ac[k & 3], a, b, k > 3 || i > 0); });
        wg_commit();
        wg_wait<1>();
        if (i && lane == 0) mbar_arrive(prev);
        prev = BE + sl * 8;
        if (++sl == 12) { sl = 0; ph ^= 1; }
      }
      wg_wait<0>();
      if (lane == 0) mbar_arrive(prev);
      #pragma unroll
      for (int e = 0; e < 4; e++) fence_regs(ac[e]);
      #pragma unroll
      for (int e = 0; e < 4; e++) acc[e] = (ac[0][e] + ac[1][e]) + (ac[2][e] + ac[3][e]);
      STALL(9);
      const int f = (warp & 3) * 16 + (lane >> 2), tk = (lane & 3) * 2;
      if (!up) {
        float* y = g->ypart + (m * DM + (job - nj) * 64 + f) * TOPC + tk;
        *(float2*)y = make_float2(acc[0], acc[1]); *(float2*)(y + 8 * TOPC) = make_float2(acc[2], acc[3]);
      } else {
        #pragma unroll
        for (int e = 0; e < 4; e++) {
          const float z = rbf(acc[e]);
          if (job & 1) asm volatile("st.shared.u16 [%0], %1;" :: "r"(HS + (job >> 1) * 1024 + ((f >> 3) + (e >> 1)) * 128 + (tk + (e & 1)) * 16 + (f & 7) * 2), "h"((uint16_t)pack_bf16(gs[e] * z, 0.f)) : "memory");
          gs[e] = rbf(z * sigmoid_f(z));
        }
      }
    }
  }
  __syncthreads();
  TRACE(0, 3);
  if (tid == 0) { flag_add_release(&g->cnt_mod.v); flag_wait(&g->cnt_mod.v, launch * 4, 50); }
  __syncthreads();
  #pragma unroll 1
  for (int i = tid; i < 2 * DM; i += 384) {
    const int t = 2 * m + (i & 1), col = i >> 1;
    const uint32_t key = lds32(SEL + t * 4);
    const float* yp = g->ypart + col * TOPC + t;
    const float y = rbf((__ldcg(yp) + __ldcg(yp + TOPC * DM)) + (__ldcg(yp + 2 * TOPC * DM) + __ldcg(yp + 3 * TOPC * DM)));
    const float rs = rbf(sigmoid_f(bf_hi((key >> 31) ? key & 0x7fffffffu : ~key)));
    const uint32_t xn = lds32(XS + (col >> 3) * 128 + t * 16 + (col & 6) * 2);
    const float z = rbf(((col & 1) ? bf_hi(xn) : bf_lo(xn)) + rbf(y * rs));
    g->gate[(size_t)(0xffff - (key & 0xffff)) * DM + col] = __float2bfloat16_rn(z * sigmoid_f(z));
  }
  __syncthreads();
  if (tid == 0) flag_add_release(&g->mod_done.v);
  TRACE(0, 4);
}

__global__ void __cluster_dims__(2, 1, 1) __launch_bounds__(384, 1) fused_kernel(const __grid_constant__ CUtensorMap tmX, const __grid_constant__ CUtensorMap tmW4,
    const __grid_constant__ CUtensorMap tmW3, const __grid_constant__ CUtensorMap tmW1,
    const __grid_constant__ CUtensorMap tmK, const __grid_constant__ CUtensorMap tmV, const __grid_constant__ CUtensorMap tmWO,
    const __grid_constant__ CUtensorMap tmG, const __grid_constant__ CUtensorMap tmU, const __grid_constant__ CUtensorMap tmD,
    const __grid_constant__ CUtensorMap tmGate, const __grid_constant__ Params P) {
  extern __shared__ __align__(1024) uint8_t smem_raw[];
  const uint32_t sb = smem_u32(smem_raw);
  const int tid = threadIdx.x, lane = tid & 31;
  const int rank = blockIdx.x & 1, cl = blockIdx.x >> 1;
  if (cl >= 64) {
    side_cta(P, &tmX, &tmW1, &tmG, &tmU, &tmD, sb, blockIdx.x & 3);
    return;
  }
  const int rr = ((cl - 36) * 37) >> 8, kk = cl - 36 - rr * 7, qp = sel_lt(cl, 4, PH, sel_lt(cl, 36, (cl - 4) & 7, kk + sel_lt(kk, PH, 0, 1)));
  const int hg = sel_lt(cl, 4, cl + 4, sel_lt(cl, 36, (cl - 4) >> 3, 4 + rr)), qt = qp * 2 + rank;
  const int warp = __shfl_sync(0xffffffff, tid >> 5, 0), wgi = warp >> 2;
  Scratch* const g = P.g;
  if (elect_one()) {
    #pragma unroll
    for (int i = 0; i < 4; i++) mbar_init(sb + SM_BAR + warp * 32 + i * 8, 1 << ((0x333444000000ull >> (4 * warp)) & 7));
    if (warp == 0) {
      mbar_expect_tx(sb + B_WF, 2 * U);
      tma_load_2d(sb + 2 * U, &tmX, sb + B_WF, 0, qt * 128);
      tma_load_3d(sb + SM_W, &tmW4, sb + B_WF, 0, 0, hg * 8);
      tma_load_3d(sb + SM_W + 8192, &tmW4, sb + B_WF, 0, 16, hg * 8);
    }
    asm volatile("fence.mbarrier_init.release.cluster;" ::: "memory");
  }
  __syncwarp();
  cluster_arrive();
  unsigned long long ticket = 0;
  if (tid == 64) asm volatile("atom.relaxed.gpu.global.add.u64 %0, [%1], 1;" : "=l"(ticket) : "l"(&g->ticket) : "memory");
  cluster_wait();
  if (warp == 0 && elect_one()) {
    #pragma unroll
    for (int i = 1; i < 6; i++) {
      mbar_expect_tx(sb + B_WF + i * 8, (i & 1) ? U : 2 * U);
      tma_load_3d_mc(sb + SM_W + i * U + rank * 8192, &tmW4, sb + B_WF + i * 8, 0, i * 32 + rank * 16, hg * 8);
      if (!(i & 1)) tma_load_2d(sb + (2 + i / 2) * U, &tmX, sb + B_WF + i * 8, i * 32, qt * 128);
    }
  }
  STALL(14);
  if (wgi == 0) {
    asm volatile("setmaxnreg.dec.sync.aligned.u32 56;");
    uint32_t w0 = 0;
    if (warp == 1 || warp == 2) {
      if (warp == 2 && lane < 12) sts128(sb + SM_EXT + 1024 + (lane >= 6 ? 1024 - 96 : 0) + lane * 16, 0, 0, 0, 0);
      __syncwarp();
      if (tid == 64) { sts32(sb + SM_ONE, 1); sts32(sb + SM_EP, launch_of(ticket)); mbar_arrive(sb + B_EP); }
      __syncwarp();
      mbar_pace(sb + B_WF, 0);
      TRACEO(1);
      auto warm = [&](int ps, int i0, int i1) {
        const uint32_t o = (((qt >> 2) * 4 + (lane & 3) + (lane >> 2) * 16) * (NH * DH) + hg * 512 + ps * 256 + (qt & 3) * 64) * 2;
        #pragma unroll 1
        for (int i = i0; i < i1; i++) {
          asm volatile("prefetch.global.L2 [%0];" :: "l"(at<char>(P.wq, o + i * 256 * (NH * DH))) : "memory");
          if (ps) __nanosleep(W1SL);
        }
      };
      if (elect_one()) l2_prefetch(P.x + (size_t)(qt * 128 + hg * 16 + warp * 8 - 6) * DM, 6 * DM * 2);
      if (warp == 1) warm(0, 1, 5);
      auto publish = [&](uint32_t w) { if (!(lane & 12)) st_relaxed(at<uint32_t>(g->stat, (qt * 128 + hg * 16 + (warp - 1) * 8 + (lane & 3) * 2 + (lane >> 4)) * 4), w ^ (lds32(sb + SM_EP) << 31)); };
      mbar_wait(sb + B_EP, 0);
      publish(0x80000000u);
      const int r0 = qt * 128 + hg * 16 + (warp - 1) * 8 + (lane >> 4);
      const uint32_t e = r0 * DM * 2 + (lane & 15) * 16;
      uint4 vn[5];
      #pragma unroll
      for (int i = 0; i < 5; i++) vn[i] = ldg_nc(at<uint4>(P.x, e) + i * 16);
      #pragma unroll 1
      for (int it = 0; it < 4; it++) {
        uint4 v[5];
        #pragma unroll
        for (int i = 0; i < 5; i++) { v[i] = vn[i]; if (it < 3) vn[i] = ldg_nc(at<uint4>(P.x, e + (it + 1) * 2560) + i * 16); }
        const float x0 = bf_lo(__shfl_sync(0xffffffff, v[0].x, lane & 16));
        float m1 = 0.f, s1 = 0.f;
        #pragma unroll
        for (int i = 0; i < 5; i++) {
          const uint32_t vw[4] = {v[i].x, v[i].y, v[i].z, v[i].w};
          #pragma unroll
          for (int k = 0; k < 4; k++) { const float d0 = bf_lo(vw[k]) - x0, d1 = bf_hi(vw[k]) - x0; m1 += d0 + d1; s1 = fmaf(d0, d0, fmaf(d1, d1, s1)); }
        }
        #pragma unroll
        for (int o = 8; o; o >>= 1) { m1 += __shfl_xor_sync(0xffffffff, m1, o); s1 += __shfl_xor_sync(0xffffffff, s1, o); }
        const float md = m1 * (1.f / DM), var = fmaxf(fmaf(-md, md, s1 * (1.f / DM)), 0.f);
        if ((lane & 15) == it) w0 = pack_bf16(x0 + md, sqrt_approx(rbf(rbf(var) + 1e-5f)));
      }
      STALL(5);
      publish(w0 & 0x7fffffffu);
      TRACE1(2, 8);
      if (warp == 1 && W1SL) warm(1, 0, 5);
    }
        if (warp >= 2) {
      const int ps = 3 - warp;
      {
        const uint4* src = at<uint4>(P.wq, (((qt >> 2) * 4 + (lane >> 3)) * (NH * DH) + hg * 512 + ps * 256 + (qt & 3) * 64 + (lane & 7) * 8) * 2);
        const uint32_t mine = ((hg * 2 + ps) * 256 + qt * 16 + (lane & 7) * 2 + (lane >> 4)) * 16;
        float cs[8];
        #pragma unroll
        for (int e = 0; e < 8; e++) cs[e] = 0.f;
        #pragma unroll 1
        for (int b = 0; b < 40 / CSB; b++, src += CSB * 16 * 512) {
          uint4 w[CSB];
          #pragma unroll
          for (int i = 0; i < CSB; i++) w[i] = ldg_nc(src + i * 16 * 512);
          #pragma unroll
          for (int i = 0; i < CSB; i++) add8(cs, w[i]);
          if (b == 0) {
            mbar_wait(sb + B_EP, 0);
            if (!(lane & 8)) st_tagged(at<uint4>(g->cs, mine), ~lds32(sb + SM_EP) & 1, 0, 0, 0);
          }
        }
        #pragma unroll
        for (int e = 0; e < 4; e++) {
          cs[e] = ((lane & 16) ? cs[e + 4] : cs[e]) + __shfl_xor_sync(0xffffffff, (lane & 16) ? cs[e] : cs[e + 4], 16);
          cs[e] += __shfl_xor_sync(0xffffffff, cs[e], 8);
        }
        STALL(6);
        mbar_wait(sb + B_EP, 0);
        const uint32_t tm = 0u - (lds32(sb + SM_EP) & 1);
        const uint4* const gc = at<uint4>(g->cs, ((hg * 2 + ps) * 256 + lane) * 16);
        if (!(lane & 8)) st_tagged(at<uint4>(g->cs, mine), (__float_as_uint(cs[0]) & ~1u) | (tm & 1), __float_as_uint(cs[1]), __float_as_uint(cs[2]), __float_as_uint(cs[3]));

        uint4 v[9];
        int it = 0;
        uint32_t miss;
        do {
          #pragma unroll
          for (int i = 0; i < 8; i++) v[i] = ld_tagged(gc + i * 32);
          v[8] = ld_relaxed4(at<uint4>(g->stat, qt * 512 + lane * 16));
          miss = (tag_miss(v[8].x, v[8].y, tm) | tag_miss(v[8].z, v[8].w, tm)) >> 31;
          #pragma unroll
          for (int i = 0; i < 8; i += 2) miss |= tag_miss(v[i].x, v[i+1].x, tm);
        } while (__any_sync(0xffffffff, miss & 1) && ++it < MAXPOLL);
        #pragma unroll
        for (int i = 0; i < 2; i++) {
          auto sum = [](uint32_t a, uint32_t b, uint32_t c, uint32_t d) { return (__uint_as_float(a) + __uint_as_float(b)) + (__uint_as_float(c) + __uint_as_float(d)); };
          const float c0 = sum(v[i].x, v[i+2].x, v[i+4].x, v[i+6].x), c1 = sum(v[i].y, v[i+2].y, v[i+4].y, v[i+6].y);
          const float c2 = sum(v[i].z, v[i+2].z, v[i+4].z, v[i+6].z), c3 = sum(v[i].w, v[i+2].w, v[i+4].w, v[i+6].w);
          const uint32_t h0 = pack_bf16(c0, c1), h1 = pack_bf16(c2, c3), a = sb + SM_EXT + ps * 1024 + i * 512 + (lane >> 1) * 32 + (lane & 1) * 8;
          asm volatile("st.shared.v2.u32 [%0], {%1,%2};" :: "r"(a), "r"(h0), "r"(h1) : "memory");
          asm volatile("st.shared.v2.u32 [%0], {%1,%2};" :: "r"(a + 16), "r"(pack_bf16(c0 - bf_lo(h0), c1 - bf_hi(h0))), "r"(pack_bf16(c2 - bf_lo(h1), c3 - bf_hi(h1))) : "memory");
        }
        sts128(sb + SM_STAT + lane * 16, v[8].x & 0x7fffffffu, v[8].y & 0x7fffffffu, v[8].z & 0x7fffffffu, v[8].w & 0x7fffffffu);
        proxy_fence();
        __syncwarp();
        if (lane == 0) mbar_arrive(sb + B_EXT + ps * 8);
        TRACE1(2, 6 + ps);
        if (elect_one()) l2_prefetch(at<char>(ps ? P.v : P.k, ((hg * 4 + 1) * S_LEN + qt * (16 + 8 * KVPF)) * DH * 2), 4096 + 2048 * KVPF);
      }
    }
    if (warp == 1 || warp == 2) {
      int j = 0;
      const int r0 = qt * 128 + hg * 16 + (warp - 1) * 8 + (lane >> 4);
      uint32_t e = r0 * DM * 2 + (lane & 15) * 16;
      uint4 xn = ldg_nc(at<uint4>(P.x, e)), wn = ldg_nc(at<uint4>(P.wr, (lane & 15) * 16));
      #pragma unroll 1
      for (int it = 0; it < 4; it++) {
        const uint32_t st = __shfl_sync(0xffffffff, w0, (lane & 16) + it), m2 = __byte_perm(st, 0, 0x1010);
        const float rsd = rcp_fast(bf_hi(st));
        float a = 0.f;
        #pragma unroll 1
        for (int i = 0; i < 5; i++) {
          #pragma unroll 1
          do { mbar_pace(sb + B_KE + (j & 1) * 8, (j >> 1) & 1); j++; } while (j < 3 || (j >= 15 && j < 20));
          STALL(8);
          uint32_t z[4] = {xn.x, xn.y, xn.z, xn.w};
          const uint32_t ww[4] = {wn.x, wn.y, wn.z, wn.w}, en = e + (i < 4 ? 256 : (it < 3 ? 1536 : 0));
          xn = ldg_nc(at<uint4>(P.x, en)); wn = ldg_nc(at<uint4>(P.wr, (i < 4 ? i * 256 + 256 : 0) + (lane & 15) * 16));
          #pragma unroll
          for (int k = 0; k < 4; k++) {
            const uint32_t n = norm2(z[k], m2, rsd);
            const float lo = bf_lo(n), hi = bf_hi(n);
            a = fmaf(lo, bf_lo(ww[k]), fmaf(hi, bf_hi(ww[k]), a));
            z[k] = pack_bf16(lo * sigmoid_f(lo), hi * sigmoid_f(hi));
          }
          stg128(at<uint4>(g->gate, e), make_uint4(z[0], z[1], z[2], z[3]));
          e = en;
        }
        #pragma unroll
        for (int o = 8; o; o >>= 1) a += __shfl_xor_sync(0xffffffff, a, o);
        uint32_t u = pack_bf16(a, 0.f);
        if (u == 0x8000u) u = 0;
        u = (u & 0x8000u) ? (~u & 0xffffu) : (u | 0x8000u);
        if (!(lane & 15)) st_relaxed(at<uint32_t>(g->key, (r0 + it * 2) * 4), (u << 16) | (uint32_t)(0xffff - r0 - it * 2));
      }
      __syncwarp();
      if (lane == 0) flag_add_release(&g->cnt_gate.v);
      TRACE1(2, 9);
    }
    if (warp == 0) {
      const int row0 = hg * 4 * S_LEN;
      uint32_t s = 0, ph = 0;
      #pragma unroll 1
      for (int c = 3; c < 20; c++) {
        const int k = (c < 10 ? c : (c < 18 ? c - 8 : c - 18)) * 64, cb = hg * 8 + (c < 10 ? 0 : 4);
        const CUtensorMap* const tm = c < 10 ? &tmW4 : &tmW3;
        const uint32_t wb = c < 10 ? U : 12288;
        const bool wx = c < 10 || (c >= XRC && c < XRC + 2);
        const uint32_t bar = sb + B_WF + s * 8, dst = sb + SM_W + rank * 8192 + s * U;
        mbar_wait(bar + (B_WE - B_WF), ph);
        if (elect_one()) {
          mbar_expect_tx(bar, wx ? wb + U : wb);
          tma_load_3d_mc(dst, tm, bar, 0, k + rank * 16, cb);
          if (wx) tma_load_2d(sb + (c < 10 ? (c + 2) & 7 : c + 4 - XRC) * U, &tmX, bar, c < 10 ? k : (c - XRC) * 64, qt * 128);
        }
        mbar_wait(bar + (B_WE - B_WF) + 8, ph);
        if (elect_one()) {
          mbar_expect_tx(bar + 8, wb);
          tma_load_3d_mc(dst + U, tm, bar + 8, 0, k + 32 + rank * 16, cb);
        }
        s += 2;
        if (s == 6) { s = 0; ph ^= 1; }
      }
      #pragma unroll 1
      for (int i = 0; i < 128; i++) {
        const int isv = i < 5 ? (i >> 1) & 1 : (i < 127 ? ~i & 1 : 1), j = i < 4 ? i & 1 : (i + 1 - 2 * isv) >> 1;
        const uint32_t b = isv * 16 + (j & 1) * 8;
        STALL(11);
        if (i) mbar_wait(sb + (i < 4 ? B_WE + ((0x3150 >> (4 * i)) & 7) * 8 : B_KE + b), i < 4 ? i < 2 : (~j >> 1) & 1);
        if (elect_one()) {
          mbar_expect_tx(sb + B_KF + b, 2 * U);
          tma_load_2d_mc(sb + (isv ? SM_V + (j & 1) * 2 * U : (j & 1) * SM_K1) + rank * U, isv ? &tmV : &tmK, sb + B_KF + b, rank * 64, row0 + kv_tile(j) * 128);
          if (GSYNC && i == 125) mbar_arrive(sb + B_ANN);
        }
        if (i == 4) TRACEO(3);
      }
      s = 0; ph = 1;
      #pragma unroll 1
      for (int n = 0; n < (X_SKIP(qp) ? 2 : 40); n++) {
        const int st = n < 5 ? (n == 1) : n >> 2, h = n < 5 ? max(n - 1, 0) : n & 3;
        const int u = st < 2 ? 8 + st : ((hg + st - 1) & 7);
        STALL(12);
        mbar_wait(sb + (n < 6 ? B_KE + (n < 4 ? n >> 1 : 3) * 8 : B_CE + s * 8), ph);
        if (elect_one()) {
          mbar_expect_tx(sb + B_CF + s * 8, U);
          tma_load_2d_mc(sb + c_slot(s) * U + rank * 8192, &tmWO, sb + B_CF + s * 8, u * 64, hg * 512 + ((0x3120 >> (4 * h)) & 3) * 128 + rank * 64);
        }
        if (n == 3) TRACEO(4);
        if (++s == 6) { s = 0; ph ^= 1; }
      }
      mbar_wait(sb + B_GATE, 0);
      asm volatile("fence.proxy.async.global;" ::: "memory");
      #pragma unroll 1
      for (int n = 0; n < (X_SKIP(qp) ? 0 : 2); n++) {
        mbar_wait(sb + B_CE + 32 + n * 8, 1);
        if (elect_one()) {
          mbar_expect_tx(sb + B_CF + 32 + n * 8, U);
          tma_load_2d(sb + (10 + n) * U, n ? &tmGate : &tmX, sb + B_CF + 32 + n * 8, hg * 64, qt * 128);
        }
      }
      if (!X_SKIP(qp)) {
        const uint4* const last = g->part + (size_t)((qt * 8 + hg) * 9 + 8) * 1024;
        mbar_wait(sb + B_CE + P8, 0);
        if (elect_one()) {
          mbar_expect_tx(sb + B_CF + 8, U);
          bulk_load(sb + U, last, U, sb + B_CF + 8);
        }
      }
    } else if (warp == 2) {
      #pragma unroll 1
      for (int h = 0; h < 4; h++) {
        mbar_wait(sb + B_OS + h * 8, 0);
        STALL(13);
        #pragma unroll 1
        for (int i = 0; i < (h < 3 ? 16 : 0); i++) {
          uint32_t z = 0;
          #pragma unroll
          for (int k = 0; k < 4; k++) { const uint4 v = lds128(sb + qo_slot(h) + i * 2048 + k * 512 + lane * 16); z = taint(taint(z, v.x, v.y), v.z, v.w); }
          flag_if(sb + SM_BAD + (i & 7) * 4 + h, tainted(z));
        }
        if (GSYNC && h == 2) {
          const uint32_t launch = lds32(sb + SM_EP);
          uint32_t* const mine = at<uint32_t>(g->near, (qt * 8 + hg) * 32 + (lane & 7) * 4);
          st_relaxed(mine, launch - 1);
          mbar_wait(sb + B_ANN, 0);
          mbar_wait(sb + B_KE, 1);
          st_relaxed(mine, launch);
          #pragma unroll 1
          for (int it = 0; __any_sync(0xffffffff, ldg32(at<uint32_t>(g->near, qp * 512 + lane * 16)) != launch) && it < MAXPOLL; it++) {}
        }
        __syncwarp();
        if (h >= 2) { proxy_fence(); if (elect_one()) mbar_arrive(sb + B_OF); }
        __syncwarp();
      }
    } else if (!elect_one()) {
    } else if (warp == 1) {
      mbar_wait(sb + B_OS + 8, 0);
      flag_wait(at<unsigned>(g->q3_done, (hg >> 1) * 128), lds32(sb + SM_EP) * 32 + qt * 2 - 30);
      asm volatile("fence.proxy.async.global;" ::: "memory");
      mbar_expect_tx(sb + B_Q3, U);
      bulk_load(sb + 5 * U, g->q3 + (qt * 8 + hg) * 1024, U, sb + B_Q3);
      flag_wait(&g->mod_done.v, lds32(sb + SM_EP) * 4);
      mbar_arrive(sb + B_GATE);
    } else {
      #pragma unroll 1
      for (int j = 2; j < 64 - KVPF; j++) {
        mbar_pace(sb + B_KE + (j & 1) * 8, (~j >> 1) & 1);
        const size_t o = (size_t)(hg * 4 * S_LEN + kv_tile(j + KVPF) * 128 + qt * 8) * DH;
        if (KVPF) { l2_prefetch(P.k + o, 2048); l2_prefetch(P.v + o, 2048); }
        if (j >= 40 && j < 56) l2_prefetch(P.wo + (size_t)(hg * 512 + qt * 32 + (j - 40) * 2) * DM, 2 * DM * 2);
        if (j >= 56 && j < 60) l2_prefetch(((j & 1) ? P.x : g->gate) + (size_t)(qt * 128 + hg * 16 + (j & 2) * 4) * DM, 8 * DM * 2);
      }
    }
    __syncwarp();
    if ((warp == 1 || warp == 2) && !X_SKIP(qp)) {
      mbar_wait(sb + B_GATE, 0);
      #pragma unroll 1
      for (int i = 0; i < 4; i++) {
        const int r = warp * 8 - 8 + (i & 1) * 4 + (lane >> 3);
        const uint32_t e = ((qt * 128 + hg * 16 + r) * DM + (8 + (i >> 1)) * 64 + (lane & 7) * 8) * 2;
        if (!(i & 1)) bar_sync(8, 192);
        STALL(10);
        const uint4 xr = ldg_nc(at<uint4>(P.x, e)), gr = ld_relaxed4(at<uint4>(g->gate, e)), sv = lds128(sb + SM_BAR + 1024 + r * 128 + (((lane ^ r) & 7) << 4));
        stg128(at<uint4>(P.out, e), gated(xr, sv, gr));
        if (i == 1) bar_arrive(9, 192);
      }
    }
    cluster_arrive();
    cluster_wait();
  } else {
    const int wg = wgi - 1, t = tid & 127, cw = warp - 4;
    asm volatile("setmaxnreg.inc.sync.aligned.u32 224;");
    uint32_t q[32], p[32];
    float s[64], o[64], l[2] = {0.f, 0.f};
    const uint32_t rb = __shfl_sync(0xffffffff, map_cta(sb, lane & 1), lane), wr = sb + cw * 2048, qa = __shfl_sync(0xffffffff, wr + lane * 16, lane);
    {
      uint32_t sl = 0, ph = 0, rprev = 0;
      float acc0[128], acc1[96];
      auto pair = [&](auto& acc, int pass, int i, auto mid) {
        const uint64_t a = desc(sb, ((i + 2 + 2 * pass) & 7) * 1024 + wg * 512 + doff(0, 16)), b = desc(sb, sl * 128 + doff(SM_W, 2048));
        STALL(4);
        mbar_wait(sb + B_WF + sl, ph);
        if (i == 0) TRACE(wg, 1 + pass);
        TRACEF(1, wg, 40 + pass * 20 + 2 * i);
        wg_fence();
        wgmma_ss_tb<0, 0>(acc, a, b, i > 0);
        wgmma_ss_tb<2, 512>(acc, a, b, 1);
        wg_commit();
        mbar_wait(sb + B_WF + 8 + sl, ph);
        wg_wait<1>();
        if (i > 0) release2(rprev, lane);
        TRACEF(1, wg, 41 + pass * 20 + 2 * i);
        wg_fence();
        wgmma_ss_tb<4, 1024>(acc, a, b, 1);
        wgmma_ss_tb<6, 1536>(acc, a, b, 1);
        wg_commit();
        mid();
        rprev = rb + B_WE + 8 + sl;
        sl += 16;
        if (sl == 48) { sl = 0; ph ^= 1; }
        wg_wait<1>();
        release2(rprev - 8, lane);
      };
      if (wg == 1) bar_arrive(1, 256);
      #pragma unroll 1
      for (int i = 0; i < 10; i++) {
        if (i == 9) bar_sync(1 + wg, 256);
        pair(acc0, 0, i, [] {});
      }
      mbar_wait(sb + B_EXT, 0);
      const uint32_t st0 = lds32(sb + SM_STAT + (cw * 16 + (lane >> 2)) * 4), st1 = lds32(sb + SM_STAT + (cw * 16 + 8 + (lane >> 2)) * 4);
      const uint32_t a0 = (lane & 3) ? 0u : (__byte_perm(st0, 0, 0x1010) ^ 0x80008000u), a1 = (lane & 3) ? 0u : (__byte_perm(st1, 0, 0x1010) ^ 0x80008000u);
      wg_fence();
      wgmma_rs_tb<0>(acc0, a0, a1, 0u, 0u, (uint64_t)desc_lo(sb + SM_EXT, 0) | ((uint64_t)2 << 32), 1);
      wg_commit();
      bar_arrive(1 + (wg ^ 1), 256);
      float rs[2] = {rcp_fast(bf_hi(st0)) * SCALE_LOG2E, rcp_fast(bf_hi(st1)) * SCALE_LOG2E};
      wg_wait<0>();
      fence_regs(acc0);
      release2(rprev, lane);
      #pragma unroll
      for (int i = 0; i < 32; i++) q[i] = pack_bf16(acc0[64+2*i] * rs[i & 1], acc0[64+2*i+1] * rs[i & 1]);
      fence_regs(q);
      pair(acc1, 1, 0, [&] {
        bar_sync(4 + wg, 128);
        const uint32_t one = lds32(sb + SM_ONE);
        rs[0] = __uint_as_float(__float_as_uint(rs[0]) * one); rs[1] = __uint_as_float(__float_as_uint(rs[1]) * one);
        #pragma unroll
        for (int i = 0; i < 32; i++) p[i] = pack_bf16(acc0[2*i] * rs[i & 1], acc0[2*i+1] * rs[i & 1]);
        fence_regs(p);
      });
      #pragma unroll 1
      for (int i = 1; i < 8; i++) pair(acc1, 1, i, [&] {
        #pragma unroll
        for (int e = 0; e < 8; e++) sts128_if(i == 4 + e / 2, qa + qo_slot(0) + (e >> 2) * U + (e & 3) * 512, p[4*e], p[4*e+1], p[4*e+2], p[4*e+3]);
      });
      mbar_wait(sb + B_WF, 0);
      mbar_wait(sb + B_WF + 8, 0);
      if (wg) { wg_wait<0>(); release2(rprev, lane); }
      bar_sync(1 + wg, 256);
      const uint64_t da = desc(sb, wg * 512 + 7), db = desc(sb, 7);
      static_for<0, 2>([&](auto ic) { constexpr int i = decltype(ic)::v;
        wg_fence();
        static_for<0, 4>([&](auto kc) { constexpr int k = decltype(kc)::v;
          wgmma_ss_tb<doff((4 + i) * U, 16) - 7 + k * 2, doff(SM_W + i * 2 * U, 2048) - 7 + k * 512>(acc1, da, db, 1); });
        if (i == 0) {
          wg_commit();
          mbar_wait(sb + B_WF + 16, 0);
          mbar_wait(sb + B_WF + 24, 0);
          mbar_wait(sb + B_EXT + 8, 0);
          wg_wait<1>();
          if (!wg) release2(rprev, lane);
        }
      });
      wgmma_rs_tb<0>(acc1, a0, a1, 0u, 0u, (uint64_t)desc_lo(sb + SM_EXT + 1024, 0) | ((uint64_t)2 << 32), 1);
      wg_commit();
      mbar_wait(sb + B_KF, 0);
      wg_wait<1>();
      release2(rb + B_WE + 8, lane);
      TRACE(wg, 3);
      mma_qk<0, 2>(s, q, desc(sb, 2));
      bar_arrive(1 + (wg ^ 1), 256);
      wg_wait<1>();
      fence_regs(acc1);
      release2(rb + B_WE + 24, lane);
      #pragma unroll
      for (int e = 0; e < 12; e++)
        sts128(qa + SM_QO + (e >> 2) * U + (e & 3) * 512, pack_bf16(acc1[8*e] * rs[0], acc1[8*e+1] * rs[0]), pack_bf16(acc1[8*e+2] * rs[1], acc1[8*e+3] * rs[1]),
               pack_bf16(acc1[8*e+4] * rs[0], acc1[8*e+5] * rs[0]), pack_bf16(acc1[8*e+6] * rs[1], acc1[8*e+7] * rs[1]));
      wg_wait<0>();
      fence_regs(s);
      release2(rb + B_KE, lane);
      exp_rows<0, 64>(s, l);
      #pragma unroll
      for (int i = 0; i < 32; i++) p[i] = pack_bf16(s[2*i], s[2*i+1]);
    }
    unsigned tz[3] = {0, 0, 0};
    bool ready = false;
    #pragma unroll 1
    for (int j = 1; ; j += 2) {
      int ph = 0;
      #pragma unroll 1
      do {
        attn_step<1, false>(sb, rb, wr, qa, wg, lane, j, ph, s, o, p, q, l, ready, g, tz);
        ph ^= 1; j += 2;
        if (wg < 2) attn_step<0, false>(sb, rb, wr, qa, wg, lane, j - 1, ph, s, o, p, q, l, ready, g, tz);
      } while ((j & 15) != 15);
      if (j == 47) mbar_wait(sb + B_Q3, 0);
      attn_step<1, true>(sb, rb, wr, qa, wg, lane, j, 1, s, o, p, q, l, ready, g, tz);
      if (j == 63) break;
      if (wg < 2) attn_step<0, true>(sb, rb, wr, qa, wg, lane, j + 1, 0, s, o, p, q, l, ready, g, tz);
    }
    mbar_wait(sb + B_OF, 0);
    mbar_wait(sb + B_CF + wg * 8, 0);
    mbar_wait(sb + B_KF + 24, 1);
    bar_sync(1 + wg, 256);
    TRACE(wg, 4);
    mma_pv<SM_V + 2 * U, 2>(o, p, desc(sb, 2), true);
    mma_c<3>(s, sb, wg, 0, 0);
    bar_arrive(1 + (wg ^ 1), 256);
    mbar_wait(sb + B_KE + 16, 1);
    const uint32_t tag = lds32(sb + SM_EP) & 1;
    row_scale(l[0], l[1], lds32(sb + SM_ONE), sb + SM_BAD + cw * 4 + 3);
    __syncwarp();
    const uint32_t flags = lds32(sb + SM_BAD + (lane & 7) * 4);
    wg_wait<1>();
    fence_regs(o); fence_regs(p);
    release2(rb + B_KE + 24, lane);
    const uint32_t over = tainted(store_o<true>(o_addr(wr, lane) + SM_V, o, l[0], l[1]));
    if (__builtin_expect(bar_any(4 + wg, 128, __any_sync(0xffffffff, flags | over)), 0)) {
      const uint32_t bad = __shfl_sync(0xffffffff, flags, cw) | (__any_sync(0xffffffff, over) << 24);
      wg_wait<0>();
      fence_regs(s);
      redo_heads(P, sb, bad, qt * 128 + cw * 16, hg * 4);
      #pragma unroll
      for (int i = 0; i < 64; i++) s[i] = 0.f;
      __syncwarp();
      if (lane == 0) mbar_arrive(sb + B_OS + 24);
      mbar_wait(sb + B_OF, 1);
      mma_c<4>(s, sb, wg, 0, 0);
    } else if (lane == 0) mbar_arrive(sb + B_OS + 24);
    wg_wait<0>();
    release2(rb + B_CE + wg * 8, lane);
    if (X_SKIP(qp)) { cluster_arrive(); } else {
      const uint4* in = at<uint4>(g->part, (((qt * 8 + hg) * 9 + wg) * 1024 + t) * 16);
      const uint32_t tm = 0u - tag;
      uint4 v[8];
      auto fetch = [&](auto half, const uint4* from) {
        #pragma unroll
        for (int i = decltype(half)::v * 4; i < decltype(half)::v * 4 + 4; i++) reload(v[i], from + i * 128);
      };
      auto verify = [&](auto half, const uint4* from) { verify4(v + decltype(half)::v * 4, from + decltype(half)::v * 512, tm); };
      int sp = 6, sl = 2 + 3 * wg, ph = 0;
      auto quarter = [&](auto site, int h, int arrive_bar) {
        STALL(2);
        mbar_wait(sb + B_CF + sl * 8, ph);
        if (h == 0) bar_sync(1 + wg, 256);
        mma_c<decltype(site)::v>(s, sb, sl, h, arrive_bar);
        if (h) { wg_wait<1>(); release2(rb + B_CE + sp * 8, lane); }
        sp = sl;
        if (++sl == 6) { sl = 0; ph ^= 1; }
      };
      auto send = [&](int st) {
        uint4* dst = at<uint4>(g->part, ((qt * 72 + st) * 1024 + (st < 2 ? hg * 128 : ((hg + st - 1) & 7) * 9216) + t) * 16);
        const uint32_t ds = st < 2 ? 9 * U : 2048;
        wg_wait<0>();
        fence_regs(s);
        TRACEF(4, wg, 106 + (st >> 1));
        release2(rb + B_CE + sp * 8, lane);
        STALL(3);
        #pragma unroll
        for (int i = 0; i < 8; i++, dst = at<uint4>(dst, ds))
          st_tagged(dst, (pack_bf16(s[8*i], s[8*i+1]) & ~1u) | tag, pack_bf16(s[8*i+2], s[8*i+3]), pack_bf16(s[8*i+4], s[8*i+5]), pack_bf16(s[8*i+6], s[8*i+7]));
        sl += st ? 4 : 3;
        if (sl >= 6) { sl -= 6; ph ^= 1; }
      };
      const uint32_t ta = ((lane >> 4) * 8 + (lane & 7)) * 128 + ((((cw & 3) * 2 + ((lane >> 3) & 1)) ^ (lane & 7)) << 4), ra = (t >> 3) * 128 + (((t & 7) ^ ((t >> 3) & 7)) << 4);
      float T[64];
      #pragma unroll
      for (int i = 0; i < 8; i++) asm volatile("mov.b64 {%0,%1}, 0;\nmov.b64 {%2,%3}, 0;" : "=r"(v[i].x), "=r"(v[i].y), "=r"(v[i].z), "=r"(v[i].w));
      TRACEF(4, wg, 112);
      bar_sync(1 + wg, 256);
      auto take = [&](auto half, int back, bool more) {
        verify(half, in - back * 1024);
        const uint4* const nx = in - (back - 1) * 1024;
        #pragma unroll
        for (int i = decltype(half)::v * 4; i < decltype(half)::v * 4 + 4; i++) { add8(T + 8 * i, v[i]); reload(v[i], nx + i * 128, more); }
      };
      #pragma unroll 1
      for (int st = wg; ; st += 2, in += 2048) {
        TRACEF(4, wg, 100 + (st >> 1));
        const bool odd5 = (st & 1) && st >= 5;
        quarter(IC<5>{}, 1, 0);
        if (odd5) take(IC<0>{}, 3, true);
        else if (st == 2) fetch(IC<0>{}, in - 2048);
        quarter(IC<6>{}, 2, 0);
        if (odd5) take(IC<1>{}, 3, true);
        else if (st == 2) fetch(IC<1>{}, in - 2048);
        if (st < 2) mbar_wait(sb + B_OF, 1);
        quarter(IC<7>{}, 3, st < 9 ? 2 - wg : 0);
        if (st < 9) send(st);
        if (odd5) {
          take(IC<0>{}, 2, st < 9);
          if (st == 9) bar_arrive(1, 256);
          take(IC<1>{}, 2, st < 9);
        }
        else if (st == 3) {
          fetch(IC<0>{}, in - 1024); fetch(IC<1>{}, in - 1024);
          #pragma unroll
          for (int i = 0; i < 64; i++) asm volatile("mov.b32 %0, 0;" : "+f"(T[i]));
        } else if (st == 2 || st == 4) {
          const uint4* const rows = at<uint4>(in - 3072, st == 2 ? U : 0);
          float a[8];
          #pragma unroll
          for (int i = 0; i < 8; i++) a[i] = 0.f;
          static_for<0, 2>([&](auto hf) {
            verify(hf, rows);
            #pragma unroll
            for (int i = decltype(hf)::v * 4; i < decltype(hf)::v * 4 + 4; i++) { add8(a, v[i]); reload(v[i], rows + 1024 + i * 128, st == 2); }
          });
          if (st == 4) bar_sync(9, 192);
          stsm4t(sb + SM_BAR + 1024 + ta, pack_bf16(a[0], a[1]), pack_bf16(a[2], a[3]), pack_bf16(a[4], a[5]), pack_bf16(a[6], a[7]));
          bar_arrive(8, 192);
        }
        if (st >= 8) break;
        quarter(IC<8>{}, 0, 0);
      }
      cluster_arrive();
      TRACEF(4, wg, 113);
      wg_wait<0>();
      fence_regs(s);
      if (wg == 0) {
        mbar_wait(sb + B_CF + 32, 0);
        mbar_wait(sb + B_CF + 40, 0);
        uint4* const op = at<uint4>(P.out, ((qt * 128 + (t >> 3)) * DM + hg * 64 + (t & 7) * 8) * 2);
        bar_sync(1, 256);
        uint4 xv[8];
        #pragma unroll
        for (int i = 0; i < 8; i++) { xv[i] = lds128(sb + 10 * U + i * 2048 + ra); v[i] = lds128(sb + 11 * U + i * 2048 + ra); }
        #pragma unroll
        for (int i = 0; i < 8; i++) {
          if (!(i & 3)) bar_sync(12 + (i >> 2), 256);
          stg128(op + i * 2 * DM, gated(xv[i], lds128(sb + i * 2048 + ra), v[i]));
        }
      } else {
        TRACEF(4, wg, 110);
        mbar_wait(sb + B_CF + 8, 1);
        #pragma unroll
        for (int i = 0; i < 8; i++) v[i] = lds128(sb + U + i * 2048 + t * 16);
        #pragma unroll
        for (int i = 0; i < 64; i++) T[i] += s[i];
        fence_regs(T);
        static_for<0, 8>([&](auto ic) { constexpr int i = decltype(ic)::v;
          if (!(i & 3)) verify(IC<i / 4>{}, in - 1024);
          add8(T + 8 * i, v[i]);
          stsm4t(sb + i * 2048 + ta, pack_bf16(T[8*i], T[8*i+1]), pack_bf16(T[8*i+2], T[8*i+3]), pack_bf16(T[8*i+4], T[8*i+5]), pack_bf16(T[8*i+6], T[8*i+7]));
          if ((i & 3) == 3) bar_arrive(12 + (i >> 2), 256);
        });
      }
    }
    TRACE(wg, 6);
    cluster_wait();
  }
}

typedef CUresult (*EncodeFn)(CUtensorMap*, CUtensorMapDataType, cuuint32_t, void*, const cuuint64_t*, const cuuint64_t*, const cuuint32_t*, const cuuint32_t*,
                             CUtensorMapInterleave, CUtensorMapSwizzle, CUtensorMapL2promotion, CUtensorMapFloatOOBfill);
void make_map(EncodeFn enc, CUtensorMap* tm, const void* ptr, uint64_t inner, uint64_t outer, uint32_t box_outer, uint32_t blocks = 0) {
  cuuint64_t dims[3] = {blocks ? 64 : inner, outer, inner / 64}; cuuint64_t strides[2] = {inner * 2, 128};
  cuuint32_t box[3] = {64, box_outer, blocks}; cuuint32_t es[3] = {1, 1, 1};
  enc(tm, CU_TENSOR_MAP_DATA_TYPE_BFLOAT16, blocks ? 3 : 2, const_cast<void*>(ptr), dims, strides, box, es, CU_TENSOR_MAP_INTERLEAVE_NONE,
      CU_TENSOR_MAP_SWIZZLE_128B, CU_TENSOR_MAP_L2_PROMOTION_L2_128B, CU_TENSOR_MAP_FLOAT_OOB_FILL_NONE);
}

}

extern "C" void kernel_launch(void* const* d_in, const int* in_sizes, int n_in, void* d_out, int out_size) {
  (void)in_sizes; (void)n_in; (void)out_size;
  Params P;
  P.x = (const __nv_bfloat16*)d_in[0]; P.k = (const __nv_bfloat16*)d_in[1]; P.v = (const __nv_bfloat16*)d_in[2];
  P.wq = (const __nv_bfloat16*)d_in[3]; P.wo = (const __nv_bfloat16*)d_in[4]; P.wr = (const __nv_bfloat16*)d_in[6];
  P.out = (__nv_bfloat16*)d_out;
  cudaGetSymbolAddress((void**)&P.g, g_s);
  void* fn = nullptr; cudaDriverEntryPointQueryResult st;
  cudaGetDriverEntryPoint("cuTensorMapEncodeTiled", &fn, cudaEnableDefault, &st);
  EncodeFn enc = (EncodeFn)fn;
  CUtensorMap tmX, tmW4, tmW3, tmW1, tmK, tmV, tmWO, tmG, tmU, tmD, tmGate;
  make_map(enc, &tmGate, P.g->gate, DM, S_LEN, 128);
  make_map(enc, &tmX, P.x, DM, S_LEN, 128);
  make_map(enc, &tmW4, P.wq, NH * DH, DM, 16, 4);
  make_map(enc, &tmW3, P.wq, NH * DH, DM, 16, 3);
  make_map(enc, &tmW1, P.wq, NH * DH, DM, 128);
  make_map(enc, &tmK, P.k, DH, (uint64_t)NH * S_LEN, 128);
  make_map(enc, &tmV, P.v, DH, (uint64_t)NH * S_LEN, 128);
  make_map(enc, &tmWO, P.wo, DM, NH * DH, 64);
  make_map(enc, &tmG, d_in[7], FF, DM, 128);
  make_map(enc, &tmU, d_in[8], FF, DM, 128);
  make_map(enc, &tmD, d_in[9], DM, FF, 128);
  cudaFuncSetAttribute(fused_kernel, cudaFuncAttributeMaxDynamicSharedMemorySize, SMEM_BYTES);
  fused_kernel<<<132, 384, SMEM_BYTES, cudaStreamPerThread>>>(tmX, tmW4, tmW3, tmW1, tmK, tmV, tmWO, tmG, tmU, tmD, tmGate, P);
}
```

```cpp
#include <cuda_runtime.h>
#include <cuda_bf16.h>
#include <cuda.h>
#include <stdint.h>

#define MAXPOLL (1 << 22)
#define DPOS 44
#define DPOSF 36
#define KVPF 1
#define WAITMAX (1 << 19)
#define PH 1
#define QSP 6
namespace {

constexpr int S_LEN = 2048, DM = 640, NH = 32, DH = 128, FF = 1728, TOPC = 8;
constexpr float SCALE_LOG2E = 0.08838834764831845f * 1.4426950408889634f;

struct alignas(128) Cnt { unsigned v; unsigned pad[31]; };
struct Scratch {
  alignas(128) unsigned long long ticket;
  alignas(128)
  uint4 part[16 * 8 * 9 * 1024];
  __nv_bfloat16 gate[S_LEN * DM];
  uint32_t stat[S_LEN];
  uint4 cs[NH * DH];
  float ypart[4 * TOPC * DM];
  uint4 q3[16 * 8 * 1024];
  uint32_t key[S_LEN];
  Cnt cnt_gate, cnt_mod, mod_done, q3_done[4];
  uint32_t near[128 * 8];
};
__device__ Scratch g_s;

__device__ __forceinline__ uint32_t smem_u32(const void* p) { return (uint32_t)__cvta_generic_to_shared(p); }
template <class T> __device__ __forceinline__ T* at(const void* p, uint32_t off) { uint64_t r;
  asm("{\n.reg .u32 lo, hi;\nmov.b64 {lo, hi}, %1;\nadd.cc.u32 lo, lo, %2;\naddc.u32 hi, hi, 0;\nmov.b64 %0, {lo, hi};\n}\n" : "=l"(r) : "l"(p), "r"(off)); return (T*)r; }
__device__ __forceinline__ void mbar_init(uint32_t bar, uint32_t cnt) { asm volatile("mbarrier.init.shared::cta.b64 [%0], %1;" :: "r"(bar), "r"(cnt) : "memory"); }
__device__ __forceinline__ void mbar_expect_tx(uint32_t bar, uint32_t bytes) { asm volatile("mbarrier.arrive.expect_tx.shared::cta.b64 _, [%0], %1;" :: "r"(bar), "r"(bytes) : "memory"); }
__device__ __forceinline__ void mbar_arrive(uint32_t bar) { asm volatile("mbarrier.arrive.shared::cta.b64 _, [%0];" :: "r"(bar) : "memory"); }
__device__ __forceinline__ uint32_t map_cta(uint32_t a, uint32_t cta) { uint32_t r; asm volatile("mapa.shared::cluster.u32 %0, %1, %2;" : "=r"(r) : "r"(a), "r"(cta)); return r; }
__device__ __forceinline__ void mbar_arrive_cluster(uint32_t bar) { asm volatile("mbarrier.arrive.shared::cluster.b64 _, [%0];" :: "r"(bar) : "memory"); }
__device__ __forceinline__ void mbar_wait(uint32_t bar, uint32_t parity) {
  asm volatile("{\n.reg .pred p;\n.reg .u32 c;\nmov.u32 c, 0;\nLAB_WAIT:\nmbarrier.try_wait.parity.shared::cta.b64 p, [%0], %1;\n@p bra LAB_DONE;\n"
               "add.u32 c, c, 1;\nsetp.lt.u32 p, c, %2;\n@p bra LAB_WAIT;\ntrap;\nLAB_DONE:\n}\n" :: "r"(bar), "r"(parity), "n"(WAITMAX) : "memory"); }
__device__ __forceinline__ void mbar_wait_idle(uint32_t bar, uint32_t parity) {
  asm volatile("{\n.reg .pred p;\n.reg .u32 c;\nmov.u32 c, 0;\nLAB_WAIT:\nmbarrier.try_wait.parity.shared::cta.b64 p, [%0], %1;\n@p bra LAB_DONE;\n"
               "nanosleep.u32 1000;\nadd.u32 c, c, 1;\nsetp.lt.u32 p, c, %2;\n@p bra LAB_WAIT;\ntrap;\nLAB_DONE:\n}\n" :: "r"(bar), "r"(parity), "n"(WAITMAX) : "memory"); }
__device__ __forceinline__ void mbar_pace(uint32_t bar, uint32_t parity) {
  asm volatile("{\n.reg .pred p;\n.reg .u32 c;\nmov.u32 c, 0;\nLAB_WAIT:\nmbarrier.try_wait.parity.shared::cta.b64 p, [%0], %1;\n@p bra LAB_DONE;\n"
               "add.u32 c, c, 1;\nsetp.lt.u32 p, c, 256;\n@p bra LAB_WAIT;\nLAB_DONE:\n}\n" :: "r"(bar), "r"(parity) : "memory"); }
__device__ __forceinline__ void flag_wait(const unsigned* p, unsigned target, unsigned ns = 500) {
  asm volatile("{\n.reg .pred p;\n.reg .u32 c, v;\nmov.u32 c, 0;\nLAB_WAIT:\nld.relaxed.gpu.global.u32 v, [%0];\nsub.u32 v, v, %1;\nsetp.ge.s32 p, v, 0;\n@p bra LAB_DONE;\n"
               "nanosleep.u32 %2;\nadd.u32 c, c, 1;\nsetp.lt.u32 p, c, 8388608;\n@p bra LAB_WAIT;\ntrap;\nLAB_DONE:\nld.acquire.gpu.global.u32 v, [%0];\n}\n" :: "l"(p), "r"(target), "r"(ns) : "memory"); }
__device__ __forceinline__ void flag_add_release(unsigned* p) { asm volatile("fence.acq_rel.gpu;\nred.relaxed.gpu.global.add.u32 [%0], 1;" :: "l"(p) : "memory"); }
__device__ __forceinline__ void tma_load_2d(uint32_t dst, const CUtensorMap* tm, uint32_t bar, int c0, int c1) {
  asm volatile("cp.async.bulk.tensor.2d.shared::cluster.global.mbarrier::complete_tx::bytes [%0], [%1, {%3, %4}], [%2];"
    :: "r"(dst), "l"(tm), "r"(bar), "r"(c0), "r"(c1) : "memory"); }
__device__ __forceinline__ void tma_load_2d_mc(uint32_t dst, const CUtensorMap* tm, uint32_t bar, int c0, int c1) {
  asm volatile("cp.async.bulk.tensor.2d.shared::cluster.global.mbarrier::complete_tx::bytes.multicast::cluster [%0], [%1, {%3, %4}], [%2], %5;"
    :: "r"(dst), "l"(tm), "r"(bar), "r"(c0), "r"(c1), "h"((uint16_t)3) : "memory"); }
__device__ __forceinline__ void tma_load_3d(uint32_t dst, const CUtensorMap* tm, uint32_t bar, int c0, int c1, int c2) {
  asm volatile("cp.async.bulk.tensor.3d.shared::cluster.global.mbarrier::complete_tx::bytes [%0], [%1, {%3, %4, %5}], [%2];"
    :: "r"(dst), "l"(tm), "r"(bar), "r"(c0), "r"(c1), "r"(c2) : "memory"); }
__device__ __forceinline__ void tma_load_3d_mc(uint32_t dst, const CUtensorMap* tm, uint32_t bar, int c0, int c1, int c2) {
  asm volatile("cp.async.bulk.tensor.3d.shared::cluster.global.mbarrier::complete_tx::bytes.multicast::cluster [%0], [%1, {%3, %4, %5}], [%2], %6;"
    :: "r"(dst), "l"(tm), "r"(bar), "r"(c0), "r"(c1), "r"(c2), "h"((uint16_t)3) : "memory"); }
__device__ __forceinline__ void bulk_load(uint32_t dst, const void* src, uint32_t bytes, uint32_t bar) {
  asm volatile("cp.async.bulk.shared::cluster.global.mbarrier::complete_tx::bytes [%0], [%1], %2, [%3];" :: "r"(dst), "l"(src), "r"(bytes), "r"(bar) : "memory"); }
__device__ __forceinline__ void l2_prefetch(const void* p, uint32_t bytes) { asm volatile("cp.async.bulk.prefetch.L2.global [%0], %1;" :: "l"(p), "r"(bytes) : "memory"); }
__device__ __forceinline__ void wg_fence() { asm volatile("wgmma.fence.sync.aligned;" ::: "memory"); }
__device__ __forceinline__ void wg_commit() { asm volatile("wgmma.commit_group.sync.aligned;" ::: "memory"); }
template <int N> __device__ __forceinline__ void wg_wait() { asm volatile("wgmma.wait_group.sync.aligned %0;" :: "n"(N) : "memory"); }
__device__ __forceinline__ void bar_sync(int id, int n) { asm volatile("bar.sync %0, %1;" :: "r"(id), "r"(n) : "memory"); }
__device__ __forceinline__ void bar_arrive(int id, int n) { asm volatile("bar.arrive %0, %1;" :: "r"(id), "r"(n) : "memory"); }
__device__ __forceinline__ bool bar_any(int id, int n, uint32_t v) { uint32_t r;
  asm volatile("{\n.reg .pred p;\nsetp.ne.u32 p, %3, 0;\nbar.red.or.pred p, %1, %2, p;\nselp.u32 %0, 1, 0, p;\n}\n" : "=r"(r) : "r"(id), "r"(n), "r"(v) : "memory"); return r; }
__device__ __forceinline__ int sel_lt(int a, int b, int x, int y) { int r; asm("{\n.reg .pred p;\nsetp.lt.s32 p, %1, %2;\nselp.s32 %0, %3, %4, p;\n}\n" : "=r"(r) : "r"(a), "r"(b), "r"(x), "r"(y)); return r; }
__device__ __forceinline__ bool elect_one() { uint32_t r; asm volatile("{\n.reg .pred p;\nelect.sync _|p, 0xffffffff;\nselp.u32 %0, 1, 0, p;\n}\n" : "=r"(r)); return r; }
__device__ __forceinline__ void cluster_arrive() { asm volatile("barrier.cluster.arrive.relaxed.aligned;" ::: "memory"); }
__device__ __forceinline__ void cluster_wait() { asm volatile("barrier.cluster.wait.aligned;" ::: "memory"); }
__device__ __forceinline__ void proxy_fence() { asm volatile("fence.proxy.async.shared::cta;" ::: "memory"); }
__device__ __forceinline__ uint32_t pack_bf16(float lo, float hi) { uint32_t r; asm("cvt.rn.bf16x2.f32 %0, %1, %2;" : "=r"(r) : "f"(hi), "f"(lo)); return r; }
__device__ __forceinline__ float bf_lo(uint32_t v) { return __uint_as_float(v << 16); }
__device__ __forceinline__ float bf_hi(uint32_t v) { return __uint_as_float(v & 0xffff0000u); }
__device__ __forceinline__ void add8(float* a, const uint4& w) {
  a[0] += bf_lo(w.x); a[1] += bf_hi(w.x); a[2] += bf_lo(w.y); a[3] += bf_hi(w.y); a[4] += bf_lo(w.z); a[5] += bf_hi(w.z); a[6] += bf_lo(w.w); a[7] += bf_hi(w.w); }
__device__ __forceinline__ float rbf(float x) { return __bfloat162float(__float2bfloat16_rn(x)); }
__device__ __forceinline__ float ex2(float x) { float y; asm("ex2.approx.ftz.f32 %0, %1;" : "=f"(y) : "f"(x)); return y; }
__device__ __forceinline__ uint32_t lds32(uint32_t a) { uint32_t v; asm volatile("ld.shared.u32 %0, [%1];" : "=r"(v) : "r"(a) : "memory"); return v; }
__device__ __forceinline__ void sts32(uint32_t a, uint32_t v) { asm volatile("st.shared.u32 [%0], %1;" :: "r"(a), "r"(v) : "memory"); }
__device__ __forceinline__ uint4 lds128(uint32_t a) { uint4 v; asm volatile("ld.shared.v4.u32 {%0,%1,%2,%3}, [%4];" : "=r"(v.x), "=r"(v.y), "=r"(v.z), "=r"(v.w) : "r"(a) : "memory"); return v; }
__device__ __forceinline__ void sts128(uint32_t a, uint32_t x, uint32_t y, uint32_t z, uint32_t w) { asm volatile("st.shared.v4.u32 [%0], {%1,%2,%3,%4};" :: "r"(a), "r"(x), "r"(y), "r"(z), "r"(w) : "memory"); }
__device__ __forceinline__ void sts128_if(bool c, uint32_t a, uint32_t x, uint32_t y, uint32_t z, uint32_t w) {
  asm volatile("{\n.reg .pred p;\nsetp.ne.u32 p, %5, 0;\n@p st.shared.v4.u32 [%0], {%1,%2,%3,%4};\n}\n" :: "r"(a), "r"(x), "r"(y), "r"(z), "r"(w), "r"((uint32_t)c) : "memory"); }
__device__ __forceinline__ void st_tagged(uint4* p, uint32_t x, uint32_t y, uint32_t z, uint32_t w) {
  asm volatile("st.relaxed.gpu.global.v4.u32 [%0], {%1,%2,%3,%4};" :: "l"(p), "r"(x), "r"(y), "r"(z), "r"(w) : "memory"); }
__device__ __forceinline__ uint4 ld_relaxed4(const void* p) { uint4 v;
  asm volatile("ld.relaxed.gpu.global.v4.u32 {%0,%1,%2,%3}, [%4];" : "=r"(v.x), "=r"(v.y), "=r"(v.z), "=r"(v.w) : "l"(p) : "memory"); return v; }
__device__ __forceinline__ uint4 ld_tagged(const uint4* p) { uint4 v;
  asm volatile("{\n.reg .b128 v;\nld.relaxed.gpu.global.b128 v, [%4];\nmov.b128 {%0,%1,%2,%3}, v;\n}\n" : "=r"(v.x), "=r"(v.y), "=r"(v.z), "=r"(v.w) : "l"(p) : "memory"); return v; }
__device__ __forceinline__ void reload(uint4& v, const uint4* p, bool yes = true) {
  asm volatile("{\n.reg .pred p;\nsetp.ne.u32 p, %5, 0;\n@p ld.relaxed.gpu.global.v4.u32 {%0,%1,%2,%3}, [%4];\n}\n" : "+r"(v.x), "+r"(v.y), "+r"(v.z), "+r"(v.w) : "l"(p), "r"((uint32_t)yes) : "memory"); }
#define TAG_TEST "lop3.b32 a, %0, %4, %17, 0x7E;\nlop3.b32 b, %8, %12, %17, 0x7E;\nlop3.b32 a, a, b, 1, 0xA8;\nsetp.ne.u32 p, a, 0;\nvote.sync.any.pred p, p, 0xffffffff;\n"
__device__ __forceinline__ void verify4(uint4* v, const uint4* p, uint32_t tm) {
  asm volatile("{\n.reg .pred p;\n.reg .u32 a, b, c;\n" TAG_TEST "@!p bra.uni LAB_DONE;\nmov.u32 c, 0;\nLAB_AGAIN:\n"
    "ld.relaxed.gpu.global.v4.u32 {%0,%1,%2,%3}, [%16];\nld.relaxed.gpu.global.v4.u32 {%4,%5,%6,%7}, [%16+2048];\n"
    "ld.relaxed.gpu.global.v4.u32 {%8,%9,%10,%11}, [%16+4096];\nld.relaxed.gpu.global.v4.u32 {%12,%13,%14,%15}, [%16+6144];\n"
    TAG_TEST "add.u32 c, c, 1;\nsetp.lt.and.u32 p, c, %18, p;\n@p bra.uni LAB_AGAIN;\nLAB_DONE:\n}\n"
    : "+r"(v[0].x), "+r"(v[0].y), "+r"(v[0].z), "+r"(v[0].w), "+r"(v[1].x), "+r"(v[1].y), "+r"(v[1].z), "+r"(v[1].w),
      "+r"(v[2].x), "+r"(v[2].y), "+r"(v[2].z), "+r"(v[2].w), "+r"(v[3].x), "+r"(v[3].y), "+r"(v[3].z), "+r"(v[3].w) : "l"(p), "r"(tm), "n"(MAXPOLL) : "memory"); }
__device__ __forceinline__ uint4 ldg_nc(const void* p) { uint4 v;
  asm volatile("ld.global.nc.L1::no_allocate.v4.u32 {%0,%1,%2,%3}, [%4];" : "=r"(v.x), "=r"(v.y), "=r"(v.z), "=r"(v.w) : "l"(p) : "memory"); return v; }
__device__ __forceinline__ uint32_t ldg32(const void* p) { uint32_t v; asm volatile("ld.relaxed.gpu.global.u32 %0, [%1];" : "=r"(v) : "l"(p) : "memory"); return v; }
__device__ __forceinline__ void stg128(void* p, const uint4& v) { asm volatile("st.global.v4.u32 [%0], {%1,%2,%3,%4};" :: "l"(p), "r"(v.x), "r"(v.y), "r"(v.z), "r"(v.w) : "memory"); }
__device__ __forceinline__ void st_relaxed(uint32_t* p, uint32_t v) { asm volatile("st.relaxed.gpu.global.u32 [%0], %1;" :: "l"(p), "r"(v) : "memory"); }
__device__ __forceinline__ uint32_t mul_bf2(uint32_t a, uint32_t b) { uint32_t r; asm("mul.rn.bf16x2 %0, %1, %2;" : "=r"(r) : "r"(a), "r"(b)); return r; }
__device__ __forceinline__ uint32_t add_bf2(uint32_t a, uint32_t b) { uint32_t r; asm("add.rn.bf16x2 %0, %1, %2;" : "=r"(r) : "r"(a), "r"(b)); return r; }
__device__ __forceinline__ uint32_t sub_bf2(uint32_t a, uint32_t b) { uint32_t r; asm("sub.rn.bf16x2 %0, %1, %2;" : "=r"(r) : "r"(a), "r"(b)); return r; }
__device__ __forceinline__ void stsm4(uint32_t a, uint32_t r0, uint32_t r1, uint32_t r2, uint32_t r3) {
  asm volatile("stmatrix.sync.aligned.m8n8.x4.shared.b16 [%0], {%1,%2,%3,%4};" :: "r"(a), "r"(r0), "r"(r1), "r"(r2), "r"(r3) : "memory"); }
__device__ __forceinline__ void stsm4t(uint32_t a, uint32_t r0, uint32_t r1, uint32_t r2, uint32_t r3) {
  asm volatile("stmatrix.sync.aligned.m8n8.x4.trans.shared.b16 [%0], {%1,%2,%3,%4};" :: "r"(a), "r"(r0), "r"(r1), "r"(r2), "r"(r3) : "memory"); }
__device__ __forceinline__ uint4 gated(const uint4& x, const uint4& s, const uint4& g) {
  return make_uint4(add_bf2(x.x, mul_bf2(s.x, g.x)), add_bf2(x.y, mul_bf2(s.y, g.y)), add_bf2(x.z, mul_bf2(s.z, g.z)), add_bf2(x.w, mul_bf2(s.w, g.w))); }
__device__ __forceinline__ uint32_t tag_miss(uint32_t a, uint32_t b, uint32_t tm) { uint32_t d; asm("lop3.b32 %0, %1, %2, %3, 0x7E;" : "=r"(d) : "r"(a), "r"(b), "r"(tm)); return d; }
template <int R> __device__ __forceinline__ void fence_regs(float (&d)[R]) {
  #pragma unroll
  for (int i = 0; i < R; i++) asm volatile("" : "+f"(d[i]) :: "memory"); }
template <int R> __device__ __forceinline__ void fence_regs(uint32_t (&d)[R]) {
  #pragma unroll
  for (int i = 0; i < R; i++) asm volatile("" : "+r"(d[i]) :: "memory"); }
__device__ __forceinline__ uint32_t desc_lo(uint32_t addr, uint32_t lbo_bytes) { return ((addr & 0x3FFFF) >> 4) | ((lbo_bytes >> 4) << 16); }
__device__ __forceinline__ uint64_t desc(uint32_t sb, uint32_t var = 0) {
  uint64_t d; asm("mov.b64 %0, {%1, %2};" : "=l"(d) : "r"(desc_lo(sb, 0) + var), "r"(0x40000040u)); return d; }
__host__ __device__ constexpr int doff(uint32_t off, uint32_t lbo_bytes) { return (off >> 4) | ((lbo_bytes >> 4) << 16); }
__device__ __forceinline__ float rcp_approx(float x) { float y; asm("rcp.approx.f32 %0, %1;" : "=f"(y) : "f"(x)); return y; }
__device__ __forceinline__ float rcp_fast(float x) { float y; asm("rcp.approx.ftz.f32 %0, %1;" : "=f"(y) : "f"(x)); return y; }
__device__ __forceinline__ float sqrt_approx(float x) { float y; asm("sqrt.approx.f32 %0, %1;" : "=f"(y) : "f"(x)); return y; }
__device__ __forceinline__ float sigmoid_f(float z) { return rcp_fast(1.f + ex2(z * -1.4426950408889634f)); }
__device__ __forceinline__ uint32_t norm2(uint32_t x, uint32_t mean2, float rsd) { const uint32_t d = sub_bf2(x, mean2); return pack_bf16(bf_lo(d) * rsd, bf_hi(d) * rsd); }
#define STALL(site)
#define TRACE(w, i)
#define TRACE1(w, i)
#define TRACEF(m, w, i)
#define TRACEO(i)

template <int OA, int OB> __device__ __forceinline__ void wgmma_ss_tb(float (&d)[128], uint64_t da, uint64_t db, int sd) {
  asm volatile("{\n.reg .pred p;\n.reg .b64 a, b;\nadd.s64 a, %128, %131;\nadd.s64 b, %129, %132;\nsetp.ne.b32 p, %130, 0;\n"
    "wgmma.mma_async.sync.aligned.m64n256k16.f32.bf16.bf16 {%0, %1, %2, %3, %4, %5, %6, %7, %8, %9, %10, %11, %12, %13, %14, %15, %16, %17, %18, %19, %20, %21, %22, %23, %24, %25, %26, %27, %28, %29, %30, %31, %32, %33, %34, %35, %36, %37, %38, %39, %40, %41, %42, %43, %44, %45, %46, %47, %48, %49, %50, %51, %52, %53, %54, %55, %56, %57, %58, %59, %60, %61, %62, %63, %64, %65, %66, %67, %68, %69, %70, %71, %72, %73, %74, %75, %76, %77, %78, %79, %80, %81, %82, %83, %84, %85, %86, %87, %88, %89, %90, %91, %92, %93, %94, %95, %96, %97, %98, %99, %100, %101, %102, %103, %104, %105, %106, %107, %108, %109, %110, %111, %112, %113, %114, %115, %116, %117, %118, %119, %120, %121, %122, %123, %124, %125, %126, %127}, a, b, p, 1, 1, 0, 1;\n}\n"
    : "+f"(d[0]), "+f"(d[1]), "+f"(d[2]), "+f"(d[3]), "+f"(d[4]), "+f"(d[5]), "+f"(d[6]), "+f"(d[7]), "+f"(d[8]), "+f"(d[9]), "+f"(d[10]), "+f"(d[11]), "+f"(d[12]), "+f"(d[13]), "+f"(d[14]), "+f"(d[15]), "+f"(d[16]), "+f"(d[17]), "+f"(d[18]), "+f"(d[19]), "+f"(d[20]), "+f"(d[21]), "+f"(d[22]), "+f"(d[23]), "+f"(d[24]), "+f"(d[25]), "+f"(d[26]), "+f"(d[27]), "+f"(d[28]), "+f"(d[29]), "+f"(d[30]), "+f"(d[31]), "+f"(d[32]), "+f"(d[33]), "+f"(d[34]), "+f"(d[35]), "+f"(d[36]), "+f"(d[37]), "+f"(d[38]), "+f"(d[39]), "+f"(d[40]), "+f"(d[41]), "+f"(d[42]), "+f"(d[43]), "+f"(d[44]), "+f"(d[45]), "+f"(d[46]), "+f"(d[47]), "+f"(d[48]), "+f"(d[49]), "+f"(d[50]), "+f"(d[51]), "+f"(d[52]), "+f"(d[53]), "+f"(d[54]), "+f"(d[55]), "+f"(d[56]), "+f"(d[57]), "+f"(d[58]), "+f"(d[59]), "+f"(d[60]), "+f"(d[61]), "+f"(d[62]), "+f"(d[63]), "+f"(d[64]), "+f"(d[65]), "+f"(d[66]), "+f"(d[67]), "+f"(d[68]), "+f"(d[69]), "+f"(d[70]), "+f"(d[71]), "+f"(d[72]), "+f"(d[73]), "+f"(d[74]), "+f"(d[75]), "+f"(d[76]), "+f"(d[77]), "+f"(d[78]), "+f"(d[79]), "+f"(d[80]), "+f"(d[81]), "+f"(d[82]), "+f"(d[83]), "+f"(d[84]), "+f"(d[85]), "+f"(d[86]), "+f"(d[87]), "+f"(d[88]), "+f"(d[89]), "+f"(d[90]), "+f"(d[91]), "+f"(d[92]), "+f"(d[93]), "+f"(d[94]), "+f"(d[95]), "+f"(d[96]), "+f"(d[97]), "+f"(d[98]), "+f"(d[99]), "+f"(d[100]), "+f"(d[101]), "+f"(d[102]), "+f"(d[103]), "+f"(d[104]), "+f"(d[105]), "+f"(d[106]), "+f"(d[107]), "+f"(d[108]), "+f"(d[109]), "+f"(d[110]), "+f"(d[111]), "+f"(d[112]), "+f"(d[113]), "+f"(d[114]), "+f"(d[115]), "+f"(d[116]), "+f"(d[117]), "+f"(d[118]), "+f"(d[119]), "+f"(d[120]), "+f"(d[121]), "+f"(d[122]), "+f"(d[123]), "+f"(d[124]), "+f"(d[125]), "+f"(d[126]), "+f"(d[127])
    : "l"(da), "l"(db), "r"(sd), "n"(OA), "n"(OB));
}
template <int OB> __device__ __forceinline__ void wgmma_rs_tb(float (&d)[128], uint32_t a0, uint32_t a1, uint32_t a2, uint32_t a3, uint64_t db, int sd) {
  asm volatile("{\n.reg .pred p;\n.reg .b64 b;\nadd.s64 b, %132, %134;\nsetp.ne.b32 p, %133, 0;\n"
    "wgmma.mma_async.sync.aligned.m64n256k16.f32.bf16.bf16 {%0, %1, %2, %3, %4, %5, %6, %7, %8, %9, %10, %11, %12, %13, %14, %15, %16, %17, %18, %19, %20, %21, %22, %23, %24, %25, %26, %27, %28, %29, %30, %31, %32, %33, %34, %35, %36, %37, %38, %39, %40, %41, %42, %43, %44, %45, %46, %47, %48, %49, %50, %51, %52, %53, %54, %55, %56, %57, %58, %59, %60, %61, %62, %63, %64, %65, %66, %67, %68, %69, %70, %71, %72, %73, %74, %75, %76, %77, %78, %79, %80, %81, %82, %83, %84, %85, %86, %87, %88, %89, %90, %91, %92, %93, %94, %95, %96, %97, %98, %99, %100, %101, %102, %103, %104, %105, %106, %107, %108, %109, %110, %111, %112, %113, %114, %115, %116, %117, %118, %119, %120, %121, %122, %123, %124, %125, %126, %127}, {%128, %129, %130, %131}, b, p, 1, 1, 1;\n}\n"
    : "+f"(d[0]), "+f"(d[1]), "+f"(d[2]), "+f"(d[3]), "+f"(d[4]), "+f"(d[5]), "+f"(d[6]), "+f"(d[7]), "+f"(d[8]), "+f"(d[9]), "+f"(d[10]), "+f"(d[11]), "+f"(d[12]), "+f"(d[13]), "+f"(d[14]), "+f"(d[15]), "+f"(d[16]), "+f"(d[17]), "+f"(d[18]), "+f"(d[19]), "+f"(d[20]), "+f"(d[21]), "+f"(d[22]), "+f"(d[23]), "+f"(d[24]), "+f"(d[25]), "+f"(d[26]), "+f"(d[27]), "+f"(d[28]), "+f"(d[29]), "+f"(d[30]), "+f"(d[31]), "+f"(d[32]), "+f"(d[33]), "+f"(d[34]), "+f"(d[35]), "+f"(d[36]), "+f"(d[37]), "+f"(d[38]), "+f"(d[39]), "+f"(d[40]), "+f"(d[41]), "+f"(d[42]), "+f"(d[43]), "+f"(d[44]), "+f"(d[45]), "+f"(d[46]), "+f"(d[47]), "+f"(d[48]), "+f"(d[49]), "+f"(d[50]), "+f"(d[51]), "+f"(d[52]), "+f"(d[53]), "+f"(d[54]), "+f"(d[55]), "+f"(d[56]), "+f"(d[57]), "+f"(d[58]), "+f"(d[59]), "+f"(d[60]), "+f"(d[61]), "+f"(d[62]), "+f"(d[63]), "+f"(d[64]), "+f"(d[65]), "+f"(d[66]), "+f"(d[67]), "+f"(d[68]), "+f"(d[69]), "+f"(d[70]), "+f"(d[71]), "+f"(d[72]), "+f"(d[73]), "+f"(d[74]), "+f"(d[75]), "+f"(d[76]), "+f"(d[77]), "+f"(d[78]), "+f"(d[79]), "+f"(d[80]), "+f"(d[81]), "+f"(d[82]), "+f"(d[83]), "+f"(d[84]), "+f"(d[85]), "+f"(d[86]), "+f"(d[87]), "+f"(d[88]), "+f"(d[89]), "+f"(d[90]), "+f"(d[91]), "+f"(d[92]), "+f"(d[93]), "+f"(d[94]), "+f"(d[95]), "+f"(d[96]), "+f"(d[97]), "+f"(d[98]), "+f"(d[99]), "+f"(d[100]), "+f"(d[101]), "+f"(d[102]), "+f"(d[103]), "+f"(d[104]), "+f"(d[105]), "+f"(d[106]), "+f"(d[107]), "+f"(d[108]), "+f"(d[109]), "+f"(d[110]), "+f"(d[111]), "+f"(d[112]), "+f"(d[113]), "+f"(d[114]), "+f"(d[115]), "+f"(d[116]), "+f"(d[117]), "+f"(d[118]), "+f"(d[119]), "+f"(d[120]), "+f"(d[121]), "+f"(d[122]), "+f"(d[123]), "+f"(d[124]), "+f"(d[125]), "+f"(d[126]), "+f"(d[127])
    : "r"(a0), "r"(a1), "r"(a2), "r"(a3), "l"(db), "r"(sd), "n"(OB));
}
template <int OA, int OB> __device__ __forceinline__ void wgmma_ss_tb(float (&d)[96], uint64_t da, uint64_t db, int sd) {
  asm volatile("{\n.reg .pred p;\n.reg .b64 a, b;\nadd.s64 a, %96, %99;\nadd.s64 b, %97, %100;\nsetp.ne.b32 p, %98, 0;\n"
    "wgmma.mma_async.sync.aligned.m64n192k16.f32.bf16.bf16 {%0, %1, %2, %3, %4, %5, %6, %7, %8, %9, %10, %11, %12, %13, %14, %15, %16, %17, %18, %19, %20, %21, %22, %23, %24, %25, %26, %27, %28, %29, %30, %31, %32, %33, %34, %35, %36, %37, %38, %39, %40, %41, %42, %43, %44, %45, %46, %47, %48, %49, %50, %51, %52, %53, %54, %55, %56, %57, %58, %59, %60, %61, %62, %63, %64, %65, %66, %67, %68, %69, %70, %71, %72, %73, %74, %75, %76, %77, %78, %79, %80, %81, %82, %83, %84, %85, %86, %87, %88, %89, %90, %91, %92, %93, %94, %95}, a, b, p, 1, 1, 0, 1;\n}\n"
    : "+f"(d[0]), "+f"(d[1]), "+f"(d[2]), "+f"(d[3]), "+f"(d[4]), "+f"(d[5]), "+f"(d[6]), "+f"(d[7]), "+f"(d[8]), "+f"(d[9]), "+f"(d[10]), "+f"(d[11]), "+f"(d[12]), "+f"(d[13]), "+f"(d[14]), "+f"(d[15]), "+f"(d[16]), "+f"(d[17]), "+f"(d[18]), "+f"(d[19]), "+f"(d[20]), "+f"(d[21]), "+f"(d[22]), "+f"(d[23]), "+f"(d[24]), "+f"(d[25]), "+f"(d[26]), "+f"(d[27]), "+f"(d[28]), "+f"(d[29]), "+f"(d[30]), "+f"(d[31]), "+f"(d[32]), "+f"(d[33]), "+f"(d[34]), "+f"(d[35]), "+f"(d[36]), "+f"(d[37]), "+f"(d[38]), "+f"(d[39]), "+f"(d[40]), "+f"(d[41]), "+f"(d[42]), "+f"(d[43]), "+f"(d[44]), "+f"(d[45]), "+f"(d[46]), "+f"(d[47]), "+f"(d[48]), "+f"(d[49]), "+f"(d[50]), "+f"(d[51]), "+f"(d[52]), "+f"(d[53]), "+f"(d[54]), "+f"(d[55]), "+f"(d[56]), "+f"(d[57]), "+f"(d[58]), "+f"(d[59]), "+f"(d[60]), "+f"(d[61]), "+f"(d[62]), "+f"(d[63]), "+f"(d[64]), "+f"(d[65]), "+f"(d[66]), "+f"(d[67]), "+f"(d[68]), "+f"(d[69]), "+f"(d[70]), "+f"(d[71]), "+f"(d[72]), "+f"(d[73]), "+f"(d[74]), "+f"(d[75]), "+f"(d[76]), "+f"(d[77]), "+f"(d[78]), "+f"(d[79]), "+f"(d[80]), "+f"(d[81]), "+f"(d[82]), "+f"(d[83]), "+f"(d[84]), "+f"(d[85]), "+f"(d[86]), "+f"(d[87]), "+f"(d[88]), "+f"(d[89]), "+f"(d[90]), "+f"(d[91]), "+f"(d[92]), "+f"(d[93]), "+f"(d[94]), "+f"(d[95])
    : "l"(da), "l"(db), "r"(sd), "n"(OA), "n"(OB));
}
template <int OB> __device__ __forceinline__ void wgmma_rs_tb(float (&d)[96], uint32_t a0, uint32_t a1, uint32_t a2, uint32_t a3, uint64_t db, int sd) {
  asm volatile("{\n.reg .pred p;\n.reg .b64 b;\nadd.s64 b, %100, %102;\nsetp.ne.b32 p, %101, 0;\n"
    "wgmma.mma_async.sync.aligned.m64n192k16.f32.bf16.bf16 {%0, %1, %2, %3, %4, %5, %6, %7, %8, %9, %10, %11, %12, %13, %14, %15, %16, %17, %18, %19, %20, %21, %22, %23, %24, %25, %26, %27, %28, %29, %30, %31, %32, %33, %34, %35, %36, %37, %38, %39, %40, %41, %42, %43, %44, %45, %46, %47, %48, %49, %50, %51, %52, %53, %54, %55, %56, %57, %58, %59, %60, %61, %62, %63, %64, %65, %66, %67, %68, %69, %70, %71, %72, %73, %74, %75, %76, %77, %78, %79, %80, %81, %82, %83, %84, %85, %86, %87, %88, %89, %90, %91, %92, %93, %94, %95}, {%96, %97, %98, %99}, b, p, 1, 1, 1;\n}\n"
    : "+f"(d[0]), "+f"(d[1]), "+f"(d[2]), "+f"(d[3]), "+f"(d[4]), "+f"(d[5]), "+f"(d[6]), "+f"(d[7]), "+f"(d[8]), "+f"(d[9]), "+f"(d[10]), "+f"(d[11]), "+f"(d[12]), "+f"(d[13]), "+f"(d[14]), "+f"(d[15]), "+f"(d[16]), "+f"(d[17]), "+f"(d[18]), "+f"(d[19]), "+f"(d[20]), "+f"(d[21]), "+f"(d[22]), "+f"(d[23]), "+f"(d[24]), "+f"(d[25]), "+f"(d[26]), "+f"(d[27]), "+f"(d[28]), "+f"(d[29]), "+f"(d[30]), "+f"(d[31]), "+f"(d[32]), "+f"(d[33]), "+f"(d[34]), "+f"(d[35]), "+f"(d[36]), "+f"(d[37]), "+f"(d[38]), "+f"(d[39]), "+f"(d[40]), "+f"(d[41]), "+f"(d[42]), "+f"(d[43]), "+f"(d[44]), "+f"(d[45]), "+f"(d[46]), "+f"(d[47]), "+f"(d[48]), "+f"(d[49]), "+f"(d[50]), "+f"(d[51]), "+f"(d[52]), "+f"(d[53]), "+f"(d[54]), "+f"(d[55]), "+f"(d[56]), "+f"(d[57]), "+f"(d[58]), "+f"(d[59]), "+f"(d[60]), "+f"(d[61]), "+f"(d[62]), "+f"(d[63]), "+f"(d[64]), "+f"(d[65]), "+f"(d[66]), "+f"(d[67]), "+f"(d[68]), "+f"(d[69]), "+f"(d[70]), "+f"(d[71]), "+f"(d[72]), "+f"(d[73]), "+f"(d[74]), "+f"(d[75]), "+f"(d[76]), "+f"(d[77]), "+f"(d[78]), "+f"(d[79]), "+f"(d[80]), "+f"(d[81]), "+f"(d[82]), "+f"(d[83]), "+f"(d[84]), "+f"(d[85]), "+f"(d[86]), "+f"(d[87]), "+f"(d[88]), "+f"(d[89]), "+f"(d[90]), "+f"(d[91]), "+f"(d[92]), "+f"(d[93]), "+f"(d[94]), "+f"(d[95])
    : "r"(a0), "r"(a1), "r"(a2), "r"(a3), "l"(db), "r"(sd), "n"(OB));
}
template <int OA, int OB> __device__ __forceinline__ void wgmma_ss_tb(float (&d)[64], uint64_t da, uint64_t db, int sd) {
  asm volatile("{\n.reg .pred p;\n.reg .b64 a, b;\nadd.s64 a, %64, %67;\nadd.s64 b, %65, %68;\nsetp.ne.b32 p, %66, 0;\n"
    "wgmma.mma_async.sync.aligned.m64n128k16.f32.bf16.bf16 {%0, %1, %2, %3, %4, %5, %6, %7, %8, %9, %10, %11, %12, %13, %14, %15, %16, %17, %18, %19, %20, %21, %22, %23, %24, %25, %26, %27, %28, %29, %30, %31, %32, %33, %34, %35, %36, %37, %38, %39, %40, %41, %42, %43, %44, %45, %46, %47, %48, %49, %50, %51, %52, %53, %54, %55, %56, %57, %58, %59, %60, %61, %62, %63}, a, b, p, 1, 1, 0, 1;\n}\n"
    : "+f"(d[0]), "+f"(d[1]), "+f"(d[2]), "+f"(d[3]), "+f"(d[4]), "+f"(d[5]), "+f"(d[6]), "+f"(d[7]), "+f"(d[8]), "+f"(d[9]), "+f"(d[10]), "+f"(d[11]), "+f"(d[12]), "+f"(d[13]), "+f"(d[14]), "+f"(d[15]), "+f"(d[16]), "+f"(d[17]), "+f"(d[18]), "+f"(d[19]), "+f"(d[20]), "+f"(d[21]), "+f"(d[22]), "+f"(d[23]), "+f"(d[24]), "+f"(d[25]), "+f"(d[26]), "+f"(d[27]), "+f"(d[28]), "+f"(d[29]), "+f"(d[30]), "+f"(d[31]), "+f"(d[32]), "+f"(d[33]), "+f"(d[34]), "+f"(d[35]), "+f"(d[36]), "+f"(d[37]), "+f"(d[38]), "+f"(d[39]), "+f"(d[40]), "+f"(d[41]), "+f"(d[42]), "+f"(d[43]), "+f"(d[44]), "+f"(d[45]), "+f"(d[46]), "+f"(d[47]), "+f"(d[48]), "+f"(d[49]), "+f"(d[50]), "+f"(d[51]), "+f"(d[52]), "+f"(d[53]), "+f"(d[54]), "+f"(d[55]), "+f"(d[56]), "+f"(d[57]), "+f"(d[58]), "+f"(d[59]), "+f"(d[60]), "+f"(d[61]), "+f"(d[62]), "+f"(d[63])
    : "l"(da), "l"(db), "r"(sd), "n"(OA), "n"(OB));
}
template <int OB> __device__ __forceinline__ void wgmma_rs_tb(float (&d)[64], uint32_t a0, uint32_t a1, uint32_t a2, uint32_t a3, uint64_t db, int sd) {
  asm volatile("{\n.reg .pred p;\n.reg .b64 b;\nadd.s64 b, %68, %70;\nsetp.ne.b32 p, %69, 0;\n"
    "wgmma.mma_async.sync.aligned.m64n128k16.f32.bf16.bf16 {%0, %1, %2, %3, %4, %5, %6, %7, %8, %9, %10, %11, %12, %13, %14, %15, %16, %17, %18, %19, %20, %21, %22, %23, %24, %25, %26, %27, %28, %29, %30, %31, %32, %33, %34, %35, %36, %37, %38, %39, %40, %41, %42, %43, %44, %45, %46, %47, %48, %49, %50, %51, %52, %53, %54, %55, %56, %57, %58, %59, %60, %61, %62, %63}, {%64, %65, %66, %67}, b, p, 1, 1, 1;\n}\n"
    : "+f"(d[0]), "+f"(d[1]), "+f"(d[2]), "+f"(d[3]), "+f"(d[4]), "+f"(d[5]), "+f"(d[6]), "+f"(d[7]), "+f"(d[8]), "+f"(d[9]), "+f"(d[10]), "+f"(d[11]), "+f"(d[12]), "+f"(d[13]), "+f"(d[14]), "+f"(d[15]), "+f"(d[16]), "+f"(d[17]), "+f"(d[18]), "+f"(d[19]), "+f"(d[20]), "+f"(d[21]), "+f"(d[22]), "+f"(d[23]), "+f"(d[24]), "+f"(d[25]), "+f"(d[26]), "+f"(d[27]), "+f"(d[28]), "+f"(d[29]), "+f"(d[30]), "+f"(d[31]), "+f"(d[32]), "+f"(d[33]), "+f"(d[34]), "+f"(d[35]), "+f"(d[36]), "+f"(d[37]), "+f"(d[38]), "+f"(d[39]), "+f"(d[40]), "+f"(d[41]), "+f"(d[42]), "+f"(d[43]), "+f"(d[44]), "+f"(d[45]), "+f"(d[46]), "+f"(d[47]), "+f"(d[48]), "+f"(d[49]), "+f"(d[50]), "+f"(d[51]), "+f"(d[52]), "+f"(d[53]), "+f"(d[54]), "+f"(d[55]), "+f"(d[56]), "+f"(d[57]), "+f"(d[58]), "+f"(d[59]), "+f"(d[60]), "+f"(d[61]), "+f"(d[62]), "+f"(d[63])
    : "r"(a0), "r"(a1), "r"(a2), "r"(a3), "l"(db), "r"(sd), "n"(OB));
}
template <int OA, int OB> __device__ __forceinline__ void wgmma_ss_ta(float (&d)[64], uint64_t da, uint64_t db, int sd) {
  asm volatile("{\n.reg .pred p;\n.reg .b64 a, b;\nadd.s64 a, %64, %67;\nadd.s64 b, %65, %68;\nsetp.ne.b32 p, %66, 0;\n"
    "wgmma.mma_async.sync.aligned.m64n128k16.f32.bf16.bf16 {%0, %1, %2, %3, %4, %5, %6, %7, %8, %9, %10, %11, %12, %13, %14, %15, %16, %17, %18, %19, %20, %21, %22, %23, %24, %25, %26, %27, %28, %29, %30, %31, %32, %33, %34, %35, %36, %37, %38, %39, %40, %41, %42, %43, %44, %45, %46, %47, %48, %49, %50, %51, %52, %53, %54, %55, %56, %57, %58, %59, %60, %61, %62, %63}, a, b, p, 1, 1, 1, 0;\n}\n"
    : "+f"(d[0]), "+f"(d[1]), "+f"(d[2]), "+f"(d[3]), "+f"(d[4]), "+f"(d[5]), "+f"(d[6]), "+f"(d[7]), "+f"(d[8]), "+f"(d[9]), "+f"(d[10]), "+f"(d[11]), "+f"(d[12]), "+f"(d[13]), "+f"(d[14]), "+f"(d[15]), "+f"(d[16]), "+f"(d[17]), "+f"(d[18]), "+f"(d[19]), "+f"(d[20]), "+f"(d[21]), "+f"(d[22]), "+f"(d[23]), "+f"(d[24]), "+f"(d[25]), "+f"(d[26]), "+f"(d[27]), "+f"(d[28]), "+f"(d[29]), "+f"(d[30]), "+f"(d[31]), "+f"(d[32]), "+f"(d[33]), "+f"(d[34]), "+f"(d[35]), "+f"(d[36]), "+f"(d[37]), "+f"(d[38]), "+f"(d[39]), "+f"(d[40]), "+f"(d[41]), "+f"(d[42]), "+f"(d[43]), "+f"(d[44]), "+f"(d[45]), "+f"(d[46]), "+f"(d[47]), "+f"(d[48]), "+f"(d[49]), "+f"(d[50]), "+f"(d[51]), "+f"(d[52]), "+f"(d[53]), "+f"(d[54]), "+f"(d[55]), "+f"(d[56]), "+f"(d[57]), "+f"(d[58]), "+f"(d[59]), "+f"(d[60]), "+f"(d[61]), "+f"(d[62]), "+f"(d[63])
    : "l"(da), "l"(db), "r"(sd), "n"(OA), "n"(OB));
}
template <int OB> __device__ __forceinline__ void wgmma_rs(float (&d)[64], uint32_t a0, uint32_t a1, uint32_t a2, uint32_t a3, uint64_t db, int sd) {
  asm volatile("{\n.reg .pred p;\n.reg .b64 b;\nadd.s64 b, %68, %70;\nsetp.ne.b32 p, %69, 0;\n"
    "wgmma.mma_async.sync.aligned.m64n128k16.f32.bf16.bf16 {%0, %1, %2, %3, %4, %5, %6, %7, %8, %9, %10, %11, %12, %13, %14, %15, %16, %17, %18, %19, %20, %21, %22, %23, %24, %25, %26, %27, %28, %29, %30, %31, %32, %33, %34, %35, %36, %37, %38, %39, %40, %41, %42, %43, %44, %45, %46, %47, %48, %49, %50, %51, %52, %53, %54, %55, %56, %57, %58, %59, %60, %61, %62, %63}, {%64, %65, %66, %67}, b, p, 1, 1, 0;\n}\n"
    : "+f"(d[0]), "+f"(d[1]), "+f"(d[2]), "+f"(d[3]), "+f"(d[4]), "+f"(d[5]), "+f"(d[6]), "+f"(d[7]), "+f"(d[8]), "+f"(d[9]), "+f"(d[10]), "+f"(d[11]), "+f"(d[12]), "+f"(d[13]), "+f"(d[14]), "+f"(d[15]), "+f"(d[16]), "+f"(d[17]), "+f"(d[18]), "+f"(d[19]), "+f"(d[20]), "+f"(d[21]), "+f"(d[22]), "+f"(d[23]), "+f"(d[24]), "+f"(d[25]), "+f"(d[26]), "+f"(d[27]), "+f"(d[28]), "+f"(d[29]), "+f"(d[30]), "+f"(d[31]), "+f"(d[32]), "+f"(d[33]), "+f"(d[34]), "+f"(d[35]), "+f"(d[36]), "+f"(d[37]), "+f"(d[38]), "+f"(d[39]), "+f"(d[40]), "+f"(d[41]), "+f"(d[42]), "+f"(d[43]), "+f"(d[44]), "+f"(d[45]), "+f"(d[46]), "+f"(d[47]), "+f"(d[48]), "+f"(d[49]), "+f"(d[50]), "+f"(d[51]), "+f"(d[52]), "+f"(d[53]), "+f"(d[54]), "+f"(d[55]), "+f"(d[56]), "+f"(d[57]), "+f"(d[58]), "+f"(d[59]), "+f"(d[60]), "+f"(d[61]), "+f"(d[62]), "+f"(d[63])
    : "r"(a0), "r"(a1), "r"(a2), "r"(a3), "l"(db), "r"(sd), "n"(OB));
}
template <int OA, int OB> __device__ __forceinline__ void wgmma_ss_ta(float (&d)[4], uint64_t da, uint64_t db, int sd) {
  asm volatile("{\n.reg .pred p;\n.reg .b64 a, b;\nadd.s64 a, %4, %7;\nadd.s64 b, %5, %8;\nsetp.ne.b32 p, %6, 0;\n"
    "wgmma.mma_async.sync.aligned.m64n8k16.f32.bf16.bf16 {%0, %1, %2, %3}, a, b, p, 1, 1, 1, 0;\n}\n"
    : "+f"(d[0]), "+f"(d[1]), "+f"(d[2]), "+f"(d[3])
    : "l"(da), "l"(db), "r"(sd), "n"(OA), "n"(OB));
}

constexpr uint32_t U = 16384;
constexpr uint32_t SM_QO = 2 * U, SM_W = 8 * U, SM_V = 8 * U, SM_K1 = 12 * U, SM_BAR = 14 * U;
constexpr uint32_t B_WF = SM_BAR, B_KF = SM_BAR + 48, B_CF = SM_BAR + 80, B_GATE = SM_BAR + 128, B_OF = SM_BAR + 136, B_EP = SM_BAR + 144, B_EXT = SM_BAR + 152, B_Q3 = SM_BAR + 168, B_ANN = SM_BAR + 176,
                   B_WE = SM_BAR + 192, B_KE = SM_BAR + 240, B_CE = SM_BAR + 288, B_OS = SM_BAR + 344;
constexpr uint32_t SM_EP = SM_BAR + 384;
constexpr uint32_t SM_ONE = SM_BAR + 388;
constexpr uint32_t SM_STAT = SM_BAR + 400, SM_EXT = SM_STAT + 512;
constexpr uint32_t SM_BAD = SM_EXT + 2048;
constexpr int SMEM_BYTES = SM_BAR + 3072;
__device__ __forceinline__ uint32_t c_slot(int s) { return (0xBADC10u >> (4 * s)) & 15; }

struct Params {
  const __nv_bfloat16 *x, *k, *v, *wq, *wo, *wr;
  __nv_bfloat16* out;
  Scratch* g;
};

__device__ __forceinline__ void release2(uint32_t rbar, int lane) { if (lane < 2) mbar_arrive_cluster(rbar); }
__device__ __forceinline__ void pin_after(uint32_t a, float e0, float e1) {
  asm volatile("{\n.reg .pred p;\nsetp.lt.f32 p, %1, %2;\n@p st.shared.u32 [%0], %0;\n}\n" :: "r"(a), "f"(e0), "f"(-e1) : "memory"); }
__device__ __forceinline__ void lds128_after(uint32_t& x, uint32_t& y, uint32_t& z, uint32_t& w, uint32_t a, float e0, float e1) {
  asm volatile("{\n.reg .pred p;\nsetp.geu.f32 p, %5, %6;\n@p ld.shared.v4.u32 {%0,%1,%2,%3}, [%4];\n}\n" : "+r"(x), "+r"(y), "+r"(z), "+r"(w) : "r"(a), "f"(e0), "f"(-e1) : "memory"); }
__device__ __forceinline__ uint32_t launch_of(unsigned long long ticket) { return (uint32_t)(ticket / 132) + 1; }

__device__ __forceinline__ void attn_slow(float (&o)[64], float& i0, float& i1, const __nv_bfloat16* __restrict__ X, const __nv_bfloat16* __restrict__ WQ, uint32_t st0, uint32_t st1,
                                          const __nv_bfloat16* __restrict__ K, const __nv_bfloat16* __restrict__ V, int lane) {
  uint32_t q[32];
  #pragma unroll
  for (int i = 0; i < 64; i++) o[i] = 0.f;
  const int g = lane >> 2, qd = lane & 3;
  #pragma unroll 1
  for (int k0 = 0; k0 < DM; k0 += 16) {
    uint32_t a[4];
    #pragma unroll
    for (int e = 0; e < 4; e++) {
      const uint32_t xv = *(const uint32_t*)(X + (size_t)(g + (e & 1) * 8) * DM + k0 + (e >> 1) * 8 + 2 * qd);
      const float mb = bf_lo((e & 1) ? st1 : st0);
      a[e] = pack_bf16(bf_lo(xv) - mb, bf_hi(xv) - mb);
    }
    const unsigned short* wr = (const unsigned short*)(WQ + (size_t)(k0 + 2 * qd) * (NH * DH) + g);
    #pragma unroll
    for (int nb = 0; nb < 16; nb++) {
      uint32_t b0 = (uint32_t)wr[nb * 8] | ((uint32_t)wr[nb * 8 + NH * DH] << 16);
      uint32_t b1 = (uint32_t)wr[nb * 8 + 8 * NH * DH] | ((uint32_t)wr[nb * 8 + 9 * NH * DH] << 16);
      asm volatile("mma.sync.aligned.m16n8k16.row.col.f32.bf16.bf16.f32 {%0,%1,%2,%3}, {%4,%5,%6,%7}, {%8,%9}, {%0,%1,%2,%3};"
        : "+f"(o[nb*4]), "+f"(o[nb*4+1]), "+f"(o[nb*4+2]), "+f"(o[nb*4+3]) : "r"(a[0]), "r"(a[1]), "r"(a[2]), "r"(a[3]), "r"(b0), "r"(b1));
    }
  }
  {
    const float r0 = rcp_approx(bf_hi(st0)) * SCALE_LOG2E, r1 = rcp_approx(bf_hi(st1)) * SCALE_LOG2E;
    #pragma unroll
    for (int i = 0; i < 16; i++) { q[2*i] = pack_bf16(o[4*i] * r0, o[4*i+1] * r0); q[2*i+1] = pack_bf16(o[4*i+2] * r1, o[4*i+3] * r1); }
    #pragma unroll
    for (int i = 0; i < 64; i++) o[i] = 0.f;
  }
  float m0 = -INFINITY, m1 = -INFINITY, l0 = 0.f, l1 = 0.f;
  #pragma unroll 1
  for (int n0 = 0; n0 < S_LEN; n0 += 16) {
    float s[8];
    #pragma unroll
    for (int i = 0; i < 8; i++) s[i] = 0.f;
    #pragma unroll
    for (int nb = 0; nb < 2; nb++) {
      const uint32_t* kr = (const uint32_t*)(K + (size_t)(n0 + nb * 8 + g) * DH) + qd;
      #pragma unroll
      for (int kk = 0; kk < 8; kk++) {
        uint32_t b0 = kr[kk * 8], b1 = kr[kk * 8 + 4];
        asm volatile("mma.sync.aligned.m16n8k16.row.col.f32.bf16.bf16.f32 {%0,%1,%2,%3}, {%4,%5,%6,%7}, {%8,%9}, {%0,%1,%2,%3};"
          : "+f"(s[nb*4]), "+f"(s[nb*4+1]), "+f"(s[nb*4+2]), "+f"(s[nb*4+3]) : "r"(q[kk*4]), "r"(q[kk*4+1]), "r"(q[kk*4+2]), "r"(q[kk*4+3]), "r"(b0), "r"(b1));
      }
    }
    float x0 = fmaxf(fmaxf(s[0], s[1]), fmaxf(s[4], s[5])), x1 = fmaxf(fmaxf(s[2], s[3]), fmaxf(s[6], s[7]));
    x0 = fmaxf(x0, __shfl_xor_sync(0xffffffff, x0, 1)); x1 = fmaxf(x1, __shfl_xor_sync(0xffffffff, x1, 1));
    x0 = fmaxf(x0, __shfl_xor_sync(0xffffffff, x0, 2)); x1 = fmaxf(x1, __shfl_xor_sync(0xffffffff, x1, 2));
    const float n0m = fmaxf(m0, x0), n1m = fmaxf(m1, x1);
    const float sh0 = (n0m == -INFINITY) ? 0.f : n0m, sh1 = (n1m == -INFINITY) ? 0.f : n1m;
    const float c0 = ex2(m0 - sh0), c1 = ex2(m1 - sh1);
    m0 = n0m; m1 = n1m;
    s[0] = ex2(s[0] - sh0); s[1] = ex2(s[1] - sh0); s[4] = ex2(s[4] - sh0); s[5] = ex2(s[5] - sh0);
    s[2] = ex2(s[2] - sh1); s[3] = ex2(s[3] - sh1); s[6] = ex2(s[6] - sh1); s[7] = ex2(s[7] - sh1);
    l0 = l0 * c0 + (s[0] + s[1]) + (s[4] + s[5]); l1 = l1 * c1 + (s[2] + s[3]) + (s[6] + s[7]);
    const uint32_t a0 = pack_bf16(s[0], s[1]), a1 = pack_bf16(s[2], s[3]), a2 = pack_bf16(s[4], s[5]), a3 = pack_bf16(s[6], s[7]);
    const unsigned short* vr = (const unsigned short*)(V + (size_t)(n0 + 2 * qd) * DH + g);
    #pragma unroll
    for (int nb = 0; nb < 16; nb++) {
      uint32_t b0 = (uint32_t)vr[nb * 8] | ((uint32_t)vr[nb * 8 + DH] << 16);
      uint32_t b1 = (uint32_t)vr[nb * 8 + 8 * DH] | ((uint32_t)vr[nb * 8 + 9 * DH] << 16);
      o[nb*4] *= c0; o[nb*4+1] *= c0; o[nb*4+2] *= c1; o[nb*4+3] *= c1;
      asm volatile("mma.sync.aligned.m16n8k16.row.col.f32.bf16.bf16.f32 {%0,%1,%2,%3}, {%4,%5,%6,%7}, {%8,%9}, {%0,%1,%2,%3};"
        : "+f"(o[nb*4]), "+f"(o[nb*4+1]), "+f"(o[nb*4+2]), "+f"(o[nb*4+3]) : "r"(a0), "r"(a1), "r"(a2), "r"(a3), "r"(b0), "r"(b1));
    }
  }
  l0 += __shfl_xor_sync(0xffffffff, l0, 1); l1 += __shfl_xor_sync(0xffffffff, l1, 1);
  l0 += __shfl_xor_sync(0xffffffff, l0, 2); l1 += __shfl_xor_sync(0xffffffff, l1, 2);
  i0 = rcp_approx(l0); i1 = rcp_approx(l1);
}

__device__ __forceinline__ void flag_if(uint32_t a, bool c) { asm volatile("{\n.reg .pred p;\nsetp.ne.u32 p, %1, 0;\n@p st.shared.u8 [%0], 1;\n}\n" :: "r"(a), "r"((uint32_t)c) : "memory"); }
__device__ __forceinline__ void row_scale(float& l0, float& l1, int one, uint32_t flag) {
  l0 += __shfl_xor_sync(0xffffffff, l0, one); l1 += __shfl_xor_sync(0xffffffff, l1, one);
  l0 += __shfl_xor_sync(0xffffffff, l0, 2); l1 += __shfl_xor_sync(0xffffffff, l1, 2);
  flag_if(flag, !((l0 >= 0.00390625f) && (l0 <= 1.8446744e19f) && (l1 >= 0.00390625f) && (l1 <= 1.8446744e19f)));
  l0 = rcp_fast(l0); l1 = rcp_fast(l1);
}
__device__ __forceinline__ uint32_t taint(uint32_t z, uint32_t a, uint32_t b) { asm("fma.rn.bf16x2 %0, %1, %2, %0;" : "+r"(z) : "r"(a), "r"(b)); return z; }
__device__ __forceinline__ bool tainted(uint32_t z) { return (taint(0u, z, 0u) & 0x7fff7fffu) != 0; }

__device__ __forceinline__ int kv_tile(int j) { return j < 32 ? j ^ 16 : j; }
__device__ __forceinline__ uint32_t qo_slot(int h) { return SM_QO + ((0x3102 >> (4 * h)) & 3) * 2 * U; }
__device__ __forceinline__ uint32_t o_addr(uint32_t wr, int lane) { return wr + (lane & 15) * 128 + (((lane >> 4) ^ (lane & 7)) << 4); }
template <bool CHECK> __device__ __forceinline__ uint32_t store_o(uint32_t a, const float (&o)[64], float i0, float i1) {
  uint32_t z = 0;
  #pragma unroll
  for (int i = 0; i < 8; i++) {
    const uint32_t w0 = pack_bf16(o[8*i] * i0, o[8*i+1] * i0), w1 = pack_bf16(o[8*i+2] * i1, o[8*i+3] * i1), w2 = pack_bf16(o[8*i+4] * i0, o[8*i+5] * i0), w3 = pack_bf16(o[8*i+6] * i1, o[8*i+7] * i1);
    stsm4((a ^ ((i & 3) << 5)) + (i >> 2) * U, w0, w1, w2, w3);
    if (CHECK) z = taint(taint(z, w0, w1), w2, w3);
  }
  return z;
}

__device__ __noinline__ void redo_heads(const Params& P, uint32_t sb, uint32_t bad, int row0, int head0) {
  const int lane = threadIdx.x & 31;
  const uint32_t st0 = lds32(sb + SM_STAT + ((row0 & 127) + (lane >> 2)) * 4), st1 = lds32(sb + SM_STAT + ((row0 & 127) + 8 + (lane >> 2)) * 4);
  #pragma unroll 1
  for (int h = 0; h < 4; h++) {
    if (!((bad >> (8 * h)) & 1)) continue;
    float o[64], i0, i1;
    const int head = head0 + (kv_tile(h * 16) >> 4);
    attn_slow(o, i0, i1, P.x + (size_t)row0 * DM, P.wq + head * DH, st0, st1, P.k + (size_t)head * S_LEN * DH, P.v + (size_t)head * S_LEN * DH, lane);
    store_o<false>(o_addr(sb + (row0 & 127) * 128, lane) + qo_slot(h), o, i0, i1);
  }
}

template <int K> struct IC { static constexpr int v = K; };
template <int K, int N, class F> __device__ __forceinline__ void static_for(F&& f) { if constexpr (K < N) { f(IC<K>{}); static_for<K + 1, N>(f); } }
template <uint32_t OFF, int SITE> __device__ __forceinline__ void mma_qk(float (&s)[64], const uint32_t (&q)[32], uint64_t d0) {
  wg_fence();
  static_for<0, 8>([&](auto kc) { constexpr int k = decltype(kc)::v; wgmma_rs<doff(OFF, 16) - SITE + (k / 4) * 1024 + (k % 4) * 2>(s, q[k*4], q[k*4+1], q[k*4+2], q[k*4+3], d0, k > 0); });
  wg_commit();
}
template <uint32_t OFF, int SITE> __device__ __forceinline__ void mma_pv(float (&o)[64], const uint32_t (&p)[32], uint64_t d0, bool keep) {
  wg_fence();
  static_for<0, 8>([&](auto kc) { constexpr int k = decltype(kc)::v; wgmma_rs_tb<doff(OFF, U) - SITE + k * 128>(o, p[k*4], p[k*4+1], p[k*4+2], p[k*4+3], d0, (k > 0) || keep); });
  wg_commit();
}
template <int I0, int I1>
__device__ __forceinline__ void exp_rows(float (&s)[64], float (&l)[2]) {
  #pragma unroll
  for (int i = I0; i < I1; i += 2) {
    s[i] = ex2(s[i]); s[i+1] = ex2(s[i+1]);
    l[(i >> 1) & 1] += s[i] + s[i+1];
  }
}

template <int KS, bool EDGE>
__device__ __forceinline__ void attn_step(uint32_t sb, uint32_t rb, uint32_t wr, uint32_t qa, int wg, int lane, int j, int ph, float (&s)[64], float (&o)[64], uint32_t (&p)[32], uint32_t (&q)[32],
                                          float (&l)[2], Scratch* g, unsigned (&tz)[3]) {
  constexpr bool FIRST = EDGE && !KS, LAST = EDGE && KS;
  TRACEF(2, wg, 32 + j);
  STALL(1);
  mbar_wait(sb + B_KF + KS * 8, ph);
  bar_sync(1 + wg, 256);
  mma_qk<KS * SM_K1, EDGE>(s, q, desc(sb, EDGE));
  mbar_wait(sb + B_KF + 24 - KS * 8, KS ? ph : ph ^ 1);
  mma_pv<SM_V + (1 - KS) * 2 * U, EDGE>(o, p, desc(sb, EDGE), !KS || LAST || ((j & 15) != 1));
  bar_arrive(1 + (wg ^ 1), 256);
  const int one = FIRST ? lds32(sb + SM_ONE) : 1;
  wg_wait<1>();
  fence_regs(s);
  release2(rb + B_KE + KS * 8, lane);
  float i0 = l[0], i1 = l[1];
  if (FIRST) { row_scale(i0, i1, one, sb + SM_BAD - 1 + ((wr - sb) >> 9) + (j >> 4)); l[0] = fminf(i0, 0.f); l[1] = fminf(i1, 0.f); }
  constexpr int DP = FIRST ? DPOSF : (LAST && DPOS < 7 * QSP ? 7 * QSP : DPOS);
  if (LAST) {
    fence_regs(q);
    const uint32_t a = qa + qo_slot(j >> 4);
    static_for<0, 8>([&](auto ic) { constexpr int i = decltype(ic)::v;
      lds128_after(q[4*i], q[4*i+1], q[4*i+2], q[4*i+3], a + (i >> 2) * U + (i & 3) * 512, l[0], l[1]);
      exp_rows<i * QSP, i < 7 ? (i + 1) * QSP : DP>(s, l);
    });
  } else exp_rows<0, DP>(s, l);
  pin_after(sb + SM_BAD, l[0], l[1]);
  exp_rows<DP, 64>(s, l);
  wg_wait<0>();
  fence_regs(o); fence_regs(p);
  release2(rb + B_KE + 24 - KS * 8, lane);
  if (FIRST) {
    const int h = (j >> 4) - 1;
    store_o<false>(o_addr(wr, lane) + qo_slot(h), o, i0, i1);
    if (lane == 0) mbar_arrive(sb + B_OS + h * 8);
  }
  #pragma unroll
  for (int i = 0; i < 32; i++) p[i] = pack_bf16(s[2*i], s[2*i+1]);
}

template <int SITE> __device__ __forceinline__ void mma_c(float (&acc)[64], uint32_t sb, int slot, int h, int arrive_bar) {
  const uint64_t a = desc(sb, c_slot(slot) * 1024 + SITE), b = desc(sb, h * 2048 + SITE);
  wg_fence();
  static_for<0, 8>([&](auto kc) { constexpr int k = decltype(kc)::v;
    wgmma_ss_ta<doff(0, 16) - SITE + k * 128, doff(SM_QO, 16) - SITE + (k >> 2) * 1024 + (k & 3) * 2>(acc, a, b, k > 0 || h > 0);
  });
  wg_commit();
  if (arrive_bar) bar_arrive(arrive_bar, 256);
}

__device__ __forceinline__ void side_cta(const Params& P, const CUtensorMap* tmX, const CUtensorMap* tmW, const CUtensorMap* tmG, const CUtensorMap* tmU,
                                         const CUtensorMap* tmD, uint32_t sb, int m) {
  const int tid = threadIdx.x, warp = __shfl_sync(0xffffffff, tid >> 5, 0), lane = tid & 31;
  const uint32_t XS = sb + 12 * U, HS = XS + 10240, BF = sb + SM_BAR, BE = BF + 96, XF = BE + 96, XE = XF + 32, BW = XE + 32, SEL = BW + 16, KEY = SEL + 64;
  Scratch* const g = P.g;
  const int nj = m < 3 ? 14 : 12, nd = m < 3 ? 4 : 3, f0 = m * 448;
  if (elect_one()) { mbar_init(BF + warp * 8, 1); mbar_init(BE + warp * 8, 4); if (warp < 9) mbar_init(XF + warp * 8, (warp & 4) ? 8 : 1); }
  if (tid == 32) sts32(SEL + 32, launch_of(atomicAdd(&g->ticket, 1ull)));
  __syncthreads();
  const uint32_t launch = lds32(SEL + 32);
  if (warp == 0) {
    if (elect_one()) {
      mbar_expect_tx(BW, 10 * U);
      #pragma unroll 1
      for (int i = 0; i < 10; i++) tma_load_2d(sb + i * U, tmW, BW, m * 1024 + (i < 5 ? 448 : 960), (i < 5 ? i : i - 5) * 128);
    }
    #pragma unroll 1
    for (int n = 0, qt = 0, c = 0; n < 160; n++) {
      const uint32_t bar = XF + (n & 3) * 8;
      mbar_wait(bar + 32, ((n >> 2) & 1) ^ 1);
      if (elect_one()) {
        mbar_expect_tx(bar, U);
        tma_load_2d(sb + (10 + (n & 3)) * U, tmX, bar, c * 64, qt * 128);
        if (c == 0 && qt < 15) l2_prefetch(P.x + (size_t)(qt * 128 + 128 + m * 32) * DM, 32 * DM * 2);
      }
      if (++c == 10) { c = 0; qt++; }
    }
  } else if (warp < 3) {
    #pragma unroll 1
    for (int qt = 0; qt < 16; qt++) {
      bar_sync(1 + warp, 160);
      if (lane == 0) flag_add_release(&g->q3_done[m].v);
      __syncwarp();
    }
  } else if (warp >= 4) {
    float acc[64], cs[32];
    mbar_wait(BW, 0);
    #pragma unroll 1
    for (int c = 0; c < 10; c++) {
      wg_fence();
      static_for<0, 4>([&](auto kc) { constexpr int k = decltype(kc)::v;
        wgmma_rs_tb<doff(0, 5 * U) + k * 128>(acc, 0x3f803f80u, 0x3f803f80u, 0x3f803f80u, 0x3f803f80u, desc(sb, c * 512), k || c); });
      wg_commit();
      wg_wait<0>();
    }
    fence_regs(acc);
    #pragma unroll
    for (int i = 0; i < 32; i++) cs[i] = -acc[(i >> 1) * 4 + (i & 1)];
    fence_regs(cs);
    #pragma unroll 1
    for (int qt = 0, n = 0; qt < 16; qt++) {
      const uint32_t* const sp = g->stat + qt * 128 + (warp - 4) * 16 + (lane >> 2);
      uint32_t st0, st1;
      #pragma unroll 1
      for (int c = 0; c < 10; c++, n++) {
        const uint64_t a = desc(sb, (n & 3) * 1024 + (warp >> 3) * 512), b = desc(sb, c * 512);
        mbar_wait(XF + (n & 3) * 8, (n >> 2) & 1);
        wg_fence();
        static_for<0, 4>([&](auto kc) { constexpr int k = decltype(kc)::v; wgmma_ss_tb<doff(10 * U, 16) + k * 2, doff(0, 5 * U) + k * 128>(acc, a, b, k || c); });
        wg_commit();
        if (c == 9) { st0 = ldg32(sp); st1 = ldg32(sp + 8); }
        wg_wait<1>();
        if (c && lane == 0) mbar_arrive(XE + ((n - 1) & 3) * 8);
      }
      #pragma unroll 1
      for (int it = 0; __any_sync(0xffffffff, tag_miss(st0, st1, launch << 31) >> 31) && it < MAXPOLL; it++) { st0 = ldg32(sp); st1 = ldg32(sp + 8); }
      st0 &= 0x7fffffffu; st1 &= 0x7fffffffu;
      const float rs[2] = {rcp_fast(bf_hi(st0)) * SCALE_LOG2E, rcp_fast(bf_hi(st1)) * SCALE_LOG2E}, nm[2] = {bf_lo(st0), bf_lo(st1)};
      wg_wait<0>();
      fence_regs(acc);
      if (lane == 0) mbar_arrive(XE + ((n - 1) & 3) * 8);
      STALL(7);
      uint4* const dst = g->q3 + (qt * 8 + m * 2) * 1024 + (warp - 4) * 128 + lane;
      #pragma unroll
      for (int e = 0; e < 8; e++) {
        uint32_t w[4];
        #pragma unroll
        for (int i = 0; i < 4; i++)
          w[i] = pack_bf16(fmaf(nm[i & 1], cs[4*e + (i & 2)], acc[8*e + 2*i]) * rs[i & 1], fmaf(nm[i & 1], cs[4*e + (i & 2) + 1], acc[8*e + 2*i + 1]) * rs[i & 1]);
        dst[(e >> 2) * 1024 + (e & 3) * 32] = make_uint4(w[0], w[1], w[2], w[3]);
      }
      bar_sync(1 + (warp >> 2), 160);
    }
  }
  if (tid == 96) flag_wait(&g->cnt_gate.v, launch * 256);
  __syncthreads();
  TRACE(0, 1);
  if (tid >= 256 && tid < 320) sts128(HS + 3072 + tid * 16, 0, 0, 0, 0);
  if (warp < 4) {
    uint4 k4[4];
    #pragma unroll
    for (int i = 0; i < 4; i++) k4[i] = ld_relaxed4(g->key + warp * 512 + i * 128 + lane * 4);
    uint32_t bound = 0;
    #pragma unroll 1
    for (int c = 0; c < TOPC; c++) {
      uint32_t b = 0;
      #pragma unroll
      for (int i = 0; i < 4; i++) b = max(max(max(b, k4[i].x - bound), k4[i].y - bound), max(k4[i].z - bound, k4[i].w - bound));
      bound += __reduce_max_sync(0xffffffff, b);
      if (lane == 0) sts32(KEY + (warp * TOPC + c) * 4, bound);
    }
    bar_sync(1, 128);
    const uint32_t v = lds32(KEY + lane * 4);
    int n = 0;
    #pragma unroll 1
    for (int j = 0; j < 32; j++) n += __shfl_sync(0xffffffff, v, j) > v;
    if (n < TOPC) sts32(SEL + n * 4, v);
  }
  __syncthreads();
  #pragma unroll 1
  for (int i = tid; i < TOPC * 80; i += 384) {
    const int row = 0xffff - (lds32(SEL + (i & 7) * 4) & 0xffff);
    const uint32_t st = ldg32(g->stat + row), m2 = __byte_perm(st, 0, 0x1010);
    const float rsd = rcp_fast(bf_hi(st & 0x7fffffffu));
    const uint4 v = ldg_nc((const uint4*)(P.x + (size_t)row * DM) + (i >> 3));
    sts128(XS + i * 16, norm2(v.x, m2, rsd), norm2(v.y, m2, rsd), norm2(v.z, m2, rsd), norm2(v.w, m2, rsd));
  }
  proxy_fence();
  __syncthreads();
  TRACE(0, 2);
  uint32_t sl = 0, ph = 0;
  if (warp == 0) {
    #pragma unroll 1
    for (int job = 0; job < nj + 10; job++) {
      const bool up = job < nj;
      #pragma unroll 1
      for (int i = 0; i < (up ? 5 : nd); i++) {
        mbar_wait(BE + sl * 8, ph ^ 1);
        if (elect_one()) {
          mbar_expect_tx(BF + sl * 8, U);
          tma_load_2d(sb + sl * U, up ? ((job & 1) ? tmU : tmG) : tmD, BF + sl * 8, up ? f0 + (job >> 1) * 64 : (job - nj) * 64, (up ? 0 : f0) + i * 128);
        }
        if (++sl == 12) { sl = 0; ph ^= 1; }
      }
    }
  } else if ((warp >> 2) == 1) {
    float gs[4];
    #pragma unroll 1
    for (int job = 0; job < nj + 10; job++) {
      const bool up = job < nj;
      if (job == nj) { proxy_fence(); bar_sync(1, 128); }
      float ac[4][4], acc[4];
      uint32_t prev = 0;
      #pragma unroll 1
      for (int i = 0; i < (up ? 5 : nd); i++) {
        const uint64_t a = desc(sb, sl * 1024 + 0x10000), b = (uint64_t)(desc_lo(up ? XS : HS, 128) + i * 128) | (8ull << 32);
        mbar_wait(BF + sl * 8, ph);
        wg_fence();
        static_for<0, 8>([&](auto kc) { constexpr int k = decltype(kc)::v; wgmma_ss_ta<k * 128, k * 16>(ac[k & 3], a, b, k > 3 || i > 0); });
        wg_commit();
        wg_wait<1>();
        if (i && lane == 0) mbar_arrive(prev);
        prev = BE + sl * 8;
        if (++sl == 12) { sl = 0; ph ^= 1; }
      }
      wg_wait<0>();
      if (lane == 0) mbar_arrive(prev);
      #pragma unroll
      for (int e = 0; e < 4; e++) fence_regs(ac[e]);
      #pragma unroll
      for (int e = 0; e < 4; e++) acc[e] = (ac[0][e] + ac[1][e]) + (ac[2][e] + ac[3][e]);
      STALL(9);
      const int f = (warp & 3) * 16 + (lane >> 2), tk = (lane & 3) * 2;
      if (!up) {
        float* y = g->ypart + (m * DM + (job - nj) * 64 + f) * TOPC + tk;
        *(float2*)y = make_float2(acc[0], acc[1]); *(float2*)(y + 8 * TOPC) = make_float2(acc[2], acc[3]);
      } else {
        #pragma unroll
        for (int e = 0; e < 4; e++) {
          const float z = rbf(acc[e]);
          if (job & 1) asm volatile("st.shared.u16 [%0], %1;" :: "r"(HS + (job >> 1) * 1024 + ((f >> 3) + (e >> 1)) * 128 + (tk + (e & 1)) * 16 + (f & 7) * 2), "h"((uint16_t)pack_bf16(gs[e] * z, 0.f)) : "memory");
          gs[e] = rbf(z * sigmoid_f(z));
        }
      }
    }
  }
  __syncthreads();
  TRACE(0, 3);
  if (tid == 0) { flag_add_release(&g->cnt_mod.v); flag_wait(&g->cnt_mod.v, launch * 4, 50); }
  __syncthreads();
  #pragma unroll 1
  for (int i = tid; i < 2 * DM; i += 384) {
    const int t = 2 * m + (i & 1), col = i >> 1;
    const uint32_t key = lds32(SEL + t * 4);
    const float* yp = g->ypart + col * TOPC + t;
    const float y = rbf((__ldcg(yp) + __ldcg(yp + TOPC * DM)) + (__ldcg(yp + 2 * TOPC * DM) + __ldcg(yp + 3 * TOPC * DM)));
    const float rs = rbf(sigmoid_f(bf_hi((key >> 31) ? key & 0x7fffffffu : ~key)));
    const uint32_t xn = lds32(XS + (col >> 3) * 128 + t * 16 + (col & 6) * 2);
    const float z = rbf(((col & 1) ? bf_hi(xn) : bf_lo(xn)) + rbf(y * rs));
    g->gate[(size_t)(0xffff - (key & 0xffff)) * DM + col] = __float2bfloat16_rn(z * sigmoid_f(z));
  }
  __syncthreads();
  if (tid == 0) flag_add_release(&g->mod_done.v);
  TRACE(0, 4);
}

__global__ void __cluster_dims__(2, 1, 1) __launch_bounds__(384, 1) fused_kernel(const __grid_constant__ CUtensorMap tmX, const __grid_constant__ CUtensorMap tmW4,
    const __grid_constant__ CUtensorMap tmW3, const __grid_constant__ CUtensorMap tmW1,
    const __grid_constant__ CUtensorMap tmK, const __grid_constant__ CUtensorMap tmV, const __grid_constant__ CUtensorMap tmWO,
    const __grid_constant__ CUtensorMap tmG, const __grid_constant__ CUtensorMap tmU, const __grid_constant__ CUtensorMap tmD,
    const __grid_constant__ CUtensorMap tmGate, const __grid_constant__ Params P) {
  extern __shared__ __align__(1024) uint8_t smem_raw[];
  const uint32_t sb = smem_u32(smem_raw);
  const int tid = threadIdx.x, lane = tid & 31;
  const int rank = blockIdx.x & 1, cl = blockIdx.x >> 1;
  if (cl >= 64) {
    side_cta(P, &tmX, &tmW1, &tmG, &tmU, &tmD, sb, blockIdx.x & 3);
    return;
  }
  const int rr = ((cl - 36) * 37) >> 8, kk = cl - 36 - rr * 7, qp = sel_lt(cl, 4, PH, sel_lt(cl, 36, (cl - 4) & 7, kk + sel_lt(kk, PH, 0, 1)));
  const int hg = sel_lt(cl, 4, cl + 4, sel_lt(cl, 36, (cl - 4) >> 3, 4 + rr)), qt = qp * 2 + rank;
  const int warp = __shfl_sync(0xffffffff, tid >> 5, 0), wgi = warp >> 2;
  Scratch* const g = P.g;
  if (elect_one()) {
    #pragma unroll
    for (int i = 0; i < 4; i++) mbar_init(sb + SM_BAR + warp * 32 + i * 8, 1 << ((0x333444000000ull >> (4 * warp)) & 7));
    if (warp == 0) {
      mbar_expect_tx(sb + B_WF, 2 * U);
      tma_load_2d(sb + 2 * U, &tmX, sb + B_WF, 0, qt * 128);
      tma_load_3d(sb + SM_W, &tmW4, sb + B_WF, 0, 0, hg * 8);
      tma_load_3d(sb + SM_W + 8192, &tmW4, sb + B_WF, 0, 16, hg * 8);
    }
    asm volatile("fence.mbarrier_init.release.cluster;" ::: "memory");
  }
  __syncwarp();
  cluster_arrive();
  unsigned long long ticket = 0;
  if (tid == 64) asm volatile("atom.relaxed.gpu.global.add.u64 %0, [%1], 1;" : "=l"(ticket) : "l"(&g->ticket) : "memory");
  cluster_wait();
  if (warp == 0 && elect_one()) {
    #pragma unroll
    for (int i = 1; i < 6; i++) {
      mbar_expect_tx(sb + B_WF + i * 8, (i & 1) ? U : 2 * U);
      tma_load_3d_mc(sb + SM_W + i * U + rank * 8192, &tmW4, sb + B_WF + i * 8, 0, i * 32 + rank * 16, hg * 8);
      if (!(i & 1)) tma_load_2d(sb + (2 + i / 2) * U, &tmX, sb + B_WF + i * 8, i * 32, qt * 128);
    }
  }
  STALL(14);
  if (wgi == 0) {
    asm volatile("setmaxnreg.dec.sync.aligned.u32 56;");
    uint32_t w0 = 0;
    if (warp == 1 || warp == 2) {
      if (warp == 2 && lane < 12) sts128(sb + SM_EXT + 1024 + (lane >= 6 ? 1024 - 96 : 0) + lane * 16, 0, 0, 0, 0);
      __syncwarp();
      if (tid == 64) { sts32(sb + SM_ONE, 1); sts32(sb + SM_EP, launch_of(ticket)); mbar_arrive(sb + B_EP); }
      __syncwarp();
      mbar_pace(sb + B_WF, 0);
      TRACEO(1);
      auto warm = [&](int ps, int i0, int i1) {
        const uint32_t o = (((qt >> 2) * 4 + (lane & 3) + (lane >> 2) * 16) * (NH * DH) + hg * 512 + ps * 256 + (qt & 3) * 64) * 2;
        #pragma unroll 1
        for (int i = i0; i < i1; i++) {
          asm volatile("prefetch.global.L2 [%0];" :: "l"(at<char>(P.wq, o + i * 256 * (NH * DH))) : "memory");
          if (ps) __nanosleep(300);
        }
      };
      if (elect_one()) l2_prefetch(P.x + (size_t)(qt * 128 + hg * 16 + warp * 8 - 6) * DM, 6 * DM * 2);
      if (warp == 1) warm(0, 1, 5);
      auto publish = [&](uint32_t w) { if (!(lane & 12)) st_relaxed(at<uint32_t>(g->stat, (qt * 128 + hg * 16 + (warp - 1) * 8 + (lane & 3) * 2 + (lane >> 4)) * 4), w ^ (lds32(sb + SM_EP) << 31)); };
      mbar_wait(sb + B_EP, 0);
      publish(0x80000000u);
      const int r0 = qt * 128 + hg * 16 + (warp - 1) * 8 + (lane >> 4);
      const uint32_t e = r0 * DM * 2 + (lane & 15) * 16;
      uint4 vn[5];
      #pragma unroll
      for (int i = 0; i < 5; i++) vn[i] = ldg_nc(at<uint4>(P.x, e) + i * 16);
      #pragma unroll 1
      for (int it = 0; it < 4; it++) {
        uint4 v[5];
        #pragma unroll
        for (int i = 0; i < 5; i++) { v[i] = vn[i]; if (it < 3) vn[i] = ldg_nc(at<uint4>(P.x, e + (it + 1) * 2560) + i * 16); }
        const float x0 = bf_lo(__shfl_sync(0xffffffff, v[0].x, lane & 16));
        float m1 = 0.f, s1 = 0.f;
        #pragma unroll
        for (int i = 0; i < 5; i++) {
          const uint32_t vw[4] = {v[i].x, v[i].y, v[i].z, v[i].w};
          #pragma unroll
          for (int k = 0; k < 4; k++) { const float d0 = bf_lo(vw[k]) - x0, d1 = bf_hi(vw[k]) - x0; m1 += d0 + d1; s1 = fmaf(d0, d0, fmaf(d1, d1, s1)); }
        }
        #pragma unroll
        for (int o = 8; o; o >>= 1) { m1 += __shfl_xor_sync(0xffffffff, m1, o); s1 += __shfl_xor_sync(0xffffffff, s1, o); }
        const float md = m1 * (1.f / DM), var = fmaxf(fmaf(-md, md, s1 * (1.f / DM)), 0.f);
        if ((lane & 15) == it) w0 = pack_bf16(x0 + md, sqrt_approx(rbf(rbf(var) + 1e-5f)));
      }
      STALL(5);
      publish(w0 & 0x7fffffffu);
      TRACE1(2, 8);
      if (warp == 1) warm(1, 0, 5);
    }
        if (warp >= 2) {
      const int ps = 3 - warp;
      {
        const uint4* src = at<uint4>(P.wq, (((qt >> 2) * 4 + (lane >> 3)) * (NH * DH) + hg * 512 + ps * 256 + (qt & 3) * 64 + (lane & 7) * 8) * 2);
        const uint32_t mine = ((hg * 2 + ps) * 256 + qt * 16 + (lane & 7) * 2 + (lane >> 4)) * 16;
        float cs[8];
        #pragma unroll
        for (int e = 0; e < 8; e++) cs[e] = 0.f;
        #pragma unroll 1
        for (int b = 0; b < 5; b++, src += 8 * 16 * 512) {
          uint4 w[8];
          #pragma unroll
          for (int i = 0; i < 8; i++) w[i] = ldg_nc(src + i * 16 * 512);
          #pragma unroll
          for (int i = 0; i < 8; i++) add8(cs, w[i]);
          if (b == 0) {
            mbar_wait(sb + B_EP, 0);
            if (!(lane & 8)) st_tagged(at<uint4>(g->cs, mine), ~lds32(sb + SM_EP) & 1, 0, 0, 0);
          }
        }
        #pragma unroll
        for (int e = 0; e < 4; e++) {
          cs[e] = ((lane & 16) ? cs[e + 4] : cs[e]) + __shfl_xor_sync(0xffffffff, (lane & 16) ? cs[e] : cs[e + 4], 16);
          cs[e] += __shfl_xor_sync(0xffffffff, cs[e], 8);
        }
        STALL(6);
        mbar_wait(sb + B_EP, 0);
        const uint32_t tm = 0u - (lds32(sb + SM_EP) & 1);
        const uint4* const gc = at<uint4>(g->cs, ((hg * 2 + ps) * 256 + lane) * 16);
        if (!(lane & 8)) st_tagged(at<uint4>(g->cs, mine), (__float_as_uint(cs[0]) & ~1u) | (tm & 1), __float_as_uint(cs[1]), __float_as_uint(cs[2]), __float_as_uint(cs[3]));

        uint4 v[9];
        int it = 0;
        uint32_t miss;
        do {
          #pragma unroll
          for (int i = 0; i < 8; i++) v[i] = ld_tagged(gc + i * 32);
          v[8] = ld_relaxed4(at<uint4>(g->stat, qt * 512 + lane * 16));
          miss = (tag_miss(v[8].x, v[8].y, tm) | tag_miss(v[8].z, v[8].w, tm)) >> 31;
          #pragma unroll
          for (int i = 0; i < 8; i += 2) miss |= tag_miss(v[i].x, v[i+1].x, tm);
        } while (__any_sync(0xffffffff, miss & 1) && ++it < MAXPOLL);
        #pragma unroll
        for (int i = 0; i < 2; i++) {
          auto sum = [](uint32_t a, uint32_t b, uint32_t c, uint32_t d) { return (__uint_as_float(a) + __uint_as_float(b)) + (__uint_as_float(c) + __uint_as_float(d)); };
          const float c0 = sum(v[i].x, v[i+2].x, v[i+4].x, v[i+6].x), c1 = sum(v[i].y, v[i+2].y, v[i+4].y, v[i+6].y);
          const float c2 = sum(v[i].z, v[i+2].z, v[i+4].z, v[i+6].z), c3 = sum(v[i].w, v[i+2].w, v[i+4].w, v[i+6].w);
          const uint32_t h0 = pack_bf16(c0, c1), h1 = pack_bf16(c2, c3), a = sb + SM_EXT + ps * 1024 + i * 512 + (lane >> 1) * 32 + (lane & 1) * 8;
          asm volatile("st.shared.v2.u32 [%0], {%1,%2};" :: "r"(a), "r"(h0), "r"(h1) : "memory");
          asm volatile("st.shared.v2.u32 [%0], {%1,%2};" :: "r"(a + 16), "r"(pack_bf16(c0 - bf_lo(h0), c1 - bf_hi(h0))), "r"(pack_bf16(c2 - bf_lo(h1), c3 - bf_hi(h1))) : "memory");
        }
        sts128(sb + SM_STAT + lane * 16, v[8].x & 0x7fffffffu, v[8].y & 0x7fffffffu, v[8].z & 0x7fffffffu, v[8].w & 0x7fffffffu);
        proxy_fence();
        __syncwarp();
        if (lane == 0) mbar_arrive(sb + B_EXT + ps * 8);
        TRACE1(2, 6 + ps);
        if (elect_one()) l2_prefetch(at<char>(ps ? P.v : P.k, ((hg * 4 + 1) * S_LEN + qt * (24 + 8 * KVPF)) * DH * 2), 6144 + 2048 * KVPF);
      }
    }
    if (warp == 1 || warp == 2) {
      int j = 0;
      const int r0 = qt * 128 + hg * 16 + (warp - 1) * 8 + (lane >> 4);
      uint32_t e = r0 * DM * 2 + (lane & 15) * 16;
      uint4 xn = ldg_nc(at<uint4>(P.x, e)), wn = ldg_nc(at<uint4>(P.wr, (lane & 15) * 16));
      #pragma unroll 1
      for (int it = 0; it < 4; it++) {
        const uint32_t st = __shfl_sync(0xffffffff, w0, (lane & 16) + it), m2 = __byte_perm(st, 0, 0x1010);
        const float rsd = rcp_fast(bf_hi(st));
        float a = 0.f;
        #pragma unroll 1
        for (int i = 0; i < 5; i++) {
          #pragma unroll 1
          do { mbar_pace(sb + B_KF + (j & 1) * 8, (j >> 1) & 1); j++; } while (j < 5 || (j >= 17 && j < 22));
          STALL(8);
          uint32_t z[4] = {xn.x, xn.y, xn.z, xn.w};
          const uint32_t ww[4] = {wn.x, wn.y, wn.z, wn.w}, en = e + (i < 4 ? 256 : (it < 3 ? 1536 : 0));
          xn = ldg_nc(at<uint4>(P.x, en)); wn = ldg_nc(at<uint4>(P.wr, (i < 4 ? i * 256 + 256 : 0) + (lane & 15) * 16));
          #pragma unroll
          for (int k = 0; k < 4; k++) {
            const uint32_t n = norm2(z[k], m2, rsd);
            const float lo = bf_lo(n), hi = bf_hi(n);
            a = fmaf(lo, bf_lo(ww[k]), fmaf(hi, bf_hi(ww[k]), a));
            z[k] = pack_bf16(lo * sigmoid_f(lo), hi * sigmoid_f(hi));
          }
          stg128(at<uint4>(g->gate, e), make_uint4(z[0], z[1], z[2], z[3]));
          e = en;
        }
        #pragma unroll
        for (int o = 8; o; o >>= 1) a += __shfl_xor_sync(0xffffffff, a, o);
        uint32_t u = pack_bf16(a, 0.f);
        if (u == 0x8000u) u = 0;
        u = (u & 0x8000u) ? (~u & 0xffffu) : (u | 0x8000u);
        if (!(lane & 15)) st_relaxed(at<uint32_t>(g->key, (r0 + it * 2) * 4), (u << 16) | (uint32_t)(0xffff - r0 - it * 2));
      }
      __syncwarp();
      if (lane == 0) flag_add_release(&g->cnt_gate.v);
      TRACE1(2, 9);
    }
    if (warp == 0) {
      const int row0 = hg * 4 * S_LEN;
      uint32_t s = 0, ph = 0;
      #pragma unroll 1
      for (int c = 3; c < 20; c++) {
        const int k = (c < 10 ? c : (c < 18 ? c - 8 : c - 18)) * 64, cb = hg * 8 + (c < 10 ? 0 : 4);
        const CUtensorMap* const tm = c < 10 ? &tmW4 : &tmW3;
        const uint32_t wb = c < 10 ? U : 12288;
        const bool wx = c < 10 || c == 15 || c == 16;
        const uint32_t bar = sb + B_WF + s * 8, dst = sb + SM_W + rank * 8192 + s * U;
        mbar_wait(bar + (B_WE - B_WF), ph);
        if (elect_one()) {
          mbar_expect_tx(bar, wx ? wb + U : wb);
          tma_load_3d_mc(dst, tm, bar, 0, k + rank * 16, cb);
          if (wx) tma_load_2d(sb + (c < 10 ? (c + 2) & 7 : c - 11) * U, &tmX, bar, c < 10 ? k : (c - 15) * 64, qt * 128);
        }
        mbar_wait(bar + (B_WE - B_WF) + 8, ph);
        if (elect_one()) {
          mbar_expect_tx(bar + 8, wb);
          tma_load_3d_mc(dst + U, tm, bar + 8, 0, k + 32 + rank * 16, cb);
        }
        s += 2;
        if (s == 6) { s = 0; ph ^= 1; }
      }
      auto kv = [&](int isv, int j) {
        const uint32_t bar = sb + B_KF + isv * 16 + (j & 1) * 8;
        mbar_expect_tx(bar, 2 * U);
        tma_load_2d_mc(sb + (isv ? SM_V + (j & 1) * 2 * U : (j & 1) * SM_K1) + rank * U, isv ? &tmV : &tmK, bar, rank * 64, row0 + kv_tile(j) * 128);
      };
      #pragma unroll 1
      for (int i = 0; i < 5; i++) {
        STALL(11);
        if (i) mbar_wait(sb + B_WE + ((0x63150 >> (4 * i)) & 7) * 8, i < 2);
        if (elect_one()) kv((i >> 1) & 1, i < 4 ? i & 1 : 2);
      }
      TRACEO(3);
      #pragma unroll 1
      for (int j = 2; j < 64; j++) {
        STALL(11);
        if (j < 63) {
          mbar_wait(sb + B_KE + (~j & 1) * 8, ((j - 1) >> 1) & 1);
          if (elect_one()) { kv(0, j + 1); if (j == 62) mbar_arrive(sb + B_ANN); }
        }
        mbar_wait(sb + B_KE + 16 + (j & 1) * 8, (~j >> 1) & 1);
        if (elect_one()) {
          kv(1, j);
          if (j + KVPF + 1 < 64) {
            const size_t o = (size_t)(row0 + kv_tile(j + KVPF + 1) * 128 + qt * 8) * DH;
            l2_prefetch(P.k + o, 2048); l2_prefetch(P.v + o, 2048);
          }
          if (j >= 40 && j < 60) l2_prefetch(j < 56 ? P.wo + (size_t)(hg * 512 + qt * 32 + (j - 40) * 2) * DM : ((j & 1) ? P.x : g->gate) + (size_t)(qt * 128 + hg * 16 + (j & 2) * 4) * DM, j < 56 ? 2 * DM * 2 : 8 * DM * 2);
        }
      }
      s = 0; ph = 1;
      #pragma unroll 1
      for (int n = 0; n < 40; n++) {
        const int st = n < 5 ? (n == 1) : n >> 2, h = n < 5 ? max(n - 1, 0) : n & 3;
        const int u = st < 2 ? 8 + st : ((hg + st - 1) & 7);
        STALL(12);
        mbar_wait(sb + (n < 6 ? B_KE + (n < 4 ? n >> 1 : 3) * 8 : B_CE + s * 8), ph);
        if (elect_one()) {
          mbar_expect_tx(sb + B_CF + s * 8, U);
          tma_load_2d_mc(sb + c_slot(s) * U + rank * 8192, &tmWO, sb + B_CF + s * 8, u * 64, hg * 512 + ((0x3120 >> (4 * h)) & 3) * 128 + rank * 64);
        }
        if (n == 3) TRACEO(4);
        if (++s == 6) { s = 0; ph ^= 1; }
      }
      mbar_wait(sb + B_GATE, 0);
      asm volatile("fence.proxy.async.global;" ::: "memory");
      #pragma unroll 1
      for (int n = 0; n < 2; n++) {
        mbar_wait(sb + B_CE + 32 + n * 8, 1);
        if (elect_one()) {
          mbar_expect_tx(sb + B_CF + 32 + n * 8, U);
          tma_load_2d(sb + (10 + n) * U, n ? &tmGate : &tmX, sb + B_CF + 32 + n * 8, hg * 64, qt * 128);
        }
      }
      {
        const uint4* const last = g->part + (size_t)((qt * 8 + hg) * 9 + 8) * 1024;
        mbar_wait(sb + B_CE + 16, 0);
        if (elect_one()) {
          mbar_expect_tx(sb + B_CF + 8, U);
          bulk_load(sb + U, last, U, sb + B_CF + 8);
        }
      }
    } else if (warp == 2) {
      #pragma unroll 1
      for (int h = 0; h < 4; h++) {
        mbar_wait(sb + B_OS + h * 8, 0);
        STALL(13);
        #pragma unroll 1
        for (int i = 0; i < (h < 3 ? 16 : 0); i++) {
          uint32_t z = 0;
          #pragma unroll
          for (int k = 0; k < 4; k++) { const uint4 v = lds128(sb + qo_slot(h) + i * 2048 + k * 512 + lane * 16); z = taint(taint(z, v.x, v.y), v.z, v.w); }
          flag_if(sb + SM_BAD + (i & 7) * 4 + h, tainted(z));
        }
        if (h == 2) {
          const uint32_t launch = lds32(sb + SM_EP);
          uint32_t* const mine = at<uint32_t>(g->near, (qt * 8 + hg) * 32 + (lane & 7) * 4);
          st_relaxed(mine, launch - 1);
          mbar_wait(sb + B_ANN, 0);
          mbar_wait(sb + B_KE, 1);
          st_relaxed(mine, launch);
          #pragma unroll 1
          for (int it = 0; __any_sync(0xffffffff, ldg32(at<uint32_t>(g->near, qp * 512 + lane * 16)) != launch) && it < MAXPOLL; it++) {}
        }
        __syncwarp();
        if (h >= 2) { proxy_fence(); if (elect_one()) mbar_arrive(sb + B_OF); }
        __syncwarp();
      }
    } else if (warp == 3 && elect_one()) {
      mbar_wait_idle(sb + B_OS + 8, 0);
      flag_wait(at<unsigned>(g->q3_done, (hg >> 1) * 128), lds32(sb + SM_EP) * 32 + qt * 2 - 30);
      asm volatile("fence.proxy.async.global;" ::: "memory");
      mbar_expect_tx(sb + B_Q3, U);
      bulk_load(sb + 5 * U, g->q3 + (qt * 8 + hg) * 1024, U, sb + B_Q3);
      mbar_wait_idle(sb + B_ANN, 0);
      flag_wait(&g->mod_done.v, lds32(sb + SM_EP) * 4);
      mbar_arrive(sb + B_GATE);
    }
    __syncwarp();
    if (warp == 1 || warp == 2) {
      #pragma unroll 1
      for (int i = 0; i < 4; i++) {
        const int r = warp * 8 - 8 + (i & 1) * 4 + (lane >> 3);
        const uint32_t e = ((qt * 128 + hg * 16 + r) * DM + (8 + (i >> 1)) * 64 + (lane & 7) * 8) * 2;
        if (!(i & 1)) bar_sync(8, 192);
        mbar_wait(sb + B_GATE, 0);
        STALL(10);
        const uint4 xr = ldg_nc(at<uint4>(P.x, e)), gr = ld_relaxed4(at<uint4>(g->gate, e)), sv = lds128(sb + SM_BAR + 1024 + r * 128 + (((lane ^ r) & 7) << 4));
        stg128(at<uint4>(P.out, e), gated(xr, sv, gr));
        if (i == 1) bar_arrive(9, 192);
      }
    }
    cluster_arrive();
    cluster_wait();
  } else {
    const int wg = wgi - 1, t = tid & 127, cw = warp - 4;
    asm volatile("setmaxnreg.inc.sync.aligned.u32 224;");
    uint32_t q[32], p[32];
    float s[64], o[64], l[2] = {0.f, 0.f};
    const uint32_t rb = __shfl_sync(0xffffffff, map_cta(sb, lane & 1), lane), wr = sb + cw * 2048, qa = __shfl_sync(0xffffffff, wr + lane * 16, lane);
    {
      uint32_t sl = 0, ph = 0, rprev = 0;
      float acc0[128], acc1[96];
      auto pair = [&](auto& acc, int pass, int i, auto mid) {
        const uint64_t a = desc(sb, ((i + 2 + 2 * pass) & 7) * 1024 + wg * 512 + doff(0, 16)), b = desc(sb, sl * 128 + doff(SM_W, 2048));
        STALL(4);
        mbar_wait(sb + B_WF + sl, ph);
        if (i == 0) TRACE(wg, 1 + pass);
        TRACEF(1, wg, 40 + pass * 20 + 2 * i);
        wg_fence();
        wgmma_ss_tb<0, 0>(acc, a, b, i > 0);
        wgmma_ss_tb<2, 512>(acc, a, b, 1);
        wg_commit();
        mbar_wait(sb + B_WF + 8 + sl, ph);
        wg_wait<1>();
        if (i > 0) release2(rprev, lane);
        TRACEF(1, wg, 41 + pass * 20 + 2 * i);
        wg_fence();
        wgmma_ss_tb<4, 1024>(acc, a, b, 1);
        wgmma_ss_tb<6, 1536>(acc, a, b, 1);
        wg_commit();
        mid();
        rprev = rb + B_WE + 8 + sl;
        sl += 16;
        if (sl == 48) { sl = 0; ph ^= 1; }
        wg_wait<1>();
        release2(rprev - 8, lane);
      };
      if (wg == 1) bar_arrive(1, 256);
      #pragma unroll 1
      for (int i = 0; i < 10; i++) {
        if (i == 9) bar_sync(1 + wg, 256);
        pair(acc0, 0, i, [] {});
      }
      mbar_wait(sb + B_EXT, 0);
      const uint32_t st0 = lds32(sb + SM_STAT + (cw * 16 + (lane >> 2)) * 4), st1 = lds32(sb + SM_STAT + (cw * 16 + 8 + (lane >> 2)) * 4);
      const uint32_t a0 = (lane & 3) ? 0u : (__byte_perm(st0, 0, 0x1010) ^ 0x80008000u), a1 = (lane & 3) ? 0u : (__byte_perm(st1, 0, 0x1010) ^ 0x80008000u);
      wg_fence();
      wgmma_rs_tb<0>(acc0, a0, a1, 0u, 0u, (uint64_t)desc_lo(sb + SM_EXT, 0) | ((uint64_t)2 << 32), 1);
      wg_commit();
      bar_arrive(1 + (wg ^ 1), 256);
      float rs[2] = {rcp_fast(bf_hi(st0)) * SCALE_LOG2E, rcp_fast(bf_hi(st1)) * SCALE_LOG2E};
      wg_wait<0>();
      fence_regs(acc0);
      release2(rprev, lane);
      #pragma unroll
      for (int i = 0; i < 32; i++) q[i] = pack_bf16(acc0[64+2*i] * rs[i & 1], acc0[64+2*i+1] * rs[i & 1]);
      fence_regs(q);
      pair(acc1, 1, 0, [&] {
        bar_sync(4 + wg, 128);
        const uint32_t one = lds32(sb + SM_ONE);
        rs[0] = __uint_as_float(__float_as_uint(rs[0]) * one); rs[1] = __uint_as_float(__float_as_uint(rs[1]) * one);
        #pragma unroll
        for (int i = 0; i < 32; i++) p[i] = pack_bf16(acc0[2*i] * rs[i & 1], acc0[2*i+1] * rs[i & 1]);
        fence_regs(p);
      });
      #pragma unroll 1
      for (int i = 1; i < 8; i++) pair(acc1, 1, i, [&] {
        #pragma unroll
        for (int e = 0; e < 8; e++) sts128_if(i == 4 + e / 2, qa + qo_slot(0) + (e >> 2) * U + (e & 3) * 512, p[4*e], p[4*e+1], p[4*e+2], p[4*e+3]);
      });
      mbar_wait(sb + B_WF, 0);
      mbar_wait(sb + B_WF + 8, 0);
      if (wg) { wg_wait<0>(); release2(rprev, lane); }
      bar_sync(1 + wg, 256);
      const uint64_t da = desc(sb, wg * 512 + 7), db = desc(sb, 7);
      static_for<0, 2>([&](auto ic) { constexpr int i = decltype(ic)::v;
        wg_fence();
        static_for<0, 4>([&](auto kc) { constexpr int k = decltype(kc)::v;
          wgmma_ss_tb<doff((4 + i) * U, 16) - 7 + k * 2, doff(SM_W + i * 2 * U, 2048) - 7 + k * 512>(acc1, da, db, 1); });
        if (i == 0) {
          wg_commit();
          mbar_wait(sb + B_WF + 16, 0);
          mbar_wait(sb + B_WF + 24, 0);
          mbar_wait(sb + B_EXT + 8, 0);
          wg_wait<1>();
          if (!wg) release2(rprev, lane);
        }
      });
      wgmma_rs_tb<0>(acc1, a0, a1, 0u, 0u, (uint64_t)desc_lo(sb + SM_EXT + 1024, 0) | ((uint64_t)2 << 32), 1);
      wg_commit();
      mbar_wait(sb + B_KF, 0);
      wg_wait<1>();
      release2(rb + B_WE + 8, lane);
      TRACE(wg, 3);
      mma_qk<0, 2>(s, q, desc(sb, 2));
      bar_arrive(1 + (wg ^ 1), 256);
      wg_wait<1>();
      fence_regs(acc1);
      release2(rb + B_WE + 24, lane);
      #pragma unroll
      for (int e = 0; e < 12; e++)
        sts128(qa + SM_QO + (e >> 2) * U + (e & 3) * 512, pack_bf16(acc1[8*e] * rs[0], acc1[8*e+1] * rs[0]), pack_bf16(acc1[8*e+2] * rs[1], acc1[8*e+3] * rs[1]),
               pack_bf16(acc1[8*e+4] * rs[0], acc1[8*e+5] * rs[0]), pack_bf16(acc1[8*e+6] * rs[1], acc1[8*e+7] * rs[1]));
      wg_wait<0>();
      fence_regs(s);
      release2(rb + B_KE, lane);
      exp_rows<0, 64>(s, l);
      #pragma unroll
      for (int i = 0; i < 32; i++) p[i] = pack_bf16(s[2*i], s[2*i+1]);
    }
    unsigned tz[3] = {0, 0, 0};
    #pragma unroll 1
    for (int j = 1; ; j += 2) {
      int ph = 0;
      #pragma unroll 1
      do {
        attn_step<1, false>(sb, rb, wr, qa, wg, lane, j, ph, s, o, p, q, l, g, tz);
        ph ^= 1; j += 2;
        if (wg < 2) attn_step<0, false>(sb, rb, wr, qa, wg, lane, j - 1, ph, s, o, p, q, l, g, tz);
      } while ((j & 15) != 15);
      if (j == 47) mbar_wait(sb + B_Q3, 0);
      attn_step<1, true>(sb, rb, wr, qa, wg, lane, j, 1, s, o, p, q, l, g, tz);
      if (j == 63) break;
      if (wg < 2) attn_step<0, true>(sb, rb, wr, qa, wg, lane, j + 1, 0, s, o, p, q, l, g, tz);
    }
    mbar_wait(sb + B_OF, 0);
    mbar_wait(sb + B_CF + wg * 8, 0);
    mbar_wait(sb + B_KF + 24, 1);
    bar_sync(1 + wg, 256);
    TRACE(wg, 4);
    mma_pv<SM_V + 2 * U, 2>(o, p, desc(sb, 2), true);
    mma_c<3>(s, sb, wg, 0, 0);
    bar_arrive(1 + (wg ^ 1), 256);
    mbar_wait(sb + B_KE + 16, 1);
    const uint32_t tag = lds32(sb + SM_EP) & 1;
    row_scale(l[0], l[1], lds32(sb + SM_ONE), sb + SM_BAD + cw * 4 + 3);
    __syncwarp();
    const uint32_t flags = lds32(sb + SM_BAD + (lane & 7) * 4);
    wg_wait<1>();
    fence_regs(o); fence_regs(p);
    release2(rb + B_KE + 24, lane);
    const uint32_t over = tainted(store_o<true>(o_addr(wr, lane) + SM_V, o, l[0], l[1]));
    if (__builtin_expect(bar_any(4 + wg, 128, __any_sync(0xffffffff, flags | over)), 0)) {
      const uint32_t bad = __shfl_sync(0xffffffff, flags, cw) | (__any_sync(0xffffffff, over) << 24);
      wg_wait<0>();
      fence_regs(s);
      redo_heads(P, sb, bad, qt * 128 + cw * 16, hg * 4);
      #pragma unroll
      for (int i = 0; i < 64; i++) s[i] = 0.f;
      __syncwarp();
      if (lane == 0) mbar_arrive(sb + B_OS + 24);
      mbar_wait(sb + B_OF, 1);
      mma_c<4>(s, sb, wg, 0, 0);
    } else if (lane == 0) mbar_arrive(sb + B_OS + 24);
    wg_wait<0>();
    release2(rb + B_CE + wg * 8, lane);
    {
      const uint4* in = at<uint4>(g->part, (((qt * 8 + hg) * 9 + wg) * 1024 + t) * 16);
      const uint32_t tm = 0u - tag;
      uint4 v[8];
      auto fetch = [&](auto half, const uint4* from) {
        #pragma unroll
        for (int i = decltype(half)::v * 4; i < decltype(half)::v * 4 + 4; i++) reload(v[i], from + i * 128);
      };
      auto verify = [&](auto half, const uint4* from) { verify4(v + decltype(half)::v * 4, from + decltype(half)::v * 512, tm); };
      int sp = 6, sl = 2 + 3 * wg, ph = 0;
      auto quarter = [&](auto site, int h, int arrive_bar) {
        STALL(2);
        mbar_wait(sb + B_CF + sl * 8, ph);
        if (h == 0) bar_sync(1 + wg, 256);
        mma_c<decltype(site)::v>(s, sb, sl, h, arrive_bar);
        if (h) { wg_wait<1>(); release2(rb + B_CE + sp * 8, lane); }
        sp = sl;
        if (++sl == 6) { sl = 0; ph ^= 1; }
      };
      auto send = [&](int st) {
        uint4* dst = at<uint4>(g->part, ((qt * 72 + st) * 1024 + (st < 2 ? hg * 128 : ((hg + st - 1) & 7) * 9216) + t) * 16);
        const uint32_t ds = st < 2 ? 9 * U : 2048;
        wg_wait<0>();
        fence_regs(s);
        TRACEF(4, wg, 106 + (st >> 1));
        release2(rb + B_CE + sp * 8, lane);
        STALL(3);
        #pragma unroll
        for (int i = 0; i < 8; i++, dst = at<uint4>(dst, ds))
          st_tagged(dst, (pack_bf16(s[8*i], s[8*i+1]) & ~1u) | tag, pack_bf16(s[8*i+2], s[8*i+3]), pack_bf16(s[8*i+4], s[8*i+5]), pack_bf16(s[8*i+6], s[8*i+7]));
        sl += st ? 4 : 3;
        if (sl >= 6) { sl -= 6; ph ^= 1; }
      };
      const uint32_t ta = ((lane >> 4) * 8 + (lane & 7)) * 128 + ((((cw & 3) * 2 + ((lane >> 3) & 1)) ^ (lane & 7)) << 4), ra = (t >> 3) * 128 + (((t & 7) ^ ((t >> 3) & 7)) << 4);
      float T[64];
      #pragma unroll
      for (int i = 0; i < 8; i++) asm volatile("mov.b64 {%0,%1}, 0;\nmov.b64 {%2,%3}, 0;" : "=r"(v[i].x), "=r"(v[i].y), "=r"(v[i].z), "=r"(v[i].w));
      TRACEF(4, wg, 112);
      bar_sync(1 + wg, 256);
      auto take = [&](auto half, int back, bool more) {
        verify(half, in - back * 1024);
        const uint4* const nx = in - (back - 1) * 1024;
        #pragma unroll
        for (int i = decltype(half)::v * 4; i < decltype(half)::v * 4 + 4; i++) { add8(T + 8 * i, v[i]); reload(v[i], nx + i * 128, more); }
      };
      #pragma unroll 1
      for (int st = wg; ; st += 2, in += 2048) {
        TRACEF(4, wg, 100 + (st >> 1));
        const bool odd5 = (st & 1) && st >= 5;
        quarter(IC<5>{}, 1, 0);
        if (odd5) take(IC<0>{}, 3, true);
        else if (st == 2) fetch(IC<0>{}, in - 2048);
        quarter(IC<6>{}, 2, 0);
        if (odd5) take(IC<1>{}, 3, true);
        else if (st == 2) fetch(IC<1>{}, in - 2048);
        if (st < 2) mbar_wait(sb + B_OF, 1);
        quarter(IC<7>{}, 3, st < 9 ? 2 - wg : 0);
        if (st < 9 && st != 4) send(st);
        if (odd5) {
          take(IC<0>{}, 2, st < 9);
          if (st == 9) bar_arrive(1, 256);
          take(IC<1>{}, 2, st < 9);
        }
        else if (st == 3) {
          fetch(IC<0>{}, in - 1024); fetch(IC<1>{}, in - 1024);
          #pragma unroll
          for (int i = 0; i < 64; i++) asm volatile("mov.b32 %0, 0;" : "+f"(T[i]));
        } else if (st == 2 || st == 4) {
          const uint4* const rows = at<uint4>(in - 3072, st == 2 ? U : 0);
          float a[8];
          #pragma unroll
          for (int i = 0; i < 8; i++) a[i] = 0.f;
          static_for<0, 2>([&](auto hf) {
            verify(hf, rows);
            #pragma unroll
            for (int i = decltype(hf)::v * 4; i < decltype(hf)::v * 4 + 4; i++) { add8(a, v[i]); reload(v[i], rows + 1024 + i * 128, st == 2); }
          });
          if (st == 4) bar_sync(9, 192);
          stsm4t(sb + SM_BAR + 1024 + ta, pack_bf16(a[0], a[1]), pack_bf16(a[2], a[3]), pack_bf16(a[4], a[5]), pack_bf16(a[6], a[7]));
          bar_arrive(8, 192);
          if (st == 4) send(4);
        }
        if (st >= 8) break;
        quarter(IC<8>{}, 0, 0);
      }
      cluster_arrive();
      TRACEF(4, wg, 113);
      wg_wait<0>();
      fence_regs(s);
      if (wg == 0) {
        mbar_wait(sb + B_CF + 32, 0);
        mbar_wait(sb + B_CF + 40, 0);
        uint4* const op = at<uint4>(P.out, ((qt * 128 + (t >> 3)) * DM + hg * 64 + (t & 7) * 8) * 2);
        bar_sync(1, 256);
        uint4 xv[8];
        #pragma unroll
        for (int i = 0; i < 8; i++) { xv[i] = lds128(sb + 10 * U + i * 2048 + ra); v[i] = lds128(sb + 11 * U + i * 2048 + ra); }
        #pragma unroll
        for (int i = 0; i < 8; i++) {
          if (!(i & 3)) bar_sync(12 + (i >> 2), 256);
          stg128(op + i * 2 * DM, gated(xv[i], lds128(sb + i * 2048 + ra), v[i]));
        }
      } else {
        TRACEF(4, wg, 110);
        mbar_wait(sb + B_CF + 8, 1);
        #pragma unroll
        for (int i = 0; i < 8; i++) v[i] = lds128(sb + U + i * 2048 + t * 16);
        #pragma unroll
        for (int i = 0; i < 64; i++) T[i] += s[i];
        fence_regs(T);
        static_for<0, 8>([&](auto ic) { constexpr int i = decltype(ic)::v;
          if (!(i & 3)) verify(IC<i / 4>{}, in - 1024);
          add8(T + 8 * i, v[i]);
          stsm4t(sb + i * 2048 + ta, pack_bf16(T[8*i], T[8*i+1]), pack_bf16(T[8*i+2], T[8*i+3]), pack_bf16(T[8*i+4], T[8*i+5]), pack_bf16(T[8*i+6], T[8*i+7]));
          if ((i & 3) == 3) bar_arrive(12 + (i >> 2), 256);
        });
      }
    }
    TRACE(wg, 6);
    cluster_wait();
  }
}

typedef CUresult (*EncodeFn)(CUtensorMap*, CUtensorMapDataType, cuuint32_t, void*, const cuuint64_t*, const cuuint64_t*, const cuuint32_t*, const cuuint32_t*,
                             CUtensorMapInterleave, CUtensorMapSwizzle, CUtensorMapL2promotion, CUtensorMapFloatOOBfill);
void make_map(EncodeFn enc, CUtensorMap* tm, const void* ptr, uint64_t inner, uint64_t outer, uint32_t box_outer, uint32_t blocks = 0) {
  cuuint64_t dims[3] = {blocks ? 64 : inner, outer, inner / 64}; cuuint64_t strides[2] = {inner * 2, 128};
  cuuint32_t box[3] = {64, box_outer, blocks}; cuuint32_t es[3] = {1, 1, 1};
  enc(tm, CU_TENSOR_MAP_DATA_TYPE_BFLOAT16, blocks ? 3 : 2, const_cast<void*>(ptr), dims, strides, box, es, CU_TENSOR_MAP_INTERLEAVE_NONE,
      CU_TENSOR_MAP_SWIZZLE_128B, CU_TENSOR_MAP_L2_PROMOTION_L2_128B, CU_TENSOR_MAP_FLOAT_OOB_FILL_NONE);
}

}

extern "C" void kernel_launch(void* const* d_in, const int* in_sizes, int n_in, void* d_out, int out_size) {
  (void)in_sizes; (void)n_in; (void)out_size;
  Params P;
  P.x = (const __nv_bfloat16*)d_in[0]; P.k = (const __nv_bfloat16*)d_in[1]; P.v = (const __nv_bfloat16*)d_in[2];
  P.wq = (const __nv_bfloat16*)d_in[3]; P.wo = (const __nv_bfloat16*)d_in[4]; P.wr = (const __nv_bfloat16*)d_in[6];
  P.out = (__nv_bfloat16*)d_out;
  cudaGetSymbolAddress((void**)&P.g, g_s);
  void* fn = nullptr; cudaDriverEntryPointQueryResult st;
  cudaGetDriverEntryPoint("cuTensorMapEncodeTiled", &fn, cudaEnableDefault, &st);
  EncodeFn enc = (EncodeFn)fn;
  CUtensorMap tmX, tmW4, tmW3, tmW1, tmK, tmV, tmWO, tmG, tmU, tmD, tmGate;
  make_map(enc, &tmGate, P.g->gate, DM, S_LEN, 128);
  make_map(enc, &tmX, P.x, DM, S_LEN, 128);
  make_map(enc, &tmW4, P.wq, NH * DH, DM, 16, 4);
  make_map(enc, &tmW3, P.wq, NH * DH, DM, 16, 3);
  make_map(enc, &tmW1, P.wq, NH * DH, DM, 128);
  make_map(enc, &tmK, P.k, DH, (uint64_t)NH * S_LEN, 128);
  make_map(enc, &tmV, P.v, DH, (uint64_t)NH * S_LEN, 128);
  make_map(enc, &tmWO, P.wo, DM, NH * DH, 64);
  make_map(enc, &tmG, d_in[7], FF, DM, 128);
  make_map(enc, &tmU, d_in[8], FF, DM, 128);
  make_map(enc, &tmD, d_in[9], DM, FF, 128);
  cudaFuncSetAttribute(fused_kernel, cudaFuncAttributeMaxDynamicSharedMemorySize, SMEM_BYTES);
  fused_kernel<<<132, 384, SMEM_BYTES, cudaStreamPerThread>>>(tmX, tmW4, tmW3, tmW1, tmK, tmV, tmWO, tmG, tmU, tmD, tmGate, P);
}
```

```cpp
#include <cuda_runtime.h>
#include <cuda_bf16.h>
#include <cuda.h>
#include <stdint.h>

#define MAXPOLL (1 << 22)
#define DPOS 44
#define DPOSF 36
#define KVPF 1
#define WAITMAX (1 << 19)
#define PH 1
#define QSP 6
namespace {

constexpr int S_LEN = 2048, DM = 640, NH = 32, DH = 128, FF = 1728, TOPC = 8;
constexpr float SCALE_LOG2E = 0.08838834764831845f * 1.4426950408889634f;

struct alignas(128) Cnt { unsigned v; unsigned pad[31]; };
struct Scratch {
  alignas(128) unsigned long long ticket;
  alignas(128)
  uint4 part[16 * 8 * 9 * 1024];
  __nv_bfloat16 gate[S_LEN * DM];
  uint32_t stat[S_LEN];
  uint4 cs[NH * DH];
  float ypart[4 * TOPC * DM];
  uint4 q3[16 * 8 * 1024];
  uint32_t key[S_LEN];
  Cnt cnt_gate, cnt_mod, mod_done, q3_done[4];
  uint32_t near[128 * 8];
};
__device__ Scratch g_s;

__device__ __forceinline__ uint32_t smem_u32(const void* p) { return (uint32_t)__cvta_generic_to_shared(p); }
template <class T> __device__ __forceinline__ T* at(const void* p, uint32_t off) { uint64_t r;
  asm("{\n.reg .u32 lo, hi;\nmov.b64 {lo, hi}, %1;\nadd.cc.u32 lo, lo, %2;\naddc.u32 hi, hi, 0;\nmov.b64 %0, {lo, hi};\n}\n" : "=l"(r) : "l"(p), "r"(off)); return (T*)r; }
__device__ __forceinline__ void mbar_init(uint32_t bar, uint32_t cnt) { asm volatile("mbarrier.init.shared::cta.b64 [%0], %1;" :: "r"(bar), "r"(cnt) : "memory"); }
__device__ __forceinline__ void mbar_expect_tx(uint32_t bar, uint32_t bytes) { asm volatile("mbarrier.arrive.expect_tx.shared::cta.b64 _, [%0], %1;" :: "r"(bar), "r"(bytes) : "memory"); }
__device__ __forceinline__ void mbar_arrive(uint32_t bar) { asm volatile("mbarrier.arrive.shared::cta.b64 _, [%0];" :: "r"(bar) : "memory"); }
__device__ __forceinline__ uint32_t map_cta(uint32_t a, uint32_t cta) { uint32_t r; asm volatile("mapa.shared::cluster.u32 %0, %1, %2;" : "=r"(r) : "r"(a), "r"(cta)); return r; }
__device__ __forceinline__ void mbar_arrive_cluster(uint32_t bar) { asm volatile("mbarrier.arrive.shared::cluster.b64 _, [%0];" :: "r"(bar) : "memory"); }
__device__ __forceinline__ void mbar_wait(uint32_t bar, uint32_t parity) {
  asm volatile("{\n.reg .pred p;\n.reg .u32 c;\nmov.u32 c, 0;\nLAB_WAIT:\nmbarrier.try_wait.parity.shared::cta.b64 p, [%0], %1;\n@p bra LAB_DONE;\n"
               "add.u32 c, c, 1;\nsetp.lt.u32 p, c, %2;\n@p bra LAB_WAIT;\ntrap;\nLAB_DONE:\n}\n" :: "r"(bar), "r"(parity), "n"(WAITMAX) : "memory"); }
__device__ __forceinline__ void mbar_wait_hot(uint32_t bar, uint32_t parity) {
  asm volatile("{\n.reg .pred p;\n.reg .u32 c;\nmbarrier.try_wait.parity.shared::cta.b64 p, [%0], %1;\n@p bra LAB_DONE;\nmov.u32 c, 0;\n"
               "LAB_WAIT:\nmbarrier.try_wait.parity.shared::cta.b64 p, [%0], %1;\n@p bra LAB_DONE;\n"
               "add.u32 c, c, 1;\nsetp.lt.u32 p, c, %2;\n@p bra LAB_WAIT;\ntrap;\nLAB_DONE:\n}\n" :: "r"(bar), "r"(parity), "n"(WAITMAX) : "memory"); }
__device__ __forceinline__ void mbar_wait_idle(uint32_t bar, uint32_t parity) {
  asm volatile("{\n.reg .pred p;\n.reg .u32 c;\nmov.u32 c, 0;\nLAB_WAIT:\nmbarrier.try_wait.parity.shared::cta.b64 p, [%0], %1;\n@p bra LAB_DONE;\n"
               "nanosleep.u32 1000;\nadd.u32 c, c, 1;\nsetp.lt.u32 p, c, %2;\n@p bra LAB_WAIT;\ntrap;\nLAB_DONE:\n}\n" :: "r"(bar), "r"(parity), "n"(WAITMAX) : "memory"); }
__device__ __forceinline__ void mbar_pace(uint32_t bar, uint32_t parity) {
  asm volatile("{\n.reg .pred p;\n.reg .u32 c;\nmov.u32 c, 0;\nLAB_WAIT:\nmbarrier.try_wait.parity.shared::cta.b64 p, [%0], %1;\n@p bra LAB_DONE;\n"
               "add.u32 c, c, 1;\nsetp.lt.u32 p, c, 256;\n@p bra LAB_WAIT;\nLAB_DONE:\n}\n" :: "r"(bar), "r"(parity) : "memory"); }
__device__ __forceinline__ void flag_wait(const unsigned* p, unsigned target, unsigned ns = 500) {
  asm volatile("{\n.reg .pred p;\n.reg .u32 c, v;\nmov.u32 c, 0;\nLAB_WAIT:\nld.relaxed.gpu.global.u32 v, [%0];\nsub.u32 v, v, %1;\nsetp.ge.s32 p, v, 0;\n@p bra LAB_DONE;\n"
               "nanosleep.u32 %2;\nadd.u32 c, c, 1;\nsetp.lt.u32 p, c, 8388608;\n@p bra LAB_WAIT;\ntrap;\nLAB_DONE:\nld.acquire.gpu.global.u32 v, [%0];\n}\n" :: "l"(p), "r"(target), "r"(ns) : "memory"); }
__device__ __forceinline__ void flag_add_release(unsigned* p) { asm volatile("fence.acq_rel.gpu;\nred.relaxed.gpu.global.add.u32 [%0], 1;" :: "l"(p) : "memory"); }
__device__ __forceinline__ void tma_load_2d(uint32_t dst, const CUtensorMap* tm, uint32_t bar, int c0, int c1) {
  asm volatile("cp.async.bulk.tensor.2d.shared::cluster.global.mbarrier::complete_tx::bytes [%0], [%1, {%3, %4}], [%2];"
    :: "r"(dst), "l"(tm), "r"(bar), "r"(c0), "r"(c1) : "memory"); }
__device__ __forceinline__ void tma_load_2d_mc(uint32_t dst, const CUtensorMap* tm, uint32_t bar, int c0, int c1) {
  asm volatile("cp.async.bulk.tensor.2d.shared::cluster.global.mbarrier::complete_tx::bytes.multicast::cluster [%0], [%1, {%3, %4}], [%2], %5;"
    :: "r"(dst), "l"(tm), "r"(bar), "r"(c0), "r"(c1), "h"((uint16_t)3) : "memory"); }
__device__ __forceinline__ void tma_load_3d(uint32_t dst, const CUtensorMap* tm, uint32_t bar, int c0, int c1, int c2) {
  asm volatile("cp.async.bulk.tensor.3d.shared::cluster.global.mbarrier::complete_tx::bytes [%0], [%1, {%3, %4, %5}], [%2];"
    :: "r"(dst), "l"(tm), "r"(bar), "r"(c0), "r"(c1), "r"(c2) : "memory"); }
__device__ __forceinline__ void tma_load_3d_mc(uint32_t dst, const CUtensorMap* tm, uint32_t bar, int c0, int c1, int c2) {
  asm volatile("cp.async.bulk.tensor.3d.shared::cluster.global.mbarrier::complete_tx::bytes.multicast::cluster [%0], [%1, {%3, %4, %5}], [%2], %6;"
    :: "r"(dst), "l"(tm), "r"(bar), "r"(c0), "r"(c1), "r"(c2), "h"((uint16_t)3) : "memory"); }
__device__ __forceinline__ void bulk_load(uint32_t dst, const void* src, uint32_t bytes, uint32_t bar) {
  asm volatile("cp.async.bulk.shared::cluster.global.mbarrier::complete_tx::bytes [%0], [%1], %2, [%3];" :: "r"(dst), "l"(src), "r"(bytes), "r"(bar) : "memory"); }
__device__ __forceinline__ void l2_prefetch(const void* p, uint32_t bytes) { asm volatile("cp.async.bulk.prefetch.L2.global [%0], %1;" :: "l"(p), "r"(bytes) : "memory"); }
__device__ __forceinline__ void wg_fence() { asm volatile("wgmma.fence.sync.aligned;" ::: "memory"); }
__device__ __forceinline__ void wg_commit() { asm volatile("wgmma.commit_group.sync.aligned;" ::: "memory"); }
template <int N> __device__ __forceinline__ void wg_wait() { asm volatile("wgmma.wait_group.sync.aligned %0;" :: "n"(N) : "memory"); }
__device__ __forceinline__ void bar_sync(int id, int n) { asm volatile("bar.sync %0, %1;" :: "r"(id), "r"(n) : "memory"); }
__device__ __forceinline__ void bar_arrive(int id, int n) { asm volatile("bar.arrive %0, %1;" :: "r"(id), "r"(n) : "memory"); }
__device__ __forceinline__ bool bar_any(int id, int n, uint32_t v) { uint32_t r;
  asm volatile("{\n.reg .pred p;\nsetp.ne.u32 p, %3, 0;\nbar.red.or.pred p, %1, %2, p;\nselp.u32 %0, 1, 0, p;\n}\n" : "=r"(r) : "r"(id), "r"(n), "r"(v) : "memory"); return r; }
__device__ __forceinline__ int sel_lt(int a, int b, int x, int y) { int r; asm("{\n.reg .pred p;\nsetp.lt.s32 p, %1, %2;\nselp.s32 %0, %3, %4, p;\n}\n" : "=r"(r) : "r"(a), "r"(b), "r"(x), "r"(y)); return r; }
__device__ __forceinline__ bool elect_one() { uint32_t r; asm volatile("{\n.reg .pred p;\nelect.sync _|p, 0xffffffff;\nselp.u32 %0, 1, 0, p;\n}\n" : "=r"(r)); return r; }
__device__ __forceinline__ void cluster_arrive() { asm volatile("barrier.cluster.arrive.relaxed.aligned;" ::: "memory"); }
__device__ __forceinline__ void cluster_wait() { asm volatile("barrier.cluster.wait.aligned;" ::: "memory"); }
__device__ __forceinline__ void proxy_fence() { asm volatile("fence.proxy.async.shared::cta;" ::: "memory"); }
__device__ __forceinline__ uint32_t pack_bf16(float lo, float hi) { uint32_t r; asm("cvt.rn.bf16x2.f32 %0, %1, %2;" : "=r"(r) : "f"(hi), "f"(lo)); return r; }
__device__ __forceinline__ float bf_lo(uint32_t v) { return __uint_as_float(v << 16); }
__device__ __forceinline__ float bf_hi(uint32_t v) { return __uint_as_float(v & 0xffff0000u); }
__device__ __forceinline__ void add8(float* a, const uint4& w) {
  a[0] += bf_lo(w.x); a[1] += bf_hi(w.x); a[2] += bf_lo(w.y); a[3] += bf_hi(w.y); a[4] += bf_lo(w.z); a[5] += bf_hi(w.z); a[6] += bf_lo(w.w); a[7] += bf_hi(w.w); }
__device__ __forceinline__ float rbf(float x) { return __bfloat162float(__float2bfloat16_rn(x)); }
__device__ __forceinline__ float ex2(float x) { float y; asm("ex2.approx.ftz.f32 %0, %1;" : "=f"(y) : "f"(x)); return y; }
__device__ __forceinline__ uint32_t lds32(uint32_t a) { uint32_t v; asm volatile("ld.shared.u32 %0, [%1];" : "=r"(v) : "r"(a) : "memory"); return v; }
__device__ __forceinline__ void sts32(uint32_t a, uint32_t v) { asm volatile("st.shared.u32 [%0], %1;" :: "r"(a), "r"(v) : "memory"); }
__device__ __forceinline__ uint4 lds128(uint32_t a) { uint4 v; asm volatile("ld.shared.v4.u32 {%0,%1,%2,%3}, [%4];" : "=r"(v.x), "=r"(v.y), "=r"(v.z), "=r"(v.w) : "r"(a) : "memory"); return v; }
__device__ __forceinline__ void sts128(uint32_t a, uint32_t x, uint32_t y, uint32_t z, uint32_t w) { asm volatile("st.shared.v4.u32 [%0], {%1,%2,%3,%4};" :: "r"(a), "r"(x), "r"(y), "r"(z), "r"(w) : "memory"); }
__device__ __forceinline__ void sts128_if(bool c, uint32_t a, uint32_t x, uint32_t y, uint32_t z, uint32_t w) {
  asm volatile("{\n.reg .pred p;\nsetp.ne.u32 p, %5, 0;\n@p st.shared.v4.u32 [%0], {%1,%2,%3,%4};\n}\n" :: "r"(a), "r"(x), "r"(y), "r"(z), "r"(w), "r"((uint32_t)c) : "memory"); }
__device__ __forceinline__ void st_tagged(uint4* p, uint32_t x, uint32_t y, uint32_t z, uint32_t w) {
  asm volatile("st.relaxed.gpu.global.v4.u32 [%0], {%1,%2,%3,%4};" :: "l"(p), "r"(x), "r"(y), "r"(z), "r"(w) : "memory"); }
__device__ __forceinline__ uint4 ld_relaxed4(const void* p) { uint4 v;
  asm volatile("ld.relaxed.gpu.global.v4.u32 {%0,%1,%2,%3}, [%4];" : "=r"(v.x), "=r"(v.y), "=r"(v.z), "=r"(v.w) : "l"(p) : "memory"); return v; }
__device__ __forceinline__ uint4 ld_tagged(const uint4* p) { uint4 v;
  asm volatile("{\n.reg .b128 v;\nld.relaxed.gpu.global.b128 v, [%4];\nmov.b128 {%0,%1,%2,%3}, v;\n}\n" : "=r"(v.x), "=r"(v.y), "=r"(v.z), "=r"(v.w) : "l"(p) : "memory"); return v; }
__device__ __forceinline__ void reload(uint4& v, const uint4* p, bool yes = true) {
  asm volatile("{\n.reg .pred p;\nsetp.ne.u32 p, %5, 0;\n@p ld.relaxed.gpu.global.v4.u32 {%0,%1,%2,%3}, [%4];\n}\n" : "+r"(v.x), "+r"(v.y), "+r"(v.z), "+r"(v.w) : "l"(p), "r"((uint32_t)yes) : "memory"); }
#define TAG_TEST "lop3.b32 a, %0, %4, %17, 0x7E;\nlop3.b32 b, %8, %12, %17, 0x7E;\nlop3.b32 a, a, b, 1, 0xA8;\nsetp.ne.u32 p, a, 0;\nvote.sync.any.pred p, p, 0xffffffff;\n"
__device__ __forceinline__ void verify4(uint4* v, const uint4* p, uint32_t tm) {
  asm volatile("{\n.reg .pred p;\n.reg .u32 a, b, c;\n" TAG_TEST "@!p bra.uni LAB_DONE;\nmov.u32 c, 0;\nLAB_AGAIN:\n"
    "ld.relaxed.gpu.global.v4.u32 {%0,%1,%2,%3}, [%16];\nld.relaxed.gpu.global.v4.u32 {%4,%5,%6,%7}, [%16+2048];\n"
    "ld.relaxed.gpu.global.v4.u32 {%8,%9,%10,%11}, [%16+4096];\nld.relaxed.gpu.global.v4.u32 {%12,%13,%14,%15}, [%16+6144];\n"
    TAG_TEST "add.u32 c, c, 1;\nsetp.lt.and.u32 p, c, %18, p;\n@p bra.uni LAB_AGAIN;\nLAB_DONE:\n}\n"
    : "+r"(v[0].x), "+r"(v[0].y), "+r"(v[0].z), "+r"(v[0].w), "+r"(v[1].x), "+r"(v[1].y), "+r"(v[1].z), "+r"(v[1].w),
      "+r"(v[2].x), "+r"(v[2].y), "+r"(v[2].z), "+r"(v[2].w), "+r"(v[3].x), "+r"(v[3].y), "+r"(v[3].z), "+r"(v[3].w) : "l"(p), "r"(tm), "n"(MAXPOLL) : "memory"); }
__device__ __forceinline__ uint4 ldg_nc(const void* p) { uint4 v;
  asm volatile("ld.global.nc.L1::no_allocate.v4.u32 {%0,%1,%2,%3}, [%4];" : "=r"(v.x), "=r"(v.y), "=r"(v.z), "=r"(v.w) : "l"(p) : "memory"); return v; }
__device__ __forceinline__ uint32_t ldg32(const void* p) { uint32_t v; asm volatile("ld.relaxed.gpu.global.u32 %0, [%1];" : "=r"(v) : "l"(p) : "memory"); return v; }
__device__ __forceinline__ void stg128(void* p, const uint4& v) { asm volatile("st.global.v4.u32 [%0], {%1,%2,%3,%4};" :: "l"(p), "r"(v.x), "r"(v.y), "r"(v.z), "r"(v.w) : "memory"); }
__device__ __forceinline__ void st_relaxed(uint32_t* p, uint32_t v) { asm volatile("st.relaxed.gpu.global.u32 [%0], %1;" :: "l"(p), "r"(v) : "memory"); }
__device__ __forceinline__ uint32_t mul_bf2(uint32_t a, uint32_t b) { uint32_t r; asm("mul.rn.bf16x2 %0, %1, %2;" : "=r"(r) : "r"(a), "r"(b)); return r; }
__device__ __forceinline__ uint32_t add_bf2(uint32_t a, uint32_t b) { uint32_t r; asm("add.rn.bf16x2 %0, %1, %2;" : "=r"(r) : "r"(a), "r"(b)); return r; }
__device__ __forceinline__ uint32_t sub_bf2(uint32_t a, uint32_t b) { uint32_t r; asm("sub.rn.bf16x2 %0, %1, %2;" : "=r"(r) : "r"(a), "r"(b)); return r; }
__device__ __forceinline__ void stsm4(uint32_t a, uint32_t r0, uint32_t r1, uint32_t r2, uint32_t r3) {
  asm volatile("stmatrix.sync.aligned.m8n8.x4.shared.b16 [%0], {%1,%2,%3,%4};" :: "r"(a), "r"(r0), "r"(r1), "r"(r2), "r"(r3) : "memory"); }
__device__ __forceinline__ void stsm4t(uint32_t a, uint32_t r0, uint32_t r1, uint32_t r2, uint32_t r3) {
  asm volatile("stmatrix.sync.aligned.m8n8.x4.trans.shared.b16 [%0], {%1,%2,%3,%4};" :: "r"(a), "r"(r0), "r"(r1), "r"(r2), "r"(r3) : "memory"); }
__device__ __forceinline__ uint4 gated(const uint4& x, const uint4& s, const uint4& g) {
  return make_uint4(add_bf2(x.x, mul_bf2(s.x, g.x)), add_bf2(x.y, mul_bf2(s.y, g.y)), add_bf2(x.z, mul_bf2(s.z, g.z)), add_bf2(x.w, mul_bf2(s.w, g.w))); }
__device__ __forceinline__ uint32_t tag_miss(uint32_t a, uint32_t b, uint32_t tm) { uint32_t d; asm("lop3.b32 %0, %1, %2, %3, 0x7E;" : "=r"(d) : "r"(a), "r"(b), "r"(tm)); return d; }
template <int R> __device__ __forceinline__ void fence_regs(float (&d)[R]) {
  #pragma unroll
  for (int i = 0; i < R; i++) asm volatile("" : "+f"(d[i]) :: "memory"); }
template <int R> __device__ __forceinline__ void fence_regs(uint32_t (&d)[R]) {
  #pragma unroll
  for (int i = 0; i < R; i++) asm volatile("" : "+r"(d[i]) :: "memory"); }
__device__ __forceinline__ uint32_t desc_lo(uint32_t addr, uint32_t lbo_bytes) { return ((addr & 0x3FFFF) >> 4) | ((lbo_bytes >> 4) << 16); }
__device__ __forceinline__ uint64_t desc(uint32_t sb, uint32_t var = 0) {
  uint64_t d; asm("mov.b64 %0, {%1, %2};" : "=l"(d) : "r"(desc_lo(sb, 0) + var), "r"(0x40000040u)); return d; }
__host__ __device__ constexpr int doff(uint32_t off, uint32_t lbo_bytes) { return (off >> 4) | ((lbo_bytes >> 4) << 16); }
__device__ __forceinline__ float rcp_approx(float x) { float y; asm("rcp.approx.f32 %0, %1;" : "=f"(y) : "f"(x)); return y; }
__device__ __forceinline__ float rcp_fast(float x) { float y; asm("rcp.approx.ftz.f32 %0, %1;" : "=f"(y) : "f"(x)); return y; }
__device__ __forceinline__ float sqrt_approx(float x) { float y; asm("sqrt.approx.f32 %0, %1;" : "=f"(y) : "f"(x)); return y; }
__device__ __forceinline__ float sigmoid_f(float z) { return rcp_fast(1.f + ex2(z * -1.4426950408889634f)); }
__device__ __forceinline__ uint32_t norm2(uint32_t x, uint32_t mean2, float rsd) { const uint32_t d = sub_bf2(x, mean2); return pack_bf16(bf_lo(d) * rsd, bf_hi(d) * rsd); }
#define STALL(site)
#define TRACE(w, i)
#define TRACE1(w, i)
#define TRACEF(m, w, i)
#define TRACEO(i)

template <int OA, int OB> __device__ __forceinline__ void wgmma_ss_tb(float (&d)[128], uint64_t da, uint64_t db, int sd) {
  asm volatile("{\n.reg .pred p;\n.reg .b64 a, b;\nadd.s64 a, %128, %131;\nadd.s64 b, %129, %132;\nsetp.ne.b32 p, %130, 0;\n"
    "wgmma.mma_async.sync.aligned.m64n256k16.f32.bf16.bf16 {%0, %1, %2, %3, %4, %5, %6, %7, %8, %9, %10, %11, %12, %13, %14, %15, %16, %17, %18, %19, %20, %21, %22, %23, %24, %25, %26, %27, %28, %29, %30, %31, %32, %33, %34, %35, %36, %37, %38, %39, %40, %41, %42, %43, %44, %45, %46, %47, %48, %49, %50, %51, %52, %53, %54, %55, %56, %57, %58, %59, %60, %61, %62, %63, %64, %65, %66, %67, %68, %69, %70, %71, %72, %73, %74, %75, %76, %77, %78, %79, %80, %81, %82, %83, %84, %85, %86, %87, %88, %89, %90, %91, %92, %93, %94, %95, %96, %97, %98, %99, %100, %101, %102, %103, %104, %105, %106, %107, %108, %109, %110, %111, %112, %113, %114, %115, %116, %117, %118, %119, %120, %121, %122, %123, %124, %125, %126, %127}, a, b, p, 1, 1, 0, 1;\n}\n"
    : "+f"(d[0]), "+f"(d[1]), "+f"(d[2]), "+f"(d[3]), "+f"(d[4]), "+f"(d[5]), "+f"(d[6]), "+f"(d[7]), "+f"(d[8]), "+f"(d[9]), "+f"(d[10]), "+f"(d[11]), "+f"(d[12]), "+f"(d[13]), "+f"(d[14]), "+f"(d[15]), "+f"(d[16]), "+f"(d[17]), "+f"(d[18]), "+f"(d[19]), "+f"(d[20]), "+f"(d[21]), "+f"(d[22]), "+f"(d[23]), "+f"(d[24]), "+f"(d[25]), "+f"(d[26]), "+f"(d[27]), "+f"(d[28]), "+f"(d[29]), "+f"(d[30]), "+f"(d[31]), "+f"(d[32]), "+f"(d[33]), "+f"(d[34]), "+f"(d[35]), "+f"(d[36]), "+f"(d[37]), "+f"(d[38]), "+f"(d[39]), "+f"(d[40]), "+f"(d[41]), "+f"(d[42]), "+f"(d[43]), "+f"(d[44]), "+f"(d[45]), "+f"(d[46]), "+f"(d[47]), "+f"(d[48]), "+f"(d[49]), "+f"(d[50]), "+f"(d[51]), "+f"(d[52]), "+f"(d[53]), "+f"(d[54]), "+f"(d[55]), "+f"(d[56]), "+f"(d[57]), "+f"(d[58]), "+f"(d[59]), "+f"(d[60]), "+f"(d[61]), "+f"(d[62]), "+f"(d[63]), "+f"(d[64]), "+f"(d[65]), "+f"(d[66]), "+f"(d[67]), "+f"(d[68]), "+f"(d[69]), "+f"(d[70]), "+f"(d[71]), "+f"(d[72]), "+f"(d[73]), "+f"(d[74]), "+f"(d[75]), "+f"(d[76]), "+f"(d[77]), "+f"(d[78]), "+f"(d[79]), "+f"(d[80]), "+f"(d[81]), "+f"(d[82]), "+f"(d[83]), "+f"(d[84]), "+f"(d[85]), "+f"(d[86]), "+f"(d[87]), "+f"(d[88]), "+f"(d[89]), "+f"(d[90]), "+f"(d[91]), "+f"(d[92]), "+f"(d[93]), "+f"(d[94]), "+f"(d[95]), "+f"(d[96]), "+f"(d[97]), "+f"(d[98]), "+f"(d[99]), "+f"(d[100]), "+f"(d[101]), "+f"(d[102]), "+f"(d[103]), "+f"(d[104]), "+f"(d[105]), "+f"(d[106]), "+f"(d[107]), "+f"(d[108]), "+f"(d[109]), "+f"(d[110]), "+f"(d[111]), "+f"(d[112]), "+f"(d[113]), "+f"(d[114]), "+f"(d[115]), "+f"(d[116]), "+f"(d[117]), "+f"(d[118]), "+f"(d[119]), "+f"(d[120]), "+f"(d[121]), "+f"(d[122]), "+f"(d[123]), "+f"(d[124]), "+f"(d[125]), "+f"(d[126]), "+f"(d[127])
    : "l"(da), "l"(db), "r"(sd), "n"(OA), "n"(OB));
}
template <int OB> __device__ __forceinline__ void wgmma_rs_tb(float (&d)[128], uint32_t a0, uint32_t a1, uint32_t a2, uint32_t a3, uint64_t db, int sd) {
  asm volatile("{\n.reg .pred p;\n.reg .b64 b;\nadd.s64 b, %132, %134;\nsetp.ne.b32 p, %133, 0;\n"
    "wgmma.mma_async.sync.aligned.m64n256k16.f32.bf16.bf16 {%0, %1, %2, %3, %4, %5, %6, %7, %8, %9, %10, %11, %12, %13, %14, %15, %16, %17, %18, %19, %20, %21, %22, %23, %24, %25, %26, %27, %28, %29, %30, %31, %32, %33, %34, %35, %36, %37, %38, %39, %40, %41, %42, %43, %44, %45, %46, %47, %48, %49, %50, %51, %52, %53, %54, %55, %56, %57, %58, %59, %60, %61, %62, %63, %64, %65, %66, %67, %68, %69, %70, %71, %72, %73, %74, %75, %76, %77, %78, %79, %80, %81, %82, %83, %84, %85, %86, %87, %88, %89, %90, %91, %92, %93, %94, %95, %96, %97, %98, %99, %100, %101, %102, %103, %104, %105, %106, %107, %108, %109, %110, %111, %112, %113, %114, %115, %116, %117, %118, %119, %120, %121, %122, %123, %124, %125, %126, %127}, {%128, %129, %130, %131}, b, p, 1, 1, 1;\n}\n"
    : "+f"(d[0]), "+f"(d[1]), "+f"(d[2]), "+f"(d[3]), "+f"(d[4]), "+f"(d[5]), "+f"(d[6]), "+f"(d[7]), "+f"(d[8]), "+f"(d[9]), "+f"(d[10]), "+f"(d[11]), "+f"(d[12]), "+f"(d[13]), "+f"(d[14]), "+f"(d[15]), "+f"(d[16]), "+f"(d[17]), "+f"(d[18]), "+f"(d[19]), "+f"(d[20]), "+f"(d[21]), "+f"(d[22]), "+f"(d[23]), "+f"(d[24]), "+f"(d[25]), "+f"(d[26]), "+f"(d[27]), "+f"(d[28]), "+f"(d[29]), "+f"(d[30]), "+f"(d[31]), "+f"(d[32]), "+f"(d[33]), "+f"(d[34]), "+f"(d[35]), "+f"(d[36]), "+f"(d[37]), "+f"(d[38]), "+f"(d[39]), "+f"(d[40]), "+f"(d[41]), "+f"(d[42]), "+f"(d[43]), "+f"(d[44]), "+f"(d[45]), "+f"(d[46]), "+f"(d[47]), "+f"(d[48]), "+f"(d[49]), "+f"(d[50]), "+f"(d[51]), "+f"(d[52]), "+f"(d[53]), "+f"(d[54]), "+f"(d[55]), "+f"(d[56]), "+f"(d[57]), "+f"(d[58]), "+f"(d[59]), "+f"(d[60]), "+f"(d[61]), "+f"(d[62]), "+f"(d[63]), "+f"(d[64]), "+f"(d[65]), "+f"(d[66]), "+f"(d[67]), "+f"(d[68]), "+f"(d[69]), "+f"(d[70]), "+f"(d[71]), "+f"(d[72]), "+f"(d[73]), "+f"(d[74]), "+f"(d[75]), "+f"(d[76]), "+f"(d[77]), "+f"(d[78]), "+f"(d[79]), "+f"(d[80]), "+f"(d[81]), "+f"(d[82]), "+f"(d[83]), "+f"(d[84]), "+f"(d[85]), "+f"(d[86]), "+f"(d[87]), "+f"(d[88]), "+f"(d[89]), "+f"(d[90]), "+f"(d[91]), "+f"(d[92]), "+f"(d[93]), "+f"(d[94]), "+f"(d[95]), "+f"(d[96]), "+f"(d[97]), "+f"(d[98]), "+f"(d[99]), "+f"(d[100]), "+f"(d[101]), "+f"(d[102]), "+f"(d[103]), "+f"(d[104]), "+f"(d[105]), "+f"(d[106]), "+f"(d[107]), "+f"(d[108]), "+f"(d[109]), "+f"(d[110]), "+f"(d[111]), "+f"(d[112]), "+f"(d[113]), "+f"(d[114]), "+f"(d[115]), "+f"(d[116]), "+f"(d[117]), "+f"(d[118]), "+f"(d[119]), "+f"(d[120]), "+f"(d[121]), "+f"(d[122]), "+f"(d[123]), "+f"(d[124]), "+f"(d[125]), "+f"(d[126]), "+f"(d[127])
    : "r"(a0), "r"(a1), "r"(a2), "r"(a3), "l"(db), "r"(sd), "n"(OB));
}
template <int OA, int OB> __device__ __forceinline__ void wgmma_ss_tb(float (&d)[96], uint64_t da, uint64_t db, int sd) {
  asm volatile("{\n.reg .pred p;\n.reg .b64 a, b;\nadd.s64 a, %96, %99;\nadd.s64 b, %97, %100;\nsetp.ne.b32 p, %98, 0;\n"
    "wgmma.mma_async.sync.aligned.m64n192k16.f32.bf16.bf16 {%0, %1, %2, %3, %4, %5, %6, %7, %8, %9, %10, %11, %12, %13, %14, %15, %16, %17, %18, %19, %20, %21, %22, %23, %24, %25, %26, %27, %28, %29, %30, %31, %32, %33, %34, %35, %36, %37, %38, %39, %40, %41, %42, %43, %44, %45, %46, %47, %48, %49, %50, %51, %52, %53, %54, %55, %56, %57, %58, %59, %60, %61, %62, %63, %64, %65, %66, %67, %68, %69, %70, %71, %72, %73, %74, %75, %76, %77, %78, %79, %80, %81, %82, %83, %84, %85, %86, %87, %88, %89, %90, %91, %92, %93, %94, %95}, a, b, p, 1, 1, 0, 1;\n}\n"
    : "+f"(d[0]), "+f"(d[1]), "+f"(d[2]), "+f"(d[3]), "+f"(d[4]), "+f"(d[5]), "+f"(d[6]), "+f"(d[7]), "+f"(d[8]), "+f"(d[9]), "+f"(d[10]), "+f"(d[11]), "+f"(d[12]), "+f"(d[13]), "+f"(d[14]), "+f"(d[15]), "+f"(d[16]), "+f"(d[17]), "+f"(d[18]), "+f"(d[19]), "+f"(d[20]), "+f"(d[21]), "+f"(d[22]), "+f"(d[23]), "+f"(d[24]), "+f"(d[25]), "+f"(d[26]), "+f"(d[27]), "+f"(d[28]), "+f"(d[29]), "+f"(d[30]), "+f"(d[31]), "+f"(d[32]), "+f"(d[33]), "+f"(d[34]), "+f"(d[35]), "+f"(d[36]), "+f"(d[37]), "+f"(d[38]), "+f"(d[39]), "+f"(d[40]), "+f"(d[41]), "+f"(d[42]), "+f"(d[43]), "+f"(d[44]), "+f"(d[45]), "+f"(d[46]), "+f"(d[47]), "+f"(d[48]), "+f"(d[49]), "+f"(d[50]), "+f"(d[51]), "+f"(d[52]), "+f"(d[53]), "+f"(d[54]), "+f"(d[55]), "+f"(d[56]), "+f"(d[57]), "+f"(d[58]), "+f"(d[59]), "+f"(d[60]), "+f"(d[61]), "+f"(d[62]), "+f"(d[63]), "+f"(d[64]), "+f"(d[65]), "+f"(d[66]), "+f"(d[67]), "+f"(d[68]), "+f"(d[69]), "+f"(d[70]), "+f"(d[71]), "+f"(d[72]), "+f"(d[73]), "+f"(d[74]), "+f"(d[75]), "+f"(d[76]), "+f"(d[77]), "+f"(d[78]), "+f"(d[79]), "+f"(d[80]), "+f"(d[81]), "+f"(d[82]), "+f"(d[83]), "+f"(d[84]), "+f"(d[85]), "+f"(d[86]), "+f"(d[87]), "+f"(d[88]), "+f"(d[89]), "+f"(d[90]), "+f"(d[91]), "+f"(d[92]), "+f"(d[93]), "+f"(d[94]), "+f"(d[95])
    : "l"(da), "l"(db), "r"(sd), "n"(OA), "n"(OB));
}
template <int OB> __device__ __forceinline__ void wgmma_rs_tb(float (&d)[96], uint32_t a0, uint32_t a1, uint32_t a2, uint32_t a3, uint64_t db, int sd) {
  asm volatile("{\n.reg .pred p;\n.reg .b64 b;\nadd.s64 b, %100, %102;\nsetp.ne.b32 p, %101, 0;\n"
    "wgmma.mma_async.sync.aligned.m64n192k16.f32.bf16.bf16 {%0, %1, %2, %3, %4, %5, %6, %7, %8, %9, %10, %11, %12, %13, %14, %15, %16, %17, %18, %19, %20, %21, %22, %23, %24, %25, %26, %27, %28, %29, %30, %31, %32, %33, %34, %35, %36, %37, %38, %39, %40, %41, %42, %43, %44, %45, %46, %47, %48, %49, %50, %51, %52, %53, %54, %55, %56, %57, %58, %59, %60, %61, %62, %63, %64, %65, %66, %67, %68, %69, %70, %71, %72, %73, %74, %75, %76, %77, %78, %79, %80, %81, %82, %83, %84, %85, %86, %87, %88, %89, %90, %91, %92, %93, %94, %95}, {%96, %97, %98, %99}, b, p, 1, 1, 1;\n}\n"
    : "+f"(d[0]), "+f"(d[1]), "+f"(d[2]), "+f"(d[3]), "+f"(d[4]), "+f"(d[5]), "+f"(d[6]), "+f"(d[7]), "+f"(d[8]), "+f"(d[9]), "+f"(d[10]), "+f"(d[11]), "+f"(d[12]), "+f"(d[13]), "+f"(d[14]), "+f"(d[15]), "+f"(d[16]), "+f"(d[17]), "+f"(d[18]), "+f"(d[19]), "+f"(d[20]), "+f"(d[21]), "+f"(d[22]), "+f"(d[23]), "+f"(d[24]), "+f"(d[25]), "+f"(d[26]), "+f"(d[27]), "+f"(d[28]), "+f"(d[29]), "+f"(d[30]), "+f"(d[31]), "+f"(d[32]), "+f"(d[33]), "+f"(d[34]), "+f"(d[35]), "+f"(d[36]), "+f"(d[37]), "+f"(d[38]), "+f"(d[39]), "+f"(d[40]), "+f"(d[41]), "+f"(d[42]), "+f"(d[43]), "+f"(d[44]), "+f"(d[45]), "+f"(d[46]), "+f"(d[47]), "+f"(d[48]), "+f"(d[49]), "+f"(d[50]), "+f"(d[51]), "+f"(d[52]), "+f"(d[53]), "+f"(d[54]), "+f"(d[55]), "+f"(d[56]), "+f"(d[57]), "+f"(d[58]), "+f"(d[59]), "+f"(d[60]), "+f"(d[61]), "+f"(d[62]), "+f"(d[63]), "+f"(d[64]), "+f"(d[65]), "+f"(d[66]), "+f"(d[67]), "+f"(d[68]), "+f"(d[69]), "+f"(d[70]), "+f"(d[71]), "+f"(d[72]), "+f"(d[73]), "+f"(d[74]), "+f"(d[75]), "+f"(d[76]), "+f"(d[77]), "+f"(d[78]), "+f"(d[79]), "+f"(d[80]), "+f"(d[81]), "+f"(d[82]), "+f"(d[83]), "+f"(d[84]), "+f"(d[85]), "+f"(d[86]), "+f"(d[87]), "+f"(d[88]), "+f"(d[89]), "+f"(d[90]), "+f"(d[91]), "+f"(d[92]), "+f"(d[93]), "+f"(d[94]), "+f"(d[95])
    : "r"(a0), "r"(a1), "r"(a2), "r"(a3), "l"(db), "r"(sd), "n"(OB));
}
template <int OA, int OB> __device__ __forceinline__ void wgmma_ss_tb(float (&d)[64], uint64_t da, uint64_t db, int sd) {
  asm volatile("{\n.reg .pred p;\n.reg .b64 a, b;\nadd.s64 a, %64, %67;\nadd.s64 b, %65, %68;\nsetp.ne.b32 p, %66, 0;\n"
    "wgmma.mma_async.sync.aligned.m64n128k16.f32.bf16.bf16 {%0, %1, %2, %3, %4, %5, %6, %7, %8, %9, %10, %11, %12, %13, %14, %15, %16, %17, %18, %19, %20, %21, %22, %23, %24, %25, %26, %27, %28, %29, %30, %31, %32, %33, %34, %35, %36, %37, %38, %39, %40, %41, %42, %43, %44, %45, %46, %47, %48, %49, %50, %51, %52, %53, %54, %55, %56, %57, %58, %59, %60, %61, %62, %63}, a, b, p, 1, 1, 0, 1;\n}\n"
    : "+f"(d[0]), "+f"(d[1]), "+f"(d[2]), "+f"(d[3]), "+f"(d[4]), "+f"(d[5]), "+f"(d[6]), "+f"(d[7]), "+f"(d[8]), "+f"(d[9]), "+f"(d[10]), "+f"(d[11]), "+f"(d[12]), "+f"(d[13]), "+f"(d[14]), "+f"(d[15]), "+f"(d[16]), "+f"(d[17]), "+f"(d[18]), "+f"(d[19]), "+f"(d[20]), "+f"(d[21]), "+f"(d[22]), "+f"(d[23]), "+f"(d[24]), "+f"(d[25]), "+f"(d[26]), "+f"(d[27]), "+f"(d[28]), "+f"(d[29]), "+f"(d[30]), "+f"(d[31]), "+f"(d[32]), "+f"(d[33]), "+f"(d[34]), "+f"(d[35]), "+f"(d[36]), "+f"(d[37]), "+f"(d[38]), "+f"(d[39]), "+f"(d[40]), "+f"(d[41]), "+f"(d[42]), "+f"(d[43]), "+f"(d[44]), "+f"(d[45]), "+f"(d[46]), "+f"(d[47]), "+f"(d[48]), "+f"(d[49]), "+f"(d[50]), "+f"(d[51]), "+f"(d[52]), "+f"(d[53]), "+f"(d[54]), "+f"(d[55]), "+f"(d[56]), "+f"(d[57]), "+f"(d[58]), "+f"(d[59]), "+f"(d[60]), "+f"(d[61]), "+f"(d[62]), "+f"(d[63])
    : "l"(da), "l"(db), "r"(sd), "n"(OA), "n"(OB));
}
template <int OB> __device__ __forceinline__ void wgmma_rs_tb(float (&d)[64], uint32_t a0, uint32_t a1, uint32_t a2, uint32_t a3, uint64_t db, int sd) {
  asm volatile("{\n.reg .pred p;\n.reg .b64 b;\nadd.s64 b, %68, %70;\nsetp.ne.b32 p, %69, 0;\n"
    "wgmma.mma_async.sync.aligned.m64n128k16.f32.bf16.bf16 {%0, %1, %2, %3, %4, %5, %6, %7, %8, %9, %10, %11, %12, %13, %14, %15, %16, %17, %18, %19, %20, %21, %22, %23, %24, %25, %26, %27, %28, %29, %30, %31, %32, %33, %34, %35, %36, %37, %38, %39, %40, %41, %42, %43, %44, %45, %46, %47, %48, %49, %50, %51, %52, %53, %54, %55, %56, %57, %58, %59, %60, %61, %62, %63}, {%64, %65, %66, %67}, b, p, 1, 1, 1;\n}\n"
    : "+f"(d[0]), "+f"(d[1]), "+f"(d[2]), "+f"(d[3]), "+f"(d[4]), "+f"(d[5]), "+f"(d[6]), "+f"(d[7]), "+f"(d[8]), "+f"(d[9]), "+f"(d[10]), "+f"(d[11]), "+f"(d[12]), "+f"(d[13]), "+f"(d[14]), "+f"(d[15]), "+f"(d[16]), "+f"(d[17]), "+f"(d[18]), "+f"(d[19]), "+f"(d[20]), "+f"(d[21]), "+f"(d[22]), "+f"(d[23]), "+f"(d[24]), "+f"(d[25]), "+f"(d[26]), "+f"(d[27]), "+f"(d[28]), "+f"(d[29]), "+f"(d[30]), "+f"(d[31]), "+f"(d[32]), "+f"(d[33]), "+f"(d[34]), "+f"(d[35]), "+f"(d[36]), "+f"(d[37]), "+f"(d[38]), "+f"(d[39]), "+f"(d[40]), "+f"(d[41]), "+f"(d[42]), "+f"(d[43]), "+f"(d[44]), "+f"(d[45]), "+f"(d[46]), "+f"(d[47]), "+f"(d[48]), "+f"(d[49]), "+f"(d[50]), "+f"(d[51]), "+f"(d[52]), "+f"(d[53]), "+f"(d[54]), "+f"(d[55]), "+f"(d[56]), "+f"(d[57]), "+f"(d[58]), "+f"(d[59]), "+f"(d[60]), "+f"(d[61]), "+f"(d[62]), "+f"(d[63])
    : "r"(a0), "r"(a1), "r"(a2), "r"(a3), "l"(db), "r"(sd), "n"(OB));
}
template <int OA, int OB> __device__ __forceinline__ void wgmma_ss_ta(float (&d)[64], uint64_t da, uint64_t db, int sd) {
  asm volatile("{\n.reg .pred p;\n.reg .b64 a, b;\nadd.s64 a, %64, %67;\nadd.s64 b, %65, %68;\nsetp.ne.b32 p, %66, 0;\n"
    "wgmma.mma_async.sync.aligned.m64n128k16.f32.bf16.bf16 {%0, %1, %2, %3, %4, %5, %6, %7, %8, %9, %10, %11, %12, %13, %14, %15, %16, %17, %18, %19, %20, %21, %22, %23, %24, %25, %26, %27, %28, %29, %30, %31, %32, %33, %34, %35, %36, %37, %38, %39, %40, %41, %42, %43, %44, %45, %46, %47, %48, %49, %50, %51, %52, %53, %54, %55, %56, %57, %58, %59, %60, %61, %62, %63}, a, b, p, 1, 1, 1, 0;\n}\n"
    : "+f"(d[0]), "+f"(d[1]), "+f"(d[2]), "+f"(d[3]), "+f"(d[4]), "+f"(d[5]), "+f"(d[6]), "+f"(d[7]), "+f"(d[8]), "+f"(d[9]), "+f"(d[10]), "+f"(d[11]), "+f"(d[12]), "+f"(d[13]), "+f"(d[14]), "+f"(d[15]), "+f"(d[16]), "+f"(d[17]), "+f"(d[18]), "+f"(d[19]), "+f"(d[20]), "+f"(d[21]), "+f"(d[22]), "+f"(d[23]), "+f"(d[24]), "+f"(d[25]), "+f"(d[26]), "+f"(d[27]), "+f"(d[28]), "+f"(d[29]), "+f"(d[30]), "+f"(d[31]), "+f"(d[32]), "+f"(d[33]), "+f"(d[34]), "+f"(d[35]), "+f"(d[36]), "+f"(d[37]), "+f"(d[38]), "+f"(d[39]), "+f"(d[40]), "+f"(d[41]), "+f"(d[42]), "+f"(d[43]), "+f"(d[44]), "+f"(d[45]), "+f"(d[46]), "+f"(d[47]), "+f"(d[48]), "+f"(d[49]), "+f"(d[50]), "+f"(d[51]), "+f"(d[52]), "+f"(d[53]), "+f"(d[54]), "+f"(d[55]), "+f"(d[56]), "+f"(d[57]), "+f"(d[58]), "+f"(d[59]), "+f"(d[60]), "+f"(d[61]), "+f"(d[62]), "+f"(d[63])
    : "l"(da), "l"(db), "r"(sd), "n"(OA), "n"(OB));
}
template <int OB> __device__ __forceinline__ void wgmma_rs(float (&d)[64], uint32_t a0, uint32_t a1, uint32_t a2, uint32_t a3, uint64_t db, int sd) {
  asm volatile("{\n.reg .pred p;\n.reg .b64 b;\nadd.s64 b, %68, %70;\nsetp.ne.b32 p, %69, 0;\n"
    "wgmma.mma_async.sync.aligned.m64n128k16.f32.bf16.bf16 {%0, %1, %2, %3, %4, %5, %6, %7, %8, %9, %10, %11, %12, %13, %14, %15, %16, %17, %18, %19, %20, %21, %22, %23, %24, %25, %26, %27, %28, %29, %30, %31, %32, %33, %34, %35, %36, %37, %38, %39, %40, %41, %42, %43, %44, %45, %46, %47, %48, %49, %50, %51, %52, %53, %54, %55, %56, %57, %58, %59, %60, %61, %62, %63}, {%64, %65, %66, %67}, b, p, 1, 1, 0;\n}\n"
    : "+f"(d[0]), "+f"(d[1]), "+f"(d[2]), "+f"(d[3]), "+f"(d[4]), "+f"(d[5]), "+f"(d[6]), "+f"(d[7]), "+f"(d[8]), "+f"(d[9]), "+f"(d[10]), "+f"(d[11]), "+f"(d[12]), "+f"(d[13]), "+f"(d[14]), "+f"(d[15]), "+f"(d[16]), "+f"(d[17]), "+f"(d[18]), "+f"(d[19]), "+f"(d[20]), "+f"(d[21]), "+f"(d[22]), "+f"(d[23]), "+f"(d[24]), "+f"(d[25]), "+f"(d[26]), "+f"(d[27]), "+f"(d[28]), "+f"(d[29]), "+f"(d[30]), "+f"(d[31]), "+f"(d[32]), "+f"(d[33]), "+f"(d[34]), "+f"(d[35]), "+f"(d[36]), "+f"(d[37]), "+f"(d[38]), "+f"(d[39]), "+f"(d[40]), "+f"(d[41]), "+f"(d[42]), "+f"(d[43]), "+f"(d[44]), "+f"(d[45]), "+f"(d[46]), "+f"(d[47]), "+f"(d[48]), "+f"(d[49]), "+f"(d[50]), "+f"(d[51]), "+f"(d[52]), "+f"(d[53]), "+f"(d[54]), "+f"(d[55]), "+f"(d[56]), "+f"(d[57]), "+f"(d[58]), "+f"(d[59]), "+f"(d[60]), "+f"(d[61]), "+f"(d[62]), "+f"(d[63])
    : "r"(a0), "r"(a1), "r"(a2), "r"(a3), "l"(db), "r"(sd), "n"(OB));
}
template <int OA, int OB> __device__ __forceinline__ void wgmma_ss_ta(float (&d)[4], uint64_t da, uint64_t db, int sd) {
  asm volatile("{\n.reg .pred p;\n.reg .b64 a, b;\nadd.s64 a, %4, %7;\nadd.s64 b, %5, %8;\nsetp.ne.b32 p, %6, 0;\n"
    "wgmma.mma_async.sync.aligned.m64n8k16.f32.bf16.bf16 {%0, %1, %2, %3}, a, b, p, 1, 1, 1, 0;\n}\n"
    : "+f"(d[0]), "+f"(d[1]), "+f"(d[2]), "+f"(d[3])
    : "l"(da), "l"(db), "r"(sd), "n"(OA), "n"(OB));
}

constexpr uint32_t U = 16384;
constexpr uint32_t SM_QO = 2 * U, SM_W = 8 * U, SM_V = 8 * U, SM_K1 = 12 * U, SM_BAR = 14 * U;
constexpr uint32_t B_WF = SM_BAR, B_KF = SM_BAR + 48, B_CF = SM_BAR + 80, B_GATE = SM_BAR + 128, B_OF = SM_BAR + 136, B_EP = SM_BAR + 144, B_EXT = SM_BAR + 152, B_Q3 = SM_BAR + 168, B_ANN = SM_BAR + 176,
                   B_WE = SM_BAR + 192, B_KE = SM_BAR + 240, B_CE = SM_BAR + 288, B_OS = SM_BAR + 344;
constexpr uint32_t SM_EP = SM_BAR + 384;
constexpr uint32_t SM_ONE = SM_BAR + 388;
constexpr uint32_t SM_STAT = SM_BAR + 400, SM_EXT = SM_STAT + 512;
constexpr uint32_t SM_BAD = SM_EXT + 2048;
constexpr int SMEM_BYTES = SM_BAR + 3072;
__device__ __forceinline__ uint32_t c_slot(int s) { return (0xBADC10u >> (4 * s)) & 15; }

struct Params {
  const __nv_bfloat16 *x, *k, *v, *wq, *wo, *wr;
  __nv_bfloat16* out;
  Scratch* g;
};

__device__ __forceinline__ void release2(uint32_t rbar, int lane) { if (lane < 2) mbar_arrive_cluster(rbar); }
__device__ __forceinline__ void pin_after(uint32_t a, float e0, float e1) {
  asm volatile("{\n.reg .pred p;\nsetp.lt.f32 p, %1, %2;\n@p st.shared.u32 [%0], 0;\n}\n" :: "r"(a), "f"(e0), "f"(-e1) : "memory"); }
__device__ __forceinline__ void lds128_after(uint32_t& x, uint32_t& y, uint32_t& z, uint32_t& w, uint32_t a, float e0, float e1) {
  asm volatile("{\n.reg .pred p;\nsetp.geu.f32 p, %5, %6;\n@p ld.shared.v4.u32 {%0,%1,%2,%3}, [%4];\n}\n" : "+r"(x), "+r"(y), "+r"(z), "+r"(w) : "r"(a), "f"(e0), "f"(-e1) : "memory"); }
__device__ __forceinline__ uint32_t launch_of(unsigned long long ticket) { return (uint32_t)(ticket / 132) + 1; }

__device__ __forceinline__ void attn_slow(float (&o)[64], float& i0, float& i1, const __nv_bfloat16* __restrict__ X, const __nv_bfloat16* __restrict__ WQ, uint32_t st0, uint32_t st1,
                                          const __nv_bfloat16* __restrict__ K, const __nv_bfloat16* __restrict__ V, int lane) {
  uint32_t q[32];
  #pragma unroll
  for (int i = 0; i < 64; i++) o[i] = 0.f;
  const int g = lane >> 2, qd = lane & 3;
  #pragma unroll 1
  for (int k0 = 0; k0 < DM; k0 += 16) {
    uint32_t a[4];
    #pragma unroll
    for (int e = 0; e < 4; e++) {
      const uint32_t xv = *(const uint32_t*)(X + (size_t)(g + (e & 1) * 8) * DM + k0 + (e >> 1) * 8 + 2 * qd);
      const float mb = bf_lo((e & 1) ? st1 : st0);
      a[e] = pack_bf16(bf_lo(xv) - mb, bf_hi(xv) - mb);
    }
    const unsigned short* wr = (const unsigned short*)(WQ + (size_t)(k0 + 2 * qd) * (NH * DH) + g);
    #pragma unroll
    for (int nb = 0; nb < 16; nb++) {
      uint32_t b0 = (uint32_t)wr[nb * 8] | ((uint32_t)wr[nb * 8 + NH * DH] << 16);
      uint32_t b1 = (uint32_t)wr[nb * 8 + 8 * NH * DH] | ((uint32_t)wr[nb * 8 + 9 * NH * DH] << 16);
      asm volatile("mma.sync.aligned.m16n8k16.row.col.f32.bf16.bf16.f32 {%0,%1,%2,%3}, {%4,%5,%6,%7}, {%8,%9}, {%0,%1,%2,%3};"
        : "+f"(o[nb*4]), "+f"(o[nb*4+1]), "+f"(o[nb*4+2]), "+f"(o[nb*4+3]) : "r"(a[0]), "r"(a[1]), "r"(a[2]), "r"(a[3]), "r"(b0), "r"(b1));
    }
  }
  {
    const float r0 = rcp_approx(bf_hi(st0)) * SCALE_LOG2E, r1 = rcp_approx(bf_hi(st1)) * SCALE_LOG2E;
    #pragma unroll
    for (int i = 0; i < 16; i++) { q[2*i] = pack_bf16(o[4*i] * r0, o[4*i+1] * r0); q[2*i+1] = pack_bf16(o[4*i+2] * r1, o[4*i+3] * r1); }
    #pragma unroll
    for (int i = 0; i < 64; i++) o[i] = 0.f;
  }
  float m0 = -INFINITY, m1 = -INFINITY, l0 = 0.f, l1 = 0.f;
  #pragma unroll 1
  for (int n0 = 0; n0 < S_LEN; n0 += 16) {
    float s[8];
    #pragma unroll
    for (int i = 0; i < 8; i++) s[i] = 0.f;
    #pragma unroll
    for (int nb = 0; nb < 2; nb++) {
      const uint32_t* kr = (const uint32_t*)(K + (size_t)(n0 + nb * 8 + g) * DH) + qd;
      #pragma unroll
      for (int kk = 0; kk < 8; kk++) {
        uint32_t b0 = kr[kk * 8], b1 = kr[kk * 8 + 4];
        asm volatile("mma.sync.aligned.m16n8k16.row.col.f32.bf16.bf16.f32 {%0,%1,%2,%3}, {%4,%5,%6,%7}, {%8,%9}, {%0,%1,%2,%3};"
          : "+f"(s[nb*4]), "+f"(s[nb*4+1]), "+f"(s[nb*4+2]), "+f"(s[nb*4+3]) : "r"(q[kk*4]), "r"(q[kk*4+1]), "r"(q[kk*4+2]), "r"(q[kk*4+3]), "r"(b0), "r"(b1));
      }
    }
    float x0 = fmaxf(fmaxf(s[0], s[1]), fmaxf(s[4], s[5])), x1 = fmaxf(fmaxf(s[2], s[3]), fmaxf(s[6], s[7]));
    x0 = fmaxf(x0, __shfl_xor_sync(0xffffffff, x0, 1)); x1 = fmaxf(x1, __shfl_xor_sync(0xffffffff, x1, 1));
    x0 = fmaxf(x0, __shfl_xor_sync(0xffffffff, x0, 2)); x1 = fmaxf(x1, __shfl_xor_sync(0xffffffff, x1, 2));
    const float n0m = fmaxf(m0, x0), n1m = fmaxf(m1, x1);
    const float sh0 = (n0m == -INFINITY) ? 0.f : n0m, sh1 = (n1m == -INFINITY) ? 0.f : n1m;
    const float c0 = ex2(m0 - sh0), c1 = ex2(m1 - sh1);
    m0 = n0m; m1 = n1m;
    s[0] = ex2(s[0] - sh0); s[1] = ex2(s[1] - sh0); s[4] = ex2(s[4] - sh0); s[5] = ex2(s[5] - sh0);
    s[2] = ex2(s[2] - sh1); s[3] = ex2(s[3] - sh1); s[6] = ex2(s[6] - sh1); s[7] = ex2(s[7] - sh1);
    l0 = l0 * c0 + (s[0] + s[1]) + (s[4] + s[5]); l1 = l1 * c1 + (s[2] + s[3]) + (s[6] + s[7]);
    const uint32_t a0 = pack_bf16(s[0], s[1]), a1 = pack_bf16(s[2], s[3]), a2 = pack_bf16(s[4], s[5]), a3 = pack_bf16(s[6], s[7]);
    const unsigned short* vr = (const unsigned short*)(V + (size_t)(n0 + 2 * qd) * DH + g);
    #pragma unroll
    for (int nb = 0; nb < 16; nb++) {
      uint32_t b0 = (uint32_t)vr[nb * 8] | ((uint32_t)vr[nb * 8 + DH] << 16);
      uint32_t b1 = (uint32_t)vr[nb * 8 + 8 * DH] | ((uint32_t)vr[nb * 8 + 9 * DH] << 16);
      o[nb*4] *= c0; o[nb*4+1] *= c0; o[nb*4+2] *= c1; o[nb*4+3] *= c1;
      asm volatile("mma.sync.aligned.m16n8k16.row.col.f32.bf16.bf16.f32 {%0,%1,%2,%3}, {%4,%5,%6,%7}, {%8,%9}, {%0,%1,%2,%3};"
        : "+f"(o[nb*4]), "+f"(o[nb*4+1]), "+f"(o[nb*4+2]), "+f"(o[nb*4+3]) : "r"(a0), "r"(a1), "r"(a2), "r"(a3), "r"(b0), "r"(b1));
    }
  }
  l0 += __shfl_xor_sync(0xffffffff, l0, 1); l1 += __shfl_xor_sync(0xffffffff, l1, 1);
  l0 += __shfl_xor_sync(0xffffffff, l0, 2); l1 += __shfl_xor_sync(0xffffffff, l1, 2);
  i0 = rcp_approx(l0); i1 = rcp_approx(l1);
}

__device__ __forceinline__ void flag_if(uint32_t a, bool c) { asm volatile("{\n.reg .pred p;\nsetp.ne.u32 p, %1, 0;\n@p st.shared.u8 [%0], 1;\n}\n" :: "r"(a), "r"((uint32_t)c) : "memory"); }
__device__ __forceinline__ void row_scale(float& l0, float& l1, int one, uint32_t flag) {
  l0 += __shfl_xor_sync(0xffffffff, l0, one); l1 += __shfl_xor_sync(0xffffffff, l1, one);
  l0 += __shfl_xor_sync(0xffffffff, l0, 2); l1 += __shfl_xor_sync(0xffffffff, l1, 2);
  flag_if(flag, !((l0 >= 0.00390625f) && (l0 <= 1.8446744e19f) && (l1 >= 0.00390625f) && (l1 <= 1.8446744e19f)));
  l0 = rcp_fast(l0); l1 = rcp_fast(l1);
}
__device__ __forceinline__ uint32_t taint(uint32_t z, uint32_t a, uint32_t b) { asm("fma.rn.bf16x2 %0, %1, %2, %0;" : "+r"(z) : "r"(a), "r"(b)); return z; }
__device__ __forceinline__ bool tainted(uint32_t z) { return (taint(0u, z, 0u) & 0x7fff7fffu) != 0; }

__device__ __forceinline__ int kv_tile(int j) { return j < 32 ? j ^ 16 : j; }
__device__ __forceinline__ uint32_t qo_slot(int h) { return SM_QO + ((0x3102 >> (4 * h)) & 3) * 2 * U; }
__device__ __forceinline__ uint32_t o_addr(uint32_t wr, int lane) { return wr + (lane & 15) * 128 + (((lane >> 4) ^ (lane & 7)) << 4); }
template <bool CHECK> __device__ __forceinline__ uint32_t store_o(uint32_t a, const float (&o)[64], float i0, float i1) {
  uint32_t z = 0;
  #pragma unroll
  for (int i = 0; i < 8; i++) {
    const uint32_t w0 = pack_bf16(o[8*i] * i0, o[8*i+1] * i0), w1 = pack_bf16(o[8*i+2] * i1, o[8*i+3] * i1), w2 = pack_bf16(o[8*i+4] * i0, o[8*i+5] * i0), w3 = pack_bf16(o[8*i+6] * i1, o[8*i+7] * i1);
    stsm4((a ^ ((i & 3) << 5)) + (i >> 2) * U, w0, w1, w2, w3);
    if (CHECK) z = taint(taint(z, w0, w1), w2, w3);
  }
  return z;
}

__device__ __noinline__ void redo_heads(const Params& P, uint32_t sb, uint32_t bad, int row0, int head0) {
  const int lane = threadIdx.x & 31;
  const uint32_t st0 = lds32(sb + SM_STAT + ((row0 & 127) + (lane >> 2)) * 4), st1 = lds32(sb + SM_STAT + ((row0 & 127) + 8 + (lane >> 2)) * 4);
  #pragma unroll 1
  for (int h = 0; h < 4; h++) {
    if (!((bad >> (8 * h)) & 1)) continue;
    float o[64], i0, i1;
    const int head = head0 + (kv_tile(h * 16) >> 4);
    attn_slow(o, i0, i1, P.x + (size_t)row0 * DM, P.wq + head * DH, st0, st1, P.k + (size_t)head * S_LEN * DH, P.v + (size_t)head * S_LEN * DH, lane);
    store_o<false>(o_addr(sb + (row0 & 127) * 128, lane) + qo_slot(h), o, i0, i1);
  }
}

template <int K> struct IC { static constexpr int v = K; };
template <int K, int N, class F> __device__ __forceinline__ void static_for(F&& f) { if constexpr (K < N) { f(IC<K>{}); static_for<K + 1, N>(f); } }
template <uint32_t OFF, int SITE> __device__ __forceinline__ void mma_qk(float (&s)[64], const uint32_t (&q)[32], uint64_t d0) {
  wg_fence();
  static_for<0, 8>([&](auto kc) { constexpr int k = decltype(kc)::v; wgmma_rs<doff(OFF, 16) - SITE + (k / 4) * 1024 + (k % 4) * 2>(s, q[k*4], q[k*4+1], q[k*4+2], q[k*4+3], d0, k > 0); });
  wg_commit();
}
template <uint32_t OFF, int SITE> __device__ __forceinline__ void mma_pv(float (&o)[64], const uint32_t (&p)[32], uint64_t d0, bool keep) {
  wg_fence();
  static_for<0, 8>([&](auto kc) { constexpr int k = decltype(kc)::v; wgmma_rs_tb<doff(OFF, U) - SITE + k * 128>(o, p[k*4], p[k*4+1], p[k*4+2], p[k*4+3], d0, (k > 0) || keep); });
  wg_commit();
}
template <int I0, int I1>
__device__ __forceinline__ void exp_rows(float (&s)[64], float (&l)[2]) {
  #pragma unroll
  for (int i = I0; i < I1; i += 2) {
    s[i] = ex2(s[i]); s[i+1] = ex2(s[i+1]);
    l[(i >> 1) & 1] += s[i] + s[i+1];
  }
}

template <int KS, bool EDGE>
__device__ __forceinline__ void attn_step(uint32_t sb, uint32_t rb, uint32_t wr, uint32_t qa, int wg, int lane, int j, int ph, float (&s)[64], float (&o)[64], uint32_t (&p)[32], uint32_t (&q)[32],
                                          float (&l)[2], Scratch* g, unsigned (&tz)[3]) {
  constexpr bool FIRST = EDGE && !KS, LAST = EDGE && KS;
  TRACEF(2, wg, 32 + j);
  STALL(1);
  mbar_wait_hot(sb + B_KF + KS * 8, ph);
  bar_sync(1 + wg, 256);
  mma_qk<KS * SM_K1, EDGE>(s, q, desc(sb, EDGE));
  mbar_wait_hot(sb + B_KF + 24 - KS * 8, KS ? ph : ph ^ 1);
  mma_pv<SM_V + (1 - KS) * 2 * U, EDGE>(o, p, desc(sb, EDGE), !KS || LAST || ((j & 15) != 1));
  bar_arrive(1 + (wg ^ 1), 256);
  const int one = FIRST ? lds32(sb + SM_ONE) : 1;
  wg_wait<1>();
  fence_regs(s);
  release2(rb + B_KE + KS * 8, lane);
  float i0 = l[0], i1 = l[1];
  if (FIRST) { row_scale(i0, i1, one, sb + SM_BAD - 1 + ((wr - sb) >> 9) + (j >> 4)); l[0] = fminf(i0, 0.f); l[1] = fminf(i1, 0.f); }
  constexpr int DP = FIRST ? DPOSF : (LAST && DPOS < 7 * QSP ? 7 * QSP : DPOS);
  if (LAST) {
    fence_regs(q);
    const uint32_t a = qa + qo_slot(j >> 4);
    static_for<0, 8>([&](auto ic) { constexpr int i = decltype(ic)::v;
      lds128_after(q[4*i], q[4*i+1], q[4*i+2], q[4*i+3], a + (i >> 2) * U + (i & 3) * 512, l[0], l[1]);
      exp_rows<i * QSP, i < 7 ? (i + 1) * QSP : DP>(s, l);
    });
  } else exp_rows<0, DP>(s, l);
  pin_after(sb + SM_BAD, l[0], l[1]);
  exp_rows<DP, 64>(s, l);
  wg_wait<0>();
  fence_regs(o); fence_regs(p);
  release2(rb + B_KE + 24 - KS * 8, lane);
  if (FIRST) {
    const int h = (j >> 4) - 1;
    store_o<false>(o_addr(wr, lane) + qo_slot(h), o, i0, i1);
    if (lane == 0) mbar_arrive(sb + B_OS + h * 8);
  }
  #pragma unroll
  for (int i = 0; i < 32; i++) p[i] = pack_bf16(s[2*i], s[2*i+1]);
}

template <int SITE> __device__ __forceinline__ void mma_c(float (&acc)[64], uint32_t sb, int slot, int h, int arrive_bar) {
  const uint64_t a = desc(sb, c_slot(slot) * 1024 + SITE), b = desc(sb, h * 2048 + SITE);
  wg_fence();
  static_for<0, 8>([&](auto kc) { constexpr int k = decltype(kc)::v;
    wgmma_ss_ta<doff(0, 16) - SITE + k * 128, doff(SM_QO, 16) - SITE + (k >> 2) * 1024 + (k & 3) * 2>(acc, a, b, k > 0 || h > 0);
  });
  wg_commit();
  if (arrive_bar) bar_arrive(arrive_bar, 256);
}

__device__ __forceinline__ void side_cta(const Params& P, const CUtensorMap* tmX, const CUtensorMap* tmW, const CUtensorMap* tmG, const CUtensorMap* tmU,
                                         const CUtensorMap* tmD, uint32_t sb, int m) {
  const int tid = threadIdx.x, warp = __shfl_sync(0xffffffff, tid >> 5, 0), lane = tid & 31;
  const uint32_t XS = sb + 12 * U, HS = XS + 10240, BF = sb + SM_BAR, BE = BF + 96, XF = BE + 96, XE = XF + 32, BW = XE + 32, SEL = BW + 16, KEY = SEL + 64;
  Scratch* const g = P.g;
  const int nj = m < 3 ? 14 : 12, nd = m < 3 ? 4 : 3, f0 = m * 448;
  if (elect_one()) { mbar_init(BF + warp * 8, 1); mbar_init(BE + warp * 8, 4); if (warp < 9) mbar_init(XF + warp * 8, (warp & 4) ? 8 : 1); }
  if (tid == 32) sts32(SEL + 32, launch_of(atomicAdd(&g->ticket, 1ull)));
  __syncthreads();
  const uint32_t launch = lds32(SEL + 32);
  if (warp == 0) {
    if (elect_one()) {
      mbar_expect_tx(BW, 10 * U);
      #pragma unroll 1
      for (int i = 0; i < 10; i++) tma_load_2d(sb + i * U, tmW, BW, m * 1024 + (i < 5 ? 448 : 960), (i < 5 ? i : i - 5) * 128);
    }
    #pragma unroll 1
    for (int n = 0, qt = 0, c = 0; n < 160; n++) {
      const uint32_t bar = XF + (n & 3) * 8;
      mbar_wait(bar + 32, ((n >> 2) & 1) ^ 1);
      if (elect_one()) {
        mbar_expect_tx(bar, U);
        tma_load_2d(sb + (10 + (n & 3)) * U, tmX, bar, c * 64, qt * 128);
        if (c == 0 && qt < 15) l2_prefetch(P.x + (size_t)(qt * 128 + 128 + m * 32) * DM, 32 * DM * 2);
      }
      if (++c == 10) { c = 0; qt++; }
    }
  } else if (warp < 3) {
    #pragma unroll 1
    for (int qt = 0; qt < 16; qt++) {
      bar_sync(1 + warp, 160);
      if (lane == 0) flag_add_release(&g->q3_done[m].v);
      __syncwarp();
    }
  } else if (warp >= 4) {
    float acc[64], cs[32];
    mbar_wait(BW, 0);
    #pragma unroll 1
    for (int c = 0; c < 10; c++) {
      wg_fence();
      static_for<0, 4>([&](auto kc) { constexpr int k = decltype(kc)::v;
        wgmma_rs_tb<doff(0, 5 * U) + k * 128>(acc, 0x3f803f80u, 0x3f803f80u, 0x3f803f80u, 0x3f803f80u, desc(sb, c * 512), k || c); });
      wg_commit();
      wg_wait<0>();
    }
    fence_regs(acc);
    #pragma unroll
    for (int i = 0; i < 32; i++) cs[i] = -acc[(i >> 1) * 4 + (i & 1)];
    fence_regs(cs);
    #pragma unroll 1
    for (int qt = 0, n = 0; qt < 16; qt++) {
      const uint32_t* const sp = g->stat + qt * 128 + (warp - 4) * 16 + (lane >> 2);
      uint32_t st0, st1;
      #pragma unroll 1
      for (int c = 0; c < 10; c++, n++) {
        const uint64_t a = desc(sb, (n & 3) * 1024 + (warp >> 3) * 512), b = desc(sb, c * 512);
        mbar_wait(XF + (n & 3) * 8, (n >> 2) & 1);
        wg_fence();
        static_for<0, 4>([&](auto kc) { constexpr int k = decltype(kc)::v; wgmma_ss_tb<doff(10 * U, 16) + k * 2, doff(0, 5 * U) + k * 128>(acc, a, b, k || c); });
        wg_commit();
        if (c == 9) { st0 = ldg32(sp); st1 = ldg32(sp + 8); }
        wg_wait<1>();
        if (c && lane == 0) mbar_arrive(XE + ((n - 1) & 3) * 8);
      }
      #pragma unroll 1
      for (int it = 0; __any_sync(0xffffffff, tag_miss(st0, st1, launch << 31) >> 31) && it < MAXPOLL; it++) { st0 = ldg32(sp); st1 = ldg32(sp + 8); }
      st0 &= 0x7fffffffu; st1 &= 0x7fffffffu;
      const float rs[2] = {rcp_fast(bf_hi(st0)) * SCALE_LOG2E, rcp_fast(bf_hi(st1)) * SCALE_LOG2E}, nm[2] = {bf_lo(st0), bf_lo(st1)};
      wg_wait<0>();
      fence_regs(acc);
      if (lane == 0) mbar_arrive(XE + ((n - 1) & 3) * 8);
      STALL(7);
      uint4* const dst = g->q3 + (qt * 8 + m * 2) * 1024 + (warp - 4) * 128 + lane;
      #pragma unroll
      for (int e = 0; e < 8; e++) {
        uint32_t w[4];
        #pragma unroll
        for (int i = 0; i < 4; i++)
          w[i] = pack_bf16(fmaf(nm[i & 1], cs[4*e + (i & 2)], acc[8*e + 2*i]) * rs[i & 1], fmaf(nm[i & 1], cs[4*e + (i & 2) + 1], acc[8*e + 2*i + 1]) * rs[i & 1]);
        dst[(e >> 2) * 1024 + (e & 3) * 32] = make_uint4(w[0], w[1], w[2], w[3]);
      }
      bar_sync(1 + (warp >> 2), 160);
    }
  }
  if (tid == 96) flag_wait(&g->cnt_gate.v, launch * 256);
  __syncthreads();
  TRACE(0, 1);
  if (tid >= 256 && tid < 320) sts128(HS + 3072 + tid * 16, 0, 0, 0, 0);
  if (warp < 4) {
    uint4 k4[4];
    #pragma unroll
    for (int i = 0; i < 4; i++) k4[i] = ld_relaxed4(g->key + warp * 512 + i * 128 + lane * 4);
    uint32_t bound = 0;
    #pragma unroll 1
    for (int c = 0; c < TOPC; c++) {
      uint32_t b = 0;
      #pragma unroll
      for (int i = 0; i < 4; i++) b = max(max(max(b, k4[i].x - bound), k4[i].y - bound), max(k4[i].z - bound, k4[i].w - bound));
      bound += __reduce_max_sync(0xffffffff, b);
      if (lane == 0) sts32(KEY + (warp * TOPC + c) * 4, bound);
    }
    bar_sync(1, 128);
    const uint32_t v = lds32(KEY + lane * 4);
    int n = 0;
    #pragma unroll 1
    for (int j = 0; j < 32; j++) n += __shfl_sync(0xffffffff, v, j) > v;
    if (n < TOPC) sts32(SEL + n * 4, v);
  }
  __syncthreads();
  #pragma unroll 1
  for (int i = tid; i < TOPC * 80; i += 384) {
    const int row = 0xffff - (lds32(SEL + (i & 7) * 4) & 0xffff);
    const uint32_t st = ldg32(g->stat + row), m2 = __byte_perm(st, 0, 0x1010);
    const float rsd = rcp_fast(bf_hi(st & 0x7fffffffu));
    const uint4 v = ldg_nc((const uint4*)(P.x + (size_t)row * DM) + (i >> 3));
    sts128(XS + i * 16, norm2(v.x, m2, rsd), norm2(v.y, m2, rsd), norm2(v.z, m2, rsd), norm2(v.w, m2, rsd));
  }
  proxy_fence();
  __syncthreads();
  TRACE(0, 2);
  uint32_t sl = 0, ph = 0;
  if (warp == 0) {
    #pragma unroll 1
    for (int job = 0; job < nj + 10; job++) {
      const bool up = job < nj;
      #pragma unroll 1
      for (int i = 0; i < (up ? 5 : nd); i++) {
        mbar_wait(BE + sl * 8, ph ^ 1);
        if (elect_one()) {
          mbar_expect_tx(BF + sl * 8, U);
          tma_load_2d(sb + sl * U, up ? ((job & 1) ? tmU : tmG) : tmD, BF + sl * 8, up ? f0 + (job >> 1) * 64 : (job - nj) * 64, (up ? 0 : f0) + i * 128);
        }
        if (++sl == 12) { sl = 0; ph ^= 1; }
      }
    }
  } else if ((warp >> 2) == 1) {
    float gs[4];
    #pragma unroll 1
    for (int job = 0; job < nj + 10; job++) {
      const bool up = job < nj;
      if (job == nj) { proxy_fence(); bar_sync(1, 128); }
      float ac[4][4], acc[4];
      uint32_t prev = 0;
      #pragma unroll 1
      for (int i = 0; i < (up ? 5 : nd); i++) {
        const uint64_t a = desc(sb, sl * 1024 + 0x10000), b = (uint64_t)(desc_lo(up ? XS : HS, 128) + i * 128) | (8ull << 32);
        mbar_wait(BF + sl * 8, ph);
        wg_fence();
        static_for<0, 8>([&](auto kc) { constexpr int k = decltype(kc)::v; wgmma_ss_ta<k * 128, k * 16>(ac[k & 3], a, b, k > 3 || i > 0); });
        wg_commit();
        wg_wait<1>();
        if (i && lane == 0) mbar_arrive(prev);
        prev = BE + sl * 8;
        if (++sl == 12) { sl = 0; ph ^= 1; }
      }
      wg_wait<0>();
      if (lane == 0) mbar_arrive(prev);
      #pragma unroll
      for (int e = 0; e < 4; e++) fence_regs(ac[e]);
      #pragma unroll
      for (int e = 0; e < 4; e++) acc[e] = (ac[0][e] + ac[1][e]) + (ac[2][e] + ac[3][e]);
      STALL(9);
      const int f = (warp & 3) * 16 + (lane >> 2), tk = (lane & 3) * 2;
      if (!up) {
        float* y = g->ypart + (m * DM + (job - nj) * 64 + f) * TOPC + tk;
        *(float2*)y = make_float2(acc[0], acc[1]); *(float2*)(y + 8 * TOPC) = make_float2(acc[2], acc[3]);
      } else {
        #pragma unroll
        for (int e = 0; e < 4; e++) {
          const float z = rbf(acc[e]);
          if (job & 1) asm volatile("st.shared.u16 [%0], %1;" :: "r"(HS + (job >> 1) * 1024 + ((f >> 3) + (e >> 1)) * 128 + (tk + (e & 1)) * 16 + (f & 7) * 2), "h"((uint16_t)pack_bf16(gs[e] * z, 0.f)) : "memory");
          gs[e] = rbf(z * sigmoid_f(z));
        }
      }
    }
  }
  __syncthreads();
  TRACE(0, 3);
  if (tid == 0) { flag_add_release(&g->cnt_mod.v); flag_wait(&g->cnt_mod.v, launch * 4, 50); }
  __syncthreads();
  #pragma unroll 1
  for (int i = tid; i < 2 * DM; i += 384) {
    const int t = 2 * m + (i & 1), col = i >> 1;
    const uint32_t key = lds32(SEL + t * 4);
    const float* yp = g->ypart + col * TOPC + t;
    const float y = rbf((__ldcg(yp) + __ldcg(yp + TOPC * DM)) + (__ldcg(yp + 2 * TOPC * DM) + __ldcg(yp + 3 * TOPC * DM)));
    const float rs = rbf(sigmoid_f(bf_hi((key >> 31) ? key & 0x7fffffffu : ~key)));
    const uint32_t xn = lds32(XS + (col >> 3) * 128 + t * 16 + (col & 6) * 2);
    const float z = rbf(((col & 1) ? bf_hi(xn) : bf_lo(xn)) + rbf(y * rs));
    g->gate[(size_t)(0xffff - (key & 0xffff)) * DM + col] = __float2bfloat16_rn(z * sigmoid_f(z));
  }
  __syncthreads();
  if (tid == 0) flag_add_release(&g->mod_done.v);
  TRACE(0, 4);
}

__global__ void __cluster_dims__(2, 1, 1) __launch_bounds__(384, 1) fused_kernel(const __grid_constant__ CUtensorMap tmX, const __grid_constant__ CUtensorMap tmW4,
    const __grid_constant__ CUtensorMap tmW3, const __grid_constant__ CUtensorMap tmW1,
    const __grid_constant__ CUtensorMap tmK, const __grid_constant__ CUtensorMap tmV, const __grid_constant__ CUtensorMap tmWO,
    const __grid_constant__ CUtensorMap tmG, const __grid_constant__ CUtensorMap tmU, const __grid_constant__ CUtensorMap tmD,
    const __grid_constant__ CUtensorMap tmGate, const __grid_constant__ Params P) {
  extern __shared__ __align__(1024) uint8_t smem_raw[];
  const uint32_t sb = smem_u32(smem_raw);
  const int tid = threadIdx.x, lane = tid & 31;
  const int rank = blockIdx.x & 1, cl = blockIdx.x >> 1;
  if (cl >= 64) {
    side_cta(P, &tmX, &tmW1, &tmG, &tmU, &tmD, sb, blockIdx.x & 3);
    return;
  }
  const int rr = ((cl - 36) * 37) >> 8, kk = cl - 36 - rr * 7, qp = sel_lt(cl, 4, PH, sel_lt(cl, 36, (cl - 4) & 7, kk + sel_lt(kk, PH, 0, 1)));
  const int hg = sel_lt(cl, 4, cl + 4, sel_lt(cl, 36, (cl - 4) >> 3, 4 + rr)), qt = qp * 2 + rank;
  const int warp = __shfl_sync(0xffffffff, tid >> 5, 0), wgi = warp >> 2;
  Scratch* const g = P.g;
  if (elect_one()) {
    #pragma unroll
    for (int i = 0; i < 4; i++) mbar_init(sb + SM_BAR + warp * 32 + i * 8, 1 << ((0x333444000000ull >> (4 * warp)) & 7));
    if (warp == 0) {
      mbar_expect_tx(sb + B_WF, 2 * U);
      tma_load_2d(sb + 2 * U, &tmX, sb + B_WF, 0, qt * 128);
      tma_load_3d(sb + SM_W, &tmW4, sb + B_WF, 0, 0, hg * 8);
      tma_load_3d(sb + SM_W + 8192, &tmW4, sb + B_WF, 0, 16, hg * 8);
    }
    asm volatile("fence.mbarrier_init.release.cluster;" ::: "memory");
  }
  __syncwarp();
  cluster_arrive();
  unsigned long long ticket = 0;
  if (tid == 64) asm volatile("atom.relaxed.gpu.global.add.u64 %0, [%1], 1;" : "=l"(ticket) : "l"(&g->ticket) : "memory");
  cluster_wait();
  if (warp == 0 && elect_one()) {
    #pragma unroll
    for (int i = 1; i < 6; i++) {
      mbar_expect_tx(sb + B_WF + i * 8, (i & 1) ? U : 2 * U);
      tma_load_3d_mc(sb + SM_W + i * U + rank * 8192, &tmW4, sb + B_WF + i * 8, 0, i * 32 + rank * 16, hg * 8);
      if (!(i & 1)) tma_load_2d(sb + (2 + i / 2) * U, &tmX, sb + B_WF + i * 8, i * 32, qt * 128);
    }
  }
  STALL(14);
  if (wgi == 0) {
    asm volatile("setmaxnreg.dec.sync.aligned.u32 56;");
    uint32_t w0 = 0;
    if (warp == 1 || warp == 2) {
      if (warp == 2 && lane < 12) sts128(sb + SM_EXT + 1024 + (lane >= 6 ? 1024 - 96 : 0) + lane * 16, 0, 0, 0, 0);
      __syncwarp();
      if (tid == 64) { sts32(sb + SM_ONE, 1); sts32(sb + SM_EP, launch_of(ticket)); mbar_arrive(sb + B_EP); }
      __syncwarp();
      mbar_pace(sb + B_WF, 0);
      TRACEO(1);
      auto warm = [&](int ps, int i0, int i1) {
        const uint32_t o = (((qt >> 2) * 4 + (lane & 3) + (lane >> 2) * 16) * (NH * DH) + hg * 512 + ps * 256 + (qt & 3) * 64) * 2;
        #pragma unroll 1
        for (int i = i0; i < i1; i++) {
          asm volatile("prefetch.global.L2 [%0];" :: "l"(at<char>(P.wq, o + i * 256 * (NH * DH))) : "memory");
          if (ps) __nanosleep(300);
        }
      };
      if (elect_one()) l2_prefetch(P.x + (size_t)(qt * 128 + hg * 16 + warp * 8 - 6) * DM, 6 * DM * 2);
      if (warp == 1) warm(0, 1, 5);
      auto publish = [&](uint32_t w) { if (!(lane & 12)) st_relaxed(at<uint32_t>(g->stat, (qt * 128 + hg * 16 + (warp - 1) * 8 + (lane & 3) * 2 + (lane >> 4)) * 4), w ^ (lds32(sb + SM_EP) << 31)); };
      mbar_wait(sb + B_EP, 0);
      publish(0x80000000u);
      const int r0 = qt * 128 + hg * 16 + (warp - 1) * 8 + (lane >> 4);
      const uint32_t e = r0 * DM * 2 + (lane & 15) * 16;
      uint4 vn[5];
      #pragma unroll
      for (int i = 0; i < 5; i++) vn[i] = ldg_nc(at<uint4>(P.x, e) + i * 16);
      #pragma unroll 1
      for (int it = 0; it < 4; it++) {
        uint4 v[5];
        #pragma unroll
        for (int i = 0; i < 5; i++) { v[i] = vn[i]; if (it < 3) vn[i] = ldg_nc(at<uint4>(P.x, e + (it + 1) * 2560) + i * 16); }
        const float x0 = bf_lo(__shfl_sync(0xffffffff, v[0].x, lane & 16));
        float m1 = 0.f, s1 = 0.f;
        #pragma unroll
        for (int i = 0; i < 5; i++) {
          const uint32_t vw[4] = {v[i].x, v[i].y, v[i].z, v[i].w};
          #pragma unroll
          for (int k = 0; k < 4; k++) { const float d0 = bf_lo(vw[k]) - x0, d1 = bf_hi(vw[k]) - x0; m1 += d0 + d1; s1 = fmaf(d0, d0, fmaf(d1, d1, s1)); }
        }
        #pragma unroll
        for (int o = 8; o; o >>= 1) { m1 += __shfl_xor_sync(0xffffffff, m1, o); s1 += __shfl_xor_sync(0xffffffff, s1, o); }
        const float md = m1 * (1.f / DM), var = fmaxf(fmaf(-md, md, s1 * (1.f / DM)), 0.f);
        if ((lane & 15) == it) w0 = pack_bf16(x0 + md, sqrt_approx(rbf(rbf(var) + 1e-5f)));
      }
      STALL(5);
      publish(w0 & 0x7fffffffu);
      TRACE1(2, 8);
      if (warp == 1) warm(1, 0, 5);
    }
        if (warp >= 2) {
      const int ps = 3 - warp;
      {
        const uint4* src = at<uint4>(P.wq, (((qt >> 2) * 4 + (lane >> 3)) * (NH * DH) + hg * 512 + ps * 256 + (qt & 3) * 64 + (lane & 7) * 8) * 2);
        const uint32_t mine = ((hg * 2 + ps) * 256 + qt * 16 + (lane & 7) * 2 + (lane >> 4)) * 16;
        float cs[8];
        #pragma unroll
        for (int e = 0; e < 8; e++) cs[e] = 0.f;
        #pragma unroll 1
        for (int b = 0; b < 5; b++, src += 8 * 16 * 512) {
          uint4 w[8];
          #pragma unroll
          for (int i = 0; i < 8; i++) w[i] = ldg_nc(src + i * 16 * 512);
          #pragma unroll
          for (int i = 0; i < 8; i++) add8(cs, w[i]);
          if (b == 0) {
            mbar_wait(sb + B_EP, 0);
            if (!(lane & 8)) st_tagged(at<uint4>(g->cs, mine), ~lds32(sb + SM_EP) & 1, 0, 0, 0);
          }
        }
        #pragma unroll
        for (int e = 0; e < 4; e++) {
          cs[e] = ((lane & 16) ? cs[e + 4] : cs[e]) + __shfl_xor_sync(0xffffffff, (lane & 16) ? cs[e] : cs[e + 4], 16);
          cs[e] += __shfl_xor_sync(0xffffffff, cs[e], 8);
        }
        STALL(6);
        mbar_wait(sb + B_EP, 0);
        const uint32_t tm = 0u - (lds32(sb + SM_EP) & 1);
        const uint4* const gc = at<uint4>(g->cs, ((hg * 2 + ps) * 256 + lane) * 16);
        if (!(lane & 8)) st_tagged(at<uint4>(g->cs, mine), (__float_as_uint(cs[0]) & ~1u) | (tm & 1), __float_as_uint(cs[1]), __float_as_uint(cs[2]), __float_as_uint(cs[3]));

        uint4 v[9];
        int it = 0;
        uint32_t miss;
        do {
          #pragma unroll
          for (int i = 0; i < 8; i++) v[i] = ld_tagged(gc + i * 32);
          v[8] = ld_relaxed4(at<uint4>(g->stat, qt * 512 + lane * 16));
          miss = (tag_miss(v[8].x, v[8].y, tm) | tag_miss(v[8].z, v[8].w, tm)) >> 31;
          #pragma unroll
          for (int i = 0; i < 8; i += 2) miss |= tag_miss(v[i].x, v[i+1].x, tm);
        } while (__any_sync(0xffffffff, miss & 1) && ++it < MAXPOLL);
        #pragma unroll
        for (int i = 0; i < 2; i++) {
          auto sum = [](uint32_t a, uint32_t b, uint32_t c, uint32_t d) { return (__uint_as_float(a) + __uint_as_float(b)) + (__uint_as_float(c) + __uint_as_float(d)); };
          const float c0 = sum(v[i].x, v[i+2].x, v[i+4].x, v[i+6].x), c1 = sum(v[i].y, v[i+2].y, v[i+4].y, v[i+6].y);
          const float c2 = sum(v[i].z, v[i+2].z, v[i+4].z, v[i+6].z), c3 = sum(v[i].w, v[i+2].w, v[i+4].w, v[i+6].w);
          const uint32_t h0 = pack_bf16(c0, c1), h1 = pack_bf16(c2, c3), a = sb + SM_EXT + ps * 1024 + i * 512 + (lane >> 1) * 32 + (lane & 1) * 8;
          asm volatile("st.shared.v2.u32 [%0], {%1,%2};" :: "r"(a), "r"(h0), "r"(h1) : "memory");
          asm volatile("st.shared.v2.u32 [%0], {%1,%2};" :: "r"(a + 16), "r"(pack_bf16(c0 - bf_lo(h0), c1 - bf_hi(h0))), "r"(pack_bf16(c2 - bf_lo(h1), c3 - bf_hi(h1))) : "memory");
        }
        sts128(sb + SM_STAT + lane * 16, v[8].x & 0x7fffffffu, v[8].y & 0x7fffffffu, v[8].z & 0x7fffffffu, v[8].w & 0x7fffffffu);
        proxy_fence();
        __syncwarp();
        if (lane == 0) mbar_arrive(sb + B_EXT + ps * 8);
        TRACE1(2, 6 + ps);
        if (elect_one()) l2_prefetch(at<char>(ps ? P.v : P.k, ((hg * 4 + 1) * S_LEN + qt * (24 + 8 * KVPF)) * DH * 2), 6144 + 2048 * KVPF);
      }
    }
    if (warp == 1 || warp == 2) {
      int j = 0;
      const int r0 = qt * 128 + hg * 16 + (warp - 1) * 8 + (lane >> 4);
      uint32_t e = r0 * DM * 2 + (lane & 15) * 16;
      uint4 xn = ldg_nc(at<uint4>(P.x, e)), wn = ldg_nc(at<uint4>(P.wr, (lane & 15) * 16));
      #pragma unroll 1
      for (int it = 0; it < 4; it++) {
        const uint32_t st = __shfl_sync(0xffffffff, w0, (lane & 16) + it), m2 = __byte_perm(st, 0, 0x1010);
        const float rsd = rcp_fast(bf_hi(st));
        float a = 0.f;
        #pragma unroll 1
        for (int i = 0; i < 5; i++) {
          #pragma unroll 1
          do { mbar_pace(sb + B_KF + (j & 1) * 8, (j >> 1) & 1); j++; } while (j < 5 || (j >= 17 && j < 22));
          STALL(8);
          uint32_t z[4] = {xn.x, xn.y, xn.z, xn.w};
          const uint32_t ww[4] = {wn.x, wn.y, wn.z, wn.w}, en = e + (i < 4 ? 256 : (it < 3 ? 1536 : 0));
          xn = ldg_nc(at<uint4>(P.x, en)); wn = ldg_nc(at<uint4>(P.wr, (i < 4 ? i * 256 + 256 : 0) + (lane & 15) * 16));
          #pragma unroll
          for (int k = 0; k < 4; k++) {
            const uint32_t n = norm2(z[k], m2, rsd);
            const float lo = bf_lo(n), hi = bf_hi(n);
            a = fmaf(lo, bf_lo(ww[k]), fmaf(hi, bf_hi(ww[k]), a));
            z[k] = pack_bf16(lo * sigmoid_f(lo), hi * sigmoid_f(hi));
          }
          stg128(at<uint4>(g->gate, e), make_uint4(z[0], z[1], z[2], z[3]));
          e = en;
        }
        #pragma unroll
        for (int o = 8; o; o >>= 1) a += __shfl_xor_sync(0xffffffff, a, o);
        uint32_t u = pack_bf16(a, 0.f);
        if (u == 0x8000u) u = 0;
        u = (u & 0x8000u) ? (~u & 0xffffu) : (u | 0x8000u);
        if (!(lane & 15)) st_relaxed(at<uint32_t>(g->key, (r0 + it * 2) * 4), (u << 16) | (uint32_t)(0xffff - r0 - it * 2));
      }
      __syncwarp();
      if (lane == 0) flag_add_release(&g->cnt_gate.v);
      TRACE1(2, 9);
    }
    if (warp == 0) {
      const int row0 = hg * 4 * S_LEN;
      uint32_t s = 0, ph = 0;
      #pragma unroll 1
      for (int c = 3; c < 20; c++) {
        const int k = (c < 10 ? c : (c < 18 ? c - 8 : c - 18)) * 64, cb = hg * 8 + (c < 10 ? 0 : 4);
        const CUtensorMap* const tm = c < 10 ? &tmW4 : &tmW3;
        const uint32_t wb = c < 10 ? U : 12288;
        const bool wx = c < 10 || c == 15 || c == 16;
        const uint32_t bar = sb + B_WF + s * 8, dst = sb + SM_W + rank * 8192 + s * U;
        mbar_wait(bar + (B_WE - B_WF), ph);
        if (elect_one()) {
          mbar_expect_tx(bar, wx ? wb + U : wb);
          tma_load_3d_mc(dst, tm, bar, 0, k + rank * 16, cb);
          if (wx) tma_load_2d(sb + (c < 10 ? (c + 2) & 7 : c - 11) * U, &tmX, bar, c < 10 ? k : (c - 15) * 64, qt * 128);
        }
        mbar_wait(bar + (B_WE - B_WF) + 8, ph);
        if (elect_one()) {
          mbar_expect_tx(bar + 8, wb);
          tma_load_3d_mc(dst + U, tm, bar + 8, 0, k + 32 + rank * 16, cb);
        }
        s += 2;
        if (s == 6) { s = 0; ph ^= 1; }
      }
      auto kv = [&](int isv, int j) {
        const uint32_t bar = sb + B_KF + isv * 16 + (j & 1) * 8;
        mbar_expect_tx(bar, 2 * U);
        tma_load_2d_mc(sb + (isv ? SM_V + (j & 1) * 2 * U : (j & 1) * SM_K1) + rank * U, isv ? &tmV : &tmK, bar, rank * 64, row0 + kv_tile(j) * 128);
      };
      #pragma unroll 1
      for (int i = 0; i < 5; i++) {
        STALL(11);
        if (i) mbar_wait(sb + B_WE + ((0x63150 >> (4 * i)) & 7) * 8, i < 2);
        if (elect_one()) kv((i >> 1) & 1, i < 4 ? i & 1 : 2);
      }
      TRACEO(3);
      #pragma unroll 1
      for (int j = 2; j < 64; j++) {
        STALL(11);
        if (j < 63) {
          mbar_wait(sb + B_KE + (~j & 1) * 8, ((j - 1) >> 1) & 1);
          if (elect_one()) { kv(0, j + 1); if (j == 62) mbar_arrive(sb + B_ANN); }
        }
        mbar_wait(sb + B_KE + 16 + (j & 1) * 8, (~j >> 1) & 1);
        if (elect_one()) {
          kv(1, j);
          if (j + KVPF + 1 < 64) {
            const size_t o = (size_t)(row0 + kv_tile(j + KVPF + 1) * 128 + qt * 8) * DH;
            l2_prefetch(P.k + o, 2048); l2_prefetch(P.v + o, 2048);
          }
          if (j >= 40 && j < 60) l2_prefetch(j < 56 ? P.wo + (size_t)(hg * 512 + qt * 32 + (j - 40) * 2) * DM : ((j & 1) ? P.x : g->gate) + (size_t)(qt * 128 + hg * 16 + (j & 2) * 4) * DM, j < 56 ? 2 * DM * 2 : 8 * DM * 2);
        }
      }
      s = 0; ph = 1;
      #pragma unroll 1
      for (int n = 0; n < 40; n++) {
        const int st = n < 5 ? (n == 1) : n >> 2, h = n < 5 ? max(n - 1, 0) : n & 3;
        const int u = st < 2 ? 8 + st : ((hg + st - 1) & 7);
        STALL(12);
        mbar_wait(sb + (n < 6 ? B_KE + (n < 4 ? n >> 1 : 3) * 8 : B_CE + s * 8), ph);
        if (elect_one()) {
          mbar_expect_tx(sb + B_CF + s * 8, U);
          tma_load_2d_mc(sb + c_slot(s) * U + rank * 8192, &tmWO, sb + B_CF + s * 8, u * 64, hg * 512 + ((0x3120 >> (4 * h)) & 3) * 128 + rank * 64);
        }
        if (n == 3) TRACEO(4);
        if (++s == 6) { s = 0; ph ^= 1; }
      }
      mbar_wait(sb + B_GATE, 0);
      asm volatile("fence.proxy.async.global;" ::: "memory");
      #pragma unroll 1
      for (int n = 0; n < 2; n++) {
        mbar_wait(sb + B_CE + 32 + n * 8, 1);
        if (elect_one()) {
          mbar_expect_tx(sb + B_CF + 32 + n * 8, U);
          tma_load_2d(sb + (10 + n) * U, n ? &tmGate : &tmX, sb + B_CF + 32 + n * 8, hg * 64, qt * 128);
        }
      }
      {
        const uint4* const last = g->part + (size_t)((qt * 8 + hg) * 9 + 8) * 1024;
        mbar_wait(sb + B_CE + 16, 0);
        if (elect_one()) {
          mbar_expect_tx(sb + B_CF + 8, U);
          bulk_load(sb + U, last, U, sb + B_CF + 8);
        }
      }
    } else if (warp == 2) {
      #pragma unroll 1
      for (int h = 0; h < 4; h++) {
        mbar_wait(sb + B_OS + h * 8, 0);
        STALL(13);
        #pragma unroll 1
        for (int i = 0; i < (h < 3 ? 16 : 0); i++) {
          uint32_t z = 0;
          #pragma unroll
          for (int k = 0; k < 4; k++) { const uint4 v = lds128(sb + qo_slot(h) + i * 2048 + k * 512 + lane * 16); z = taint(taint(z, v.x, v.y), v.z, v.w); }
          flag_if(sb + SM_BAD + (i & 7) * 4 + h, tainted(z));
        }
        if (h == 2) {
          const uint32_t launch = lds32(sb + SM_EP);
          uint32_t* const mine = at<uint32_t>(g->near, (qt * 8 + hg) * 32 + (lane & 7) * 4);
          st_relaxed(mine, launch - 1);
          mbar_wait(sb + B_ANN, 0);
          mbar_wait(sb + B_KE, 1);
          st_relaxed(mine, launch);
          #pragma unroll 1
          for (int it = 0; __any_sync(0xffffffff, ldg32(at<uint32_t>(g->near, qp * 512 + lane * 16)) != launch) && it < MAXPOLL; it++) {}
        }
        __syncwarp();
        if (h >= 2) { proxy_fence(); if (elect_one()) mbar_arrive(sb + B_OF); }
        __syncwarp();
      }
    } else if (warp == 3 && elect_one()) {
      mbar_wait_idle(sb + B_OS + 8, 0);
      flag_wait(at<unsigned>(g->q3_done, (hg >> 1) * 128), lds32(sb + SM_EP) * 32 + qt * 2 - 30);
      asm volatile("fence.proxy.async.global;" ::: "memory");
      mbar_expect_tx(sb + B_Q3, U);
      bulk_load(sb + 5 * U, g->q3 + (qt * 8 + hg) * 1024, U, sb + B_Q3);
      mbar_wait_idle(sb + B_ANN, 0);
      flag_wait(&g->mod_done.v, lds32(sb + SM_EP) * 4);
      mbar_arrive(sb + B_GATE);
    }
    __syncwarp();
    if (warp == 1 || warp == 2) {
      #pragma unroll 1
      for (int i = 0; i < 4; i++) {
        const int r = warp * 8 - 8 + (i & 1) * 4 + (lane >> 3);
        const uint32_t e = ((qt * 128 + hg * 16 + r) * DM + (8 + (i >> 1)) * 64 + (lane & 7) * 8) * 2;
        if (!(i & 1)) bar_sync(8, 192);
        mbar_wait(sb + B_GATE, 0);
        STALL(10);
        const uint4 xr = ldg_nc(at<uint4>(P.x, e)), gr = ld_relaxed4(at<uint4>(g->gate, e)), sv = lds128(sb + SM_BAR + 1024 + r * 128 + (((lane ^ r) & 7) << 4));
        stg128(at<uint4>(P.out, e), gated(xr, sv, gr));
        if (i == 1) bar_arrive(9, 192);
      }
    }
    cluster_arrive();
    cluster_wait();
  } else {
    const int wg = wgi - 1, t = tid & 127, cw = warp - 4;
    asm volatile("setmaxnreg.inc.sync.aligned.u32 224;");
    uint32_t q[32], p[32];
    float s[64], o[64], l[2] = {0.f, 0.f};
    const uint32_t rb = __shfl_sync(0xffffffff, map_cta(sb, lane & 1), lane), wr = sb + cw * 2048, qa = __shfl_sync(0xffffffff, wr + lane * 16, lane);
    {
      uint32_t sl = 0, ph = 0, rprev = 0;
      float acc0[128], acc1[96];
      auto pair = [&](auto& acc, int pass, int i, auto mid) {
        const uint64_t a = desc(sb, ((i + 2 + 2 * pass) & 7) * 1024 + wg * 512 + doff(0, 16)), b = desc(sb, sl * 128 + doff(SM_W, 2048));
        STALL(4);
        mbar_wait(sb + B_WF + sl, ph);
        if (i == 0) TRACE(wg, 1 + pass);
        TRACEF(1, wg, 40 + pass * 20 + 2 * i);
        wg_fence();
        wgmma_ss_tb<0, 0>(acc, a, b, i > 0);
        wgmma_ss_tb<2, 512>(acc, a, b, 1);
        wg_commit();
        mbar_wait(sb + B_WF + 8 + sl, ph);
        wg_wait<1>();
        if (i > 0) release2(rprev, lane);
        TRACEF(1, wg, 41 + pass * 20 + 2 * i);
        wg_fence();
        wgmma_ss_tb<4, 1024>(acc, a, b, 1);
        wgmma_ss_tb<6, 1536>(acc, a, b, 1);
        wg_commit();
        mid();
        rprev = rb + B_WE + 8 + sl;
        sl += 16;
        if (sl == 48) { sl = 0; ph ^= 1; }
        wg_wait<1>();
        release2(rprev - 8, lane);
      };
      if (wg == 1) bar_arrive(1, 256);
      #pragma unroll 1
      for (int i = 0; i < 10; i++) {
        if (i == 9) bar_sync(1 + wg, 256);
        pair(acc0, 0, i, [] {});
      }
      mbar_wait(sb + B_EXT, 0);
      const uint32_t st0 = lds32(sb + SM_STAT + (cw * 16 + (lane >> 2)) * 4), st1 = lds32(sb + SM_STAT + (cw * 16 + 8 + (lane >> 2)) * 4);
      const uint32_t a0 = (lane & 3) ? 0u : (__byte_perm(st0, 0, 0x1010) ^ 0x80008000u), a1 = (lane & 3) ? 0u : (__byte_perm(st1, 0, 0x1010) ^ 0x80008000u);
      wg_fence();
      wgmma_rs_tb<0>(acc0, a0, a1, 0u, 0u, (uint64_t)desc_lo(sb + SM_EXT, 0) | ((uint64_t)2 << 32), 1);
      wg_commit();
      bar_arrive(1 + (wg ^ 1), 256);
      float rs[2] = {rcp_fast(bf_hi(st0)) * SCALE_LOG2E, rcp_fast(bf_hi(st1)) * SCALE_LOG2E};
      wg_wait<0>();
      fence_regs(acc0);
      release2(rprev, lane);
      #pragma unroll
      for (int i = 0; i < 32; i++) q[i] = pack_bf16(acc0[64+2*i] * rs[i & 1], acc0[64+2*i+1] * rs[i & 1]);
      fence_regs(q);
      pair(acc1, 1, 0, [&] {
        bar_sync(4 + wg, 128);
        const uint32_t one = lds32(sb + SM_ONE);
        rs[0] = __uint_as_float(__float_as_uint(rs[0]) * one); rs[1] = __uint_as_float(__float_as_uint(rs[1]) * one);
        #pragma unroll
        for (int i = 0; i < 32; i++) p[i] = pack_bf16(acc0[2*i] * rs[i & 1], acc0[2*i+1] * rs[i & 1]);
        fence_regs(p);
      });
      #pragma unroll 1
      for (int i = 1; i < 8; i++) pair(acc1, 1, i, [&] {
        #pragma unroll
        for (int e = 0; e < 8; e++) sts128_if(i == 4 + e / 2, qa + qo_slot(0) + (e >> 2) * U + (e & 3) * 512, p[4*e], p[4*e+1], p[4*e+2], p[4*e+3]);
      });
      mbar_wait(sb + B_WF, 0);
      mbar_wait(sb + B_WF + 8, 0);
      if (wg) { wg_wait<0>(); release2(rprev, lane); }
      bar_sync(1 + wg, 256);
      const uint64_t da = desc(sb, wg * 512 + 7), db = desc(sb, 7);
      static_for<0, 2>([&](auto ic) { constexpr int i = decltype(ic)::v;
        wg_fence();
        static_for<0, 4>([&](auto kc) { constexpr int k = decltype(kc)::v;
          wgmma_ss_tb<doff((4 + i) * U, 16) - 7 + k * 2, doff(SM_W + i * 2 * U, 2048) - 7 + k * 512>(acc1, da, db, 1); });
        if (i == 0) {
          wg_commit();
          mbar_wait(sb + B_WF + 16, 0);
          mbar_wait(sb + B_WF + 24, 0);
          mbar_wait(sb + B_EXT + 8, 0);
          wg_wait<1>();
          if (!wg) release2(rprev, lane);
        }
      });
      wgmma_rs_tb<0>(acc1, a0, a1, 0u, 0u, (uint64_t)desc_lo(sb + SM_EXT + 1024, 0) | ((uint64_t)2 << 32), 1);
      wg_commit();
      mbar_wait(sb + B_KF, 0);
      wg_wait<1>();
      release2(rb + B_WE + 8, lane);
      TRACE(wg, 3);
      mma_qk<0, 2>(s, q, desc(sb, 2));
      bar_arrive(1 + (wg ^ 1), 256);
      wg_wait<1>();
      fence_regs(acc1);
      release2(rb + B_WE + 24, lane);
      #pragma unroll
      for (int e = 0; e < 12; e++)
        sts128(qa + SM_QO + (e >> 2) * U + (e & 3) * 512, pack_bf16(acc1[8*e] * rs[0], acc1[8*e+1] * rs[0]), pack_bf16(acc1[8*e+2] * rs[1], acc1[8*e+3] * rs[1]),
               pack_bf16(acc1[8*e+4] * rs[0], acc1[8*e+5] * rs[0]), pack_bf16(acc1[8*e+6] * rs[1], acc1[8*e+7] * rs[1]));
      wg_wait<0>();
      fence_regs(s);
      release2(rb + B_KE, lane);
      exp_rows<0, 64>(s, l);
      #pragma unroll
      for (int i = 0; i < 32; i++) p[i] = pack_bf16(s[2*i], s[2*i+1]);
    }
    unsigned tz[3] = {0, 0, 0};
    #pragma unroll 1
    for (int j = 1; ; j += 2) {
      int ph = 0;
      #pragma unroll 1
      do {
        attn_step<1, false>(sb, rb, wr, qa, wg, lane, j, ph, s, o, p, q, l, g, tz);
        ph ^= 1; j += 2;
        if (wg < 2) attn_step<0, false>(sb, rb, wr, qa, wg, lane, j - 1, ph, s, o, p, q, l, g, tz);
      } while ((j & 15) != 15);
      if (j == 47) mbar_wait(sb + B_Q3, 0);
      attn_step<1, true>(sb, rb, wr, qa, wg, lane, j, 1, s, o, p, q, l, g, tz);
      if (j == 63) break;
      if (wg < 2) attn_step<0, true>(sb, rb, wr, qa, wg, lane, j + 1, 0, s, o, p, q, l, g, tz);
    }
    mbar_wait(sb + B_OF, 0);
    mbar_wait(sb + B_CF + wg * 8, 0);
    mbar_wait(sb + B_KF + 24, 1);
    bar_sync(1 + wg, 256);
    TRACE(wg, 4);
    mma_pv<SM_V + 2 * U, 2>(o, p, desc(sb, 2), true);
    mma_c<3>(s, sb, wg, 0, 0);
    bar_arrive(1 + (wg ^ 1), 256);
    mbar_wait(sb + B_KE + 16, 1);
    const uint32_t tag = lds32(sb + SM_EP) & 1;
    row_scale(l[0], l[1], lds32(sb + SM_ONE), sb + SM_BAD + cw * 4 + 3);
    __syncwarp();
    const uint32_t flags = lds32(sb + SM_BAD + (lane & 7) * 4);
    wg_wait<1>();
    fence_regs(o); fence_regs(p);
    release2(rb + B_KE + 24, lane);
    const uint32_t over = tainted(store_o<true>(o_addr(wr, lane) + SM_V, o, l[0], l[1]));
    if (__builtin_expect(bar_any(4 + wg, 128, __any_sync(0xffffffff, flags | over)), 0)) {
      const uint32_t bad = __shfl_sync(0xffffffff, flags, cw) | (__any_sync(0xffffffff, over) << 24);
      wg_wait<0>();
      fence_regs(s);
      redo_heads(P, sb, bad, qt * 128 + cw * 16, hg * 4);
      #pragma unroll
      for (int i = 0; i < 64; i++) s[i] = 0.f;
      __syncwarp();
      if (lane == 0) mbar_arrive(sb + B_OS + 24);
      mbar_wait(sb + B_OF, 1);
      mma_c<4>(s, sb, wg, 0, 0);
    } else if (lane == 0) mbar_arrive(sb + B_OS + 24);
    wg_wait<0>();
    release2(rb + B_CE + wg * 8, lane);
    {
      const uint4* in = at<uint4>(g->part, (((qt * 8 + hg) * 9 + wg) * 1024 + t) * 16);
      const uint32_t tm = 0u - tag;
      uint4 v[8];
      auto fetch = [&](auto half, const uint4* from) {
        #pragma unroll
        for (int i = decltype(half)::v * 4; i < decltype(half)::v * 4 + 4; i++) reload(v[i], from + i * 128);
      };
      auto verify = [&](auto half, const uint4* from) { verify4(v + decltype(half)::v * 4, from + decltype(half)::v * 512, tm); };
      int sp = 6, sl = 2 + 3 * wg, ph = 0;
      auto quarter = [&](auto site, int h, int arrive_bar) {
        STALL(2);
        if (h == 0) bar_sync(1 + wg, 256);
        mbar_wait(sb + B_CF + sl * 8, ph);
        mma_c<decltype(site)::v>(s, sb, sl, h, arrive_bar);
        if (h) { wg_wait<1>(); release2(rb + B_CE + sp * 8, lane); }
        sp = sl;
        if (++sl == 6) { sl = 0; ph ^= 1; }
      };
      auto send = [&](int st) {
        uint4* dst = at<uint4>(g->part, ((qt * 72 + st) * 1024 + (st < 2 ? hg * 128 : ((hg + st - 1) & 7) * 9216) + t) * 16);
        const uint32_t ds = st < 2 ? 9 * U : 2048;
        wg_wait<0>();
        fence_regs(s);
        TRACEF(4, wg, 106 + (st >> 1));
        release2(rb + B_CE + sp * 8, lane);
        STALL(3);
        #pragma unroll
        for (int i = 0; i < 8; i++, dst = at<uint4>(dst, ds))
          st_tagged(dst, (pack_bf16(s[8*i], s[8*i+1]) & ~1u) | tag, pack_bf16(s[8*i+2], s[8*i+3]), pack_bf16(s[8*i+4], s[8*i+5]), pack_bf16(s[8*i+6], s[8*i+7]));
        sl += st ? 4 : 3;
        if (sl >= 6) { sl -= 6; ph ^= 1; }
      };
      const uint32_t ta = ((lane >> 4) * 8 + (lane & 7)) * 128 + ((((cw & 3) * 2 + ((lane >> 3) & 1)) ^ (lane & 7)) << 4), ra = (t >> 3) * 128 + (((t & 7) ^ ((t >> 3) & 7)) << 4);
      float T[64];
      #pragma unroll
      for (int i = 0; i < 8; i++) asm volatile("mov.b64 {%0,%1}, 0;\nmov.b64 {%2,%3}, 0;" : "=r"(v[i].x), "=r"(v[i].y), "=r"(v[i].z), "=r"(v[i].w));
      TRACEF(4, wg, 112);
      bar_sync(1 + wg, 256);
      auto take = [&](auto half, int back, bool more) {
        verify(half, in - back * 1024);
        const uint4* const nx = in - (back - 1) * 1024;
        #pragma unroll
        for (int i = decltype(half)::v * 4; i < decltype(half)::v * 4 + 4; i++) { add8(T + 8 * i, v[i]); reload(v[i], nx + i * 128, more); }
      };
      #pragma unroll 1
      for (int st = wg; ; st += 2, in += 2048) {
        TRACEF(4, wg, 100 + (st >> 1));
        const bool odd5 = (st & 1) && st >= 5;
        quarter(IC<5>{}, 1, 0);
        if (odd5) take(IC<0>{}, 3, true);
        else if (st == 2) fetch(IC<0>{}, in - 2048);
        quarter(IC<6>{}, 2, 0);
        if (odd5) take(IC<1>{}, 3, true);
        else if (st == 2) fetch(IC<1>{}, in - 2048);
        if (st < 2) mbar_wait(sb + B_OF, 1);
        quarter(IC<7>{}, 3, st < 9 ? 2 - wg : 0);
        if (st < 9 && st != 4) send(st);
        if (odd5) {
          take(IC<0>{}, 2, st < 9);
          if (st == 9) bar_arrive(1, 256);
          take(IC<1>{}, 2, st < 9);
        }
        else if (st == 3) {
          fetch(IC<0>{}, in - 1024); fetch(IC<1>{}, in - 1024);
          #pragma unroll
          for (int i = 0; i < 64; i++) asm volatile("mov.b32 %0, 0;" : "+f"(T[i]));
        } else if (st == 2 || st == 4) {
          const uint4* const rows = at<uint4>(in - 3072, st == 2 ? U : 0);
          float a[8];
          #pragma unroll
          for (int i = 0; i < 8; i++) a[i] = 0.f;
          static_for<0, 2>([&](auto hf) {
            verify(hf, rows);
            #pragma unroll
            for (int i = decltype(hf)::v * 4; i < decltype(hf)::v * 4 + 4; i++) { add8(a, v[i]); reload(v[i], rows + 1024 + i * 128, st == 2); }
          });
          if (st == 4) bar_sync(9, 192);
          stsm4t(sb + SM_BAR + 1024 + ta, pack_bf16(a[0], a[1]), pack_bf16(a[2], a[3]), pack_bf16(a[4], a[5]), pack_bf16(a[6], a[7]));
          bar_arrive(8, 192);
          if (st == 4) send(4);
        }
        if (st >= 8) break;
        quarter(IC<8>{}, 0, 0);
      }
      cluster_arrive();
      TRACEF(4, wg, 113);
      wg_wait<0>();
      fence_regs(s);
      if (wg == 0) {
        mbar_wait(sb + B_CF + 32, 0);
        mbar_wait(sb + B_CF + 40, 0);
        uint4* const op = at<uint4>(P.out, ((qt * 128 + (t >> 3)) * DM + hg * 64 + (t & 7) * 8) * 2);
        bar_sync(1, 256);
        uint4 xv[8];
        #pragma unroll
        for (int i = 0; i < 8; i++) { xv[i] = lds128(sb + 10 * U + i * 2048 + ra); v[i] = lds128(sb + 11 * U + i * 2048 + ra); }
        #pragma unroll
        for (int i = 0; i < 8; i++) {
          if (!(i & 3)) bar_sync(12 + (i >> 2), 256);
          stg128(op + i * 2 * DM, gated(xv[i], lds128(sb + i * 2048 + ra), v[i]));
        }
      } else {
        TRACEF(4, wg, 110);
        mbar_wait(sb + B_CF + 8, 1);
        #pragma unroll
        for (int i = 0; i < 8; i++) v[i] = lds128(sb + U + i * 2048 + t * 16);
        #pragma unroll
        for (int i = 0; i < 64; i++) T[i] += s[i];
        fence_regs(T);
        static_for<0, 8>([&](auto ic) { constexpr int i = decltype(ic)::v;
          if (!(i & 3)) verify(IC<i / 4>{}, in - 1024);
          add8(T + 8 * i, v[i]);
          stsm4t(sb + i * 2048 + ta, pack_bf16(T[8*i], T[8*i+1]), pack_bf16(T[8*i+2], T[8*i+3]), pack_bf16(T[8*i+4], T[8*i+5]), pack_bf16(T[8*i+6], T[8*i+7]));
          if ((i & 3) == 3) bar_arrive(12 + (i >> 2), 256);
        });
      }
    }
    TRACE(wg, 6);
    cluster_wait();
  }
}

typedef CUresult (*EncodeFn)(CUtensorMap*, CUtensorMapDataType, cuuint32_t, void*, const cuuint64_t*, const cuuint64_t*, const cuuint32_t*, const cuuint32_t*,
                             CUtensorMapInterleave, CUtensorMapSwizzle, CUtensorMapL2promotion, CUtensorMapFloatOOBfill);
void make_map(EncodeFn enc, CUtensorMap* tm, const void* ptr, uint64_t inner, uint64_t outer, uint32_t box_outer, uint32_t blocks = 0) {
  cuuint64_t dims[3] = {blocks ? 64 : inner, outer, inner / 64}; cuuint64_t strides[2] = {inner * 2, 128};
  cuuint32_t box[3] = {64, box_outer, blocks}; cuuint32_t es[3] = {1, 1, 1};
  enc(tm, CU_TENSOR_MAP_DATA_TYPE_BFLOAT16, blocks ? 3 : 2, const_cast<void*>(ptr), dims, strides, box, es, CU_TENSOR_MAP_INTERLEAVE_NONE,
      CU_TENSOR_MAP_SWIZZLE_128B, CU_TENSOR_MAP_L2_PROMOTION_L2_128B, CU_TENSOR_MAP_FLOAT_OOB_FILL_NONE);
}

}

extern "C" void kernel_launch(void* const* d_in, const int* in_sizes, int n_in, void* d_out, int out_size) {
  (void)in_sizes; (void)n_in; (void)out_size;
  Params P;
  P.x = (const __nv_bfloat16*)d_in[0]; P.k = (const __nv_bfloat16*)d_in[1]; P.v = (const __nv_bfloat16*)d_in[2];
  P.wq = (const __nv_bfloat16*)d_in[3]; P.wo = (const __nv_bfloat16*)d_in[4]; P.wr = (const __nv_bfloat16*)d_in[6];
  P.out = (__nv_bfloat16*)d_out;
  cudaGetSymbolAddress((void**)&P.g, g_s);
  void* fn = nullptr; cudaDriverEntryPointQueryResult st;
  cudaGetDriverEntryPoint("cuTensorMapEncodeTiled", &fn, cudaEnableDefault, &st);
  EncodeFn enc = (EncodeFn)fn;
  CUtensorMap tmX, tmW4, tmW3, tmW1, tmK, tmV, tmWO, tmG, tmU, tmD, tmGate;
  make_map(enc, &tmGate, P.g->gate, DM, S_LEN, 128);
  make_map(enc, &tmX, P.x, DM, S_LEN, 128);
  make_map(enc, &tmW4, P.wq, NH * DH, DM, 16, 4);
  make_map(enc, &tmW3, P.wq, NH * DH, DM, 16, 3);
  make_map(enc, &tmW1, P.wq, NH * DH, DM, 128);
  make_map(enc, &tmK, P.k, DH, (uint64_t)NH * S_LEN, 128);
  make_map(enc, &tmV, P.v, DH, (uint64_t)NH * S_LEN, 128);
  make_map(enc, &tmWO, P.wo, DM, NH * DH, 64);
  make_map(enc, &tmG, d_in[7], FF, DM, 128);
  make_map(enc, &tmU, d_in[8], FF, DM, 128);
  make_map(enc, &tmD, d_in[9], DM, FF, 128);
  cudaFuncSetAttribute(fused_kernel, cudaFuncAttributeMaxDynamicSharedMemorySize, SMEM_BYTES);
  fused_kernel<<<132, 384, SMEM_BYTES, cudaStreamPerThread>>>(tmX, tmW4, tmW3, tmW1, tmK, tmV, tmWO, tmG, tmU, tmD, tmGate, P);
}
```
